```python
import torch

def _softmax(x, axis=-1):
    return torch.softmax(x, dim=axis)
def _gelu(x):
    return torch.nn.functional.gelu(x, approximate="tanh")
def _silu(x):
    return torch.nn.functional.silu(x)
def _sigmoid(x):
    return torch.sigmoid(x)
def _layernorm(x, axis=-1, eps=1e-5):
    m = x.mean(dim=axis, keepdim=True)
    v = x.var(dim=axis, keepdim=True, unbiased=False)
    return (x - m) / torch.sqrt(v + eps)
def _scatter_add(tgt, idx, src, axis=0):
    return tgt.clone().index_add_(axis, idx, src)
def _segment_sum(src, seg, n):
    out = torch.zeros((n,) + src.shape[1:], dtype=src.dtype)
    return out.index_add_(0, seg, src)
def _pad(x, pw):
    flat = tuple(v for pair in reversed(pw) for v in pair)
    return torch.nn.functional.pad(x, flat)

kernel_name = 'standalone__window_attn_swin__vision'

def setup_inputs():

    _w = (lambda a: (lambda t: t.to(torch.bfloat16) if t.is_floating_point() else t)(torch.as_tensor(a)))
    H = W = 512
    C = 192
    ws = 8
    nh = 4
    shift = ws // 2
    coords = torch.stack(torch.meshgrid(torch.arange(ws), torch.arange(ws), indexing='ij'), 0).reshape(2, -1)
    rel = coords[:, :, None] - coords[:, None, :]
    rel[0] += ws - 1
    rel[1] += ws - 1
    rel[0] *= 2 * ws - 1
    rp_idx = rel.sum(0).to(torch.int64)
    img_mask = torch.zeros((1, H, W, 1), dtype=float)
    cnt = 0
    for hs in (slice(0, H - ws), slice(H - ws, H - shift), slice(H - shift, H)):
        for vs in (slice(0, W - ws), slice(W - ws, W - shift), slice(W - shift, W)):
            img_mask[:, hs, vs, :] = cnt
            cnt += 1
    mw = img_mask.reshape(1, H // ws, ws, W // ws, ws, 1).permute(0, 1, 3, 2, 4, 5).reshape(-1, ws * ws)
    am = mw[:, :, None] - mw[:, None, :]
    attn_mask = torch.where(am != 0, -100.0, 0.0).to(float)
    return {
        "x": _w((lambda *s: torch.randn(*s, dtype=torch.bfloat16) * 1.6)(1, H, W, C)),
        "wqkv": _w((lambda *s: torch.randn(*s, dtype=torch.bfloat16) * 1.6)(C, 3 * C) * 0.02),
        "wo": _w((lambda *s: torch.randn(*s, dtype=torch.bfloat16) * 0.05)(C, C) * 0.02),
        "rpb": _w((lambda *s: torch.randn(*s, dtype=torch.bfloat16) * 0.2)((2 * ws - 1) * (2 * ws - 1), nh)),
        "rp_idx": _w(rp_idx),
        "attn_mask": _w(attn_mask),
    }

def reference(x, wqkv, wo, rpb, rp_idx, attn_mask):
    B, H, W, C = x.shape
    N = rp_idx.shape[0]
    ws = int(round(N ** 0.5))
    nh = rpb.shape[-1]
    hd = C // nh
    shift = ws // 2
    xs = torch.roll(x, (-shift, -shift), (1, 2))
    nWh = H // ws
    nWw = W // ws
    xw = (lambda x, *d: x.permute(*d))(xs.reshape(B, nWh, ws, nWw, ws, C), 0, 1, 3, 2, 4, 5).reshape(B * nWh * nWw, N, C)
    qkv = (lambda x, *d: x.permute(*d))(torch.einsum('wnc,cd->wnd', xw, wqkv).reshape(-1, N, 3, nh, hd), 2, 0, 3, 1, 4)
    q, k, v = qkv[0], qkv[1], qkv[2]
    attn = torch.einsum('whid,whjd->whij', q, k) * (hd ** -0.5)
    bias = (lambda x, *d: x.permute(*d))(rpb[rp_idx.reshape(-1)].reshape(N, N, nh), 2, 0, 1)
    attn = attn + bias[None, :, :, :]
    attn = (attn.reshape(B, nWh * nWw, nh, N, N) + attn_mask[None, :, None, :, :]).reshape(-1, nh, N, N)
    attn = _softmax(attn, axis=-1)
    out = (lambda x, *d: x.permute(*d))(torch.einsum('whij,whjd->whid', attn, v), 0, 2, 1, 3).reshape(-1, N, C)
    out = torch.einsum('wnc,cd->wnd', out, wo)
    out = (lambda x, *d: x.permute(*d))(out.reshape(B, nWh, nWw, ws, ws, C), 0, 1, 3, 2, 4, 5).reshape(B, H, W, C)
    return torch.roll(out, (shift, shift), (1, 2))
```

```cpp
#include <cuda_runtime.h>
#include <cuda_bf16.h>
#include <cuda.h>
#include <stdint.h>

namespace {

constexpr int NWIN = 4096;
constexpr int KV_WG = 0;
constexpr int PF_DIST = 4;

constexpr uint32_t OFF_WQ   = 0;
constexpr uint32_t OFF_WO   = 36864;
constexpr uint32_t OFF_X    = 73728;
constexpr uint32_t X_BYTES  = 24576;
constexpr uint32_t OFF_MASK = 122880;
constexpr uint32_t M_BYTES  = 8192;
constexpr uint32_t OFF_KV   = 139264;
constexpr uint32_t KV_BYTES = 25600;
constexpr uint32_t OFF_OIN  = 190464;
constexpr uint32_t O_BYTES  = 12288;
constexpr uint32_t OFF_BIAS = 215040;
constexpr uint32_t OFF_BAR  = 231424;
constexpr uint32_t SMEM_BYTES = OFF_BAR + 128;
constexpr uint32_t B_XFULL = 0, B_XEMPTY = 16, B_KFULL = 32, B_VFULL = 48, B_KVEMPTY = 64, B_OFULL = 80;

__device__ __forceinline__ void mma_q_init(float (&d)[48], uint64_t descA, uint64_t descB) {
  asm volatile("wgmma.mma_async.sync.aligned.m64n96k16.f32.bf16.bf16 {%0, %1, %2, %3, %4, %5, %6, %7, %8, %9, %10, %11, %12, %13, %14, %15, %16, %17, %18, %19, %20, %21, %22, %23, %24, %25, %26, %27, %28, %29, %30, %31, %32, %33, %34, %35, %36, %37, %38, %39, %40, %41, %42, %43, %44, %45, %46, %47}, "
    "%48, %49, 0, 1, 1, 0, 0;"
    : "=f"(d[0]), "=f"(d[1]), "=f"(d[2]), "=f"(d[3]), "=f"(d[4]), "=f"(d[5]), "=f"(d[6]), "=f"(d[7]), "=f"(d[8]), "=f"(d[9]), "=f"(d[10]), "=f"(d[11]), "=f"(d[12]), "=f"(d[13]), "=f"(d[14]), "=f"(d[15]), "=f"(d[16]), "=f"(d[17]), "=f"(d[18]), "=f"(d[19]), "=f"(d[20]), "=f"(d[21]), "=f"(d[22]), "=f"(d[23]), "=f"(d[24]), "=f"(d[25]), "=f"(d[26]), "=f"(d[27]), "=f"(d[28]), "=f"(d[29]), "=f"(d[30]), "=f"(d[31]), "=f"(d[32]), "=f"(d[33]), "=f"(d[34]), "=f"(d[35]), "=f"(d[36]), "=f"(d[37]), "=f"(d[38]), "=f"(d[39]), "=f"(d[40]), "=f"(d[41]), "=f"(d[42]), "=f"(d[43]), "=f"(d[44]), "=f"(d[45]), "=f"(d[46]), "=f"(d[47])
    : "l"(descA), "l"(descB));
}
__device__ __forceinline__ void mma_q(float (&d)[48], uint64_t descA, uint64_t descB) {
  asm volatile("wgmma.mma_async.sync.aligned.m64n96k16.f32.bf16.bf16 {%0, %1, %2, %3, %4, %5, %6, %7, %8, %9, %10, %11, %12, %13, %14, %15, %16, %17, %18, %19, %20, %21, %22, %23, %24, %25, %26, %27, %28, %29, %30, %31, %32, %33, %34, %35, %36, %37, %38, %39, %40, %41, %42, %43, %44, %45, %46, %47}, "
    "%48, %49, 1, 1, 1, 0, 0;"
    : "+f"(d[0]), "+f"(d[1]), "+f"(d[2]), "+f"(d[3]), "+f"(d[4]), "+f"(d[5]), "+f"(d[6]), "+f"(d[7]), "+f"(d[8]), "+f"(d[9]), "+f"(d[10]), "+f"(d[11]), "+f"(d[12]), "+f"(d[13]), "+f"(d[14]), "+f"(d[15]), "+f"(d[16]), "+f"(d[17]), "+f"(d[18]), "+f"(d[19]), "+f"(d[20]), "+f"(d[21]), "+f"(d[22]), "+f"(d[23]), "+f"(d[24]), "+f"(d[25]), "+f"(d[26]), "+f"(d[27]), "+f"(d[28]), "+f"(d[29]), "+f"(d[30]), "+f"(d[31]), "+f"(d[32]), "+f"(d[33]), "+f"(d[34]), "+f"(d[35]), "+f"(d[36]), "+f"(d[37]), "+f"(d[38]), "+f"(d[39]), "+f"(d[40]), "+f"(d[41]), "+f"(d[42]), "+f"(d[43]), "+f"(d[44]), "+f"(d[45]), "+f"(d[46]), "+f"(d[47])
    : "l"(descA), "l"(descB));
}
__device__ __forceinline__ void mma_kv_init(float (&d)[32], uint32_t a0, uint32_t a1, uint32_t a2, uint32_t a3, uint64_t descB) {
  asm volatile("wgmma.mma_async.sync.aligned.m64n64k16.f32.bf16.bf16 {%0, %1, %2, %3, %4, %5, %6, %7, %8, %9, %10, %11, %12, %13, %14, %15, %16, %17, %18, %19, %20, %21, %22, %23, %24, %25, %26, %27, %28, %29, %30, %31}, "
    "{%32, %33, %34, %35}, %36, 0, 1, 1, 0;"
    : "=f"(d[0]), "=f"(d[1]), "=f"(d[2]), "=f"(d[3]), "=f"(d[4]), "=f"(d[5]), "=f"(d[6]), "=f"(d[7]), "=f"(d[8]), "=f"(d[9]), "=f"(d[10]), "=f"(d[11]), "=f"(d[12]), "=f"(d[13]), "=f"(d[14]), "=f"(d[15]), "=f"(d[16]), "=f"(d[17]), "=f"(d[18]), "=f"(d[19]), "=f"(d[20]), "=f"(d[21]), "=f"(d[22]), "=f"(d[23]), "=f"(d[24]), "=f"(d[25]), "=f"(d[26]), "=f"(d[27]), "=f"(d[28]), "=f"(d[29]), "=f"(d[30]), "=f"(d[31])
    : "r"(a0), "r"(a1), "r"(a2), "r"(a3), "l"(descB));
}
__device__ __forceinline__ void mma_kv(float (&d)[32], uint32_t a0, uint32_t a1, uint32_t a2, uint32_t a3, uint64_t descB) {
  asm volatile("wgmma.mma_async.sync.aligned.m64n64k16.f32.bf16.bf16 {%0, %1, %2, %3, %4, %5, %6, %7, %8, %9, %10, %11, %12, %13, %14, %15, %16, %17, %18, %19, %20, %21, %22, %23, %24, %25, %26, %27, %28, %29, %30, %31}, "
    "{%32, %33, %34, %35}, %36, 1, 1, 1, 0;"
    : "+f"(d[0]), "+f"(d[1]), "+f"(d[2]), "+f"(d[3]), "+f"(d[4]), "+f"(d[5]), "+f"(d[6]), "+f"(d[7]), "+f"(d[8]), "+f"(d[9]), "+f"(d[10]), "+f"(d[11]), "+f"(d[12]), "+f"(d[13]), "+f"(d[14]), "+f"(d[15]), "+f"(d[16]), "+f"(d[17]), "+f"(d[18]), "+f"(d[19]), "+f"(d[20]), "+f"(d[21]), "+f"(d[22]), "+f"(d[23]), "+f"(d[24]), "+f"(d[25]), "+f"(d[26]), "+f"(d[27]), "+f"(d[28]), "+f"(d[29]), "+f"(d[30]), "+f"(d[31])
    : "r"(a0), "r"(a1), "r"(a2), "r"(a3), "l"(descB));
}
__device__ __forceinline__ void mma_s(float (&d)[32], uint32_t a0, uint32_t a1, uint32_t a2, uint32_t a3, uint64_t descB) {
  asm volatile("wgmma.mma_async.sync.aligned.m64n64k16.f32.bf16.bf16 {%0, %1, %2, %3, %4, %5, %6, %7, %8, %9, %10, %11, %12, %13, %14, %15, %16, %17, %18, %19, %20, %21, %22, %23, %24, %25, %26, %27, %28, %29, %30, %31}, "
    "{%32, %33, %34, %35}, %36, 1, 1, 1, 1;"
    : "+f"(d[0]), "+f"(d[1]), "+f"(d[2]), "+f"(d[3]), "+f"(d[4]), "+f"(d[5]), "+f"(d[6]), "+f"(d[7]), "+f"(d[8]), "+f"(d[9]), "+f"(d[10]), "+f"(d[11]), "+f"(d[12]), "+f"(d[13]), "+f"(d[14]), "+f"(d[15]), "+f"(d[16]), "+f"(d[17]), "+f"(d[18]), "+f"(d[19]), "+f"(d[20]), "+f"(d[21]), "+f"(d[22]), "+f"(d[23]), "+f"(d[24]), "+f"(d[25]), "+f"(d[26]), "+f"(d[27]), "+f"(d[28]), "+f"(d[29]), "+f"(d[30]), "+f"(d[31])
    : "r"(a0), "r"(a1), "r"(a2), "r"(a3), "l"(descB));
}
__device__ __forceinline__ void mma_p_init(float (&d)[28], uint32_t a0, uint32_t a1, uint32_t a2, uint32_t a3, uint64_t descB) {
  asm volatile("wgmma.mma_async.sync.aligned.m64n56k16.f32.bf16.bf16 {%0, %1, %2, %3, %4, %5, %6, %7, %8, %9, %10, %11, %12, %13, %14, %15, %16, %17, %18, %19, %20, %21, %22, %23, %24, %25, %26, %27}, "
    "{%28, %29, %30, %31}, %32, 0, 1, 1, 0;"
    : "=f"(d[0]), "=f"(d[1]), "=f"(d[2]), "=f"(d[3]), "=f"(d[4]), "=f"(d[5]), "=f"(d[6]), "=f"(d[7]), "=f"(d[8]), "=f"(d[9]), "=f"(d[10]), "=f"(d[11]), "=f"(d[12]), "=f"(d[13]), "=f"(d[14]), "=f"(d[15]), "=f"(d[16]), "=f"(d[17]), "=f"(d[18]), "=f"(d[19]), "=f"(d[20]), "=f"(d[21]), "=f"(d[22]), "=f"(d[23]), "=f"(d[24]), "=f"(d[25]), "=f"(d[26]), "=f"(d[27])
    : "r"(a0), "r"(a1), "r"(a2), "r"(a3), "l"(descB));
}
__device__ __forceinline__ void mma_p(float (&d)[28], uint32_t a0, uint32_t a1, uint32_t a2, uint32_t a3, uint64_t descB) {
  asm volatile("wgmma.mma_async.sync.aligned.m64n56k16.f32.bf16.bf16 {%0, %1, %2, %3, %4, %5, %6, %7, %8, %9, %10, %11, %12, %13, %14, %15, %16, %17, %18, %19, %20, %21, %22, %23, %24, %25, %26, %27}, "
    "{%28, %29, %30, %31}, %32, 1, 1, 1, 0;"
    : "+f"(d[0]), "+f"(d[1]), "+f"(d[2]), "+f"(d[3]), "+f"(d[4]), "+f"(d[5]), "+f"(d[6]), "+f"(d[7]), "+f"(d[8]), "+f"(d[9]), "+f"(d[10]), "+f"(d[11]), "+f"(d[12]), "+f"(d[13]), "+f"(d[14]), "+f"(d[15]), "+f"(d[16]), "+f"(d[17]), "+f"(d[18]), "+f"(d[19]), "+f"(d[20]), "+f"(d[21]), "+f"(d[22]), "+f"(d[23]), "+f"(d[24]), "+f"(d[25]), "+f"(d[26]), "+f"(d[27])
    : "r"(a0), "r"(a1), "r"(a2), "r"(a3), "l"(descB));
}
__device__ __forceinline__ void mma_o_init(float (&d)[48], uint32_t a0, uint32_t a1, uint32_t a2, uint32_t a3, uint64_t descB) {
  asm volatile("wgmma.mma_async.sync.aligned.m64n96k16.f32.bf16.bf16 {%0, %1, %2, %3, %4, %5, %6, %7, %8, %9, %10, %11, %12, %13, %14, %15, %16, %17, %18, %19, %20, %21, %22, %23, %24, %25, %26, %27, %28, %29, %30, %31, %32, %33, %34, %35, %36, %37, %38, %39, %40, %41, %42, %43, %44, %45, %46, %47}, "
    "{%48, %49, %50, %51}, %52, 0, 1, 1, 0;"
    : "=f"(d[0]), "=f"(d[1]), "=f"(d[2]), "=f"(d[3]), "=f"(d[4]), "=f"(d[5]), "=f"(d[6]), "=f"(d[7]), "=f"(d[8]), "=f"(d[9]), "=f"(d[10]), "=f"(d[11]), "=f"(d[12]), "=f"(d[13]), "=f"(d[14]), "=f"(d[15]), "=f"(d[16]), "=f"(d[17]), "=f"(d[18]), "=f"(d[19]), "=f"(d[20]), "=f"(d[21]), "=f"(d[22]), "=f"(d[23]), "=f"(d[24]), "=f"(d[25]), "=f"(d[26]), "=f"(d[27]), "=f"(d[28]), "=f"(d[29]), "=f"(d[30]), "=f"(d[31]), "=f"(d[32]), "=f"(d[33]), "=f"(d[34]), "=f"(d[35]), "=f"(d[36]), "=f"(d[37]), "=f"(d[38]), "=f"(d[39]), "=f"(d[40]), "=f"(d[41]), "=f"(d[42]), "=f"(d[43]), "=f"(d[44]), "=f"(d[45]), "=f"(d[46]), "=f"(d[47])
    : "r"(a0), "r"(a1), "r"(a2), "r"(a3), "l"(descB));
}
__device__ __forceinline__ void mma_o(float (&d)[48], uint32_t a0, uint32_t a1, uint32_t a2, uint32_t a3, uint64_t descB) {
  asm volatile("wgmma.mma_async.sync.aligned.m64n96k16.f32.bf16.bf16 {%0, %1, %2, %3, %4, %5, %6, %7, %8, %9, %10, %11, %12, %13, %14, %15, %16, %17, %18, %19, %20, %21, %22, %23, %24, %25, %26, %27, %28, %29, %30, %31, %32, %33, %34, %35, %36, %37, %38, %39, %40, %41, %42, %43, %44, %45, %46, %47}, "
    "{%48, %49, %50, %51}, %52, 1, 1, 1, 0;"
    : "+f"(d[0]), "+f"(d[1]), "+f"(d[2]), "+f"(d[3]), "+f"(d[4]), "+f"(d[5]), "+f"(d[6]), "+f"(d[7]), "+f"(d[8]), "+f"(d[9]), "+f"(d[10]), "+f"(d[11]), "+f"(d[12]), "+f"(d[13]), "+f"(d[14]), "+f"(d[15]), "+f"(d[16]), "+f"(d[17]), "+f"(d[18]), "+f"(d[19]), "+f"(d[20]), "+f"(d[21]), "+f"(d[22]), "+f"(d[23]), "+f"(d[24]), "+f"(d[25]), "+f"(d[26]), "+f"(d[27]), "+f"(d[28]), "+f"(d[29]), "+f"(d[30]), "+f"(d[31]), "+f"(d[32]), "+f"(d[33]), "+f"(d[34]), "+f"(d[35]), "+f"(d[36]), "+f"(d[37]), "+f"(d[38]), "+f"(d[39]), "+f"(d[40]), "+f"(d[41]), "+f"(d[42]), "+f"(d[43]), "+f"(d[44]), "+f"(d[45]), "+f"(d[46]), "+f"(d[47])
    : "r"(a0), "r"(a1), "r"(a2), "r"(a3), "l"(descB));
}

__device__ __forceinline__ void wg_fence() { asm volatile("wgmma.fence.sync.aligned;" ::: "memory"); }
__device__ __forceinline__ void wg_commit() { asm volatile("wgmma.commit_group.sync.aligned;" ::: "memory"); }
template <int N> __device__ __forceinline__ void wg_wait() { asm volatile("wgmma.wait_group.sync.aligned %0;" ::"n"(N) : "memory"); }
template <int N> __device__ __forceinline__ void pin(float (&d)[N]) {
#pragma unroll
  for (int i = 0; i < N; i++) asm volatile("" : "+f"(d[i])::"memory");
}
template <int N> __device__ __forceinline__ void pin(uint32_t (&d)[N]) {
#pragma unroll
  for (int i = 0; i < N; i++) asm volatile("" : "+r"(d[i])::"memory");
}
__device__ __forceinline__ uint64_t desc128(uint32_t lo16, uint32_t sbo) {
  uint32_t hi = (sbo >> 4) | (1u << 30);
  uint32_t lo = lo16 | (1u << 16);
  return ((uint64_t)hi << 32) | lo;
}
__device__ __forceinline__ uint32_t pack_bf16(float lo, float hi) {
  uint32_t r;
  asm("cvt.rn.bf16x2.f32 %0, %1, %2;" : "=r"(r) : "f"(hi), "f"(lo));
  return r;
}
__device__ __forceinline__ float ex2(float x) {
  float r;
  asm("ex2.approx.ftz.f32 %0, %1;" : "=f"(r) : "f"(x));
  return r;
}
__device__ __forceinline__ float rcp(float x) {
  float r;
  asm("rcp.approx.ftz.f32 %0, %1;" : "=f"(r) : "f"(x));
  return r;
}
__device__ __forceinline__ void mbar_init(uint32_t bar, uint32_t cnt) {
  asm volatile("mbarrier.init.shared::cta.b64 [%0], %1;" ::"r"(bar), "r"(cnt) : "memory");
}
__device__ __forceinline__ void mbar_wait(uint32_t bar, uint32_t parity) {
  asm volatile(
      "{\n.reg .pred p;\n.reg .u32 n;\n"
      "mbarrier.try_wait.parity.shared::cta.b64 p, [%0], %1;\n"
      "@p bra DONE;\n"
      "mov.u32 n, 0;\n"
      "LOOP:\n"
      "mbarrier.try_wait.parity.shared::cta.b64 p, [%0], %1;\n"
      "@p bra DONE;\n"
      "add.u32 n, n, 1;\n"
      "setp.lt.u32 p, n, 0x400000;\n"
      "@p bra LOOP;\n"
      "trap;\n"
      "DONE:\n}\n" ::"r"(bar), "r"(parity)
      : "memory");
}
__device__ __forceinline__ void mbar_arrive(uint32_t bar) {
  asm volatile("mbarrier.arrive.shared::cta.b64 _, [%0];" ::"r"(bar) : "memory");
}
__device__ __forceinline__ void mbar_arrive_cluster(uint32_t bar) {
  asm volatile("mbarrier.arrive.shared::cluster.b64 _, [%0];" ::"r"(bar) : "memory");
}
__device__ __forceinline__ void mbar_expect_tx(uint32_t bar, uint32_t bytes) {
  asm volatile("mbarrier.arrive.expect_tx.shared::cta.b64 _, [%0], %1;" ::"r"(bar), "r"(bytes) : "memory");
}
__device__ __forceinline__ uint32_t mapa(uint32_t addr, uint32_t rank) {
  uint32_t r;
  asm("mapa.shared::cluster.u32 %0, %1, %2;" : "=r"(r) : "r"(addr), "r"(rank));
  return r;
}
__device__ __forceinline__ void fence_async() { asm volatile("fence.proxy.async.shared::cta;" ::: "memory"); }
__device__ __forceinline__ void stsm4(uint32_t addr, uint32_t r0, uint32_t r1, uint32_t r2, uint32_t r3) {
  asm volatile("stmatrix.sync.aligned.m8n8.x4.shared.b16 [%0], {%1,%2,%3,%4};" ::"r"(addr), "r"(r0), "r"(r1), "r"(r2), "r"(r3) : "memory");
}
__device__ __forceinline__ void stsm4t(uint32_t addr, uint4 v) {
  asm volatile("stmatrix.sync.aligned.m8n8.x4.trans.shared.b16 [%0], {%1,%2,%3,%4};" ::"r"(addr), "r"(v.x), "r"(v.y), "r"(v.z), "r"(v.w) : "memory");
}
__device__ __forceinline__ void lds128(uint32_t addr, uint32_t& r0, uint32_t& r1, uint32_t& r2, uint32_t& r3) {
  asm volatile("ld.shared.v4.b32 {%0,%1,%2,%3}, [%4];" : "=r"(r0), "=r"(r1), "=r"(r2), "=r"(r3) : "r"(addr) : "memory");
}
__device__ __forceinline__ uint32_t movm(uint32_t a) {
  uint32_t d;
  asm volatile("movmatrix.sync.aligned.m8n8.trans.b16 %0, %1;" : "=r"(d) : "r"(a));
  return d;
}
__device__ __forceinline__ void tma5_mc(uint32_t dst, const CUtensorMap* tm, uint32_t bar, int c2, int c4) {
  asm volatile(
      "cp.async.bulk.tensor.5d.shared::cluster.global.mbarrier::complete_tx::bytes.multicast::cluster "
      "[%0], [%1, {0, 0, %3, 0, %4}], [%2], %5;" ::"r"(dst), "l"(tm), "r"(bar), "r"(c2), "r"(c4), "h"((uint16_t)3)
      : "memory");
}
__device__ __forceinline__ void tma5_pf(const CUtensorMap* tm, int c2, int c4) {
  asm volatile("cp.async.bulk.prefetch.tensor.5d.L2.global [%0, {0, 0, %1, 0, %2}];" ::"l"(tm), "r"(c2), "r"(c4) : "memory");
}
__device__ __forceinline__ void load_window(const CUtensorMap* tx, const CUtensorMap* tmk, uint32_t xs, uint32_t ms,
                                            uint32_t bar, int win, int rank) {
  int y0 = ((win >> 6) * 8 + 4 + 4 * rank) & 511;
  int xh = (win & 63) * 4 + 2;
  mbar_expect_tx(bar, X_BYTES + M_BYTES);
  tma5_mc(xs + rank * 12288, tx, bar, y0, xh);
  tma5_mc(xs + rank * 12288 + 6144, tx, bar, y0, (xh + 2) & 255);
  tma5_mc(ms + rank * 4096, tmk, bar, 0, 2 * win + rank);
}
__device__ __forceinline__ void prefetch_window(const CUtensorMap* tx, const CUtensorMap* tmk, int win, int rank) {
  int y0 = ((win >> 6) * 8 + 4 + 4 * rank) & 511;
  int xh = (win & 63) * 4 + 2;
  tma5_pf(tx, y0, xh);
  tma5_pf(tx, y0, (xh + 2) & 255);
  tma5_pf(tmk, 0, 2 * win + rank);
}
__device__ __forceinline__ int sigma16(int rho) { return 4 * ((rho & 7) >> 1) + 2 * (rho >> 3) + (rho & 1); }

constexpr float SQRT_HD = 6.92820323027551f;
constexpr float SM_C = 1.4426950408889634f / SQRT_HD;

__device__ __forceinline__ void s_init(float (&s)[32], const uint32_t (&mk)[16], uint32_t bias_addr) {
  uint32_t b[16];
#pragma unroll
  for (int c = 0; c < 4; c++) lds128(bias_addr + c * 2048, b[4 * c], b[4 * c + 1], b[4 * c + 2], b[4 * c + 3]);
#pragma unroll
  for (int i = 0; i < 16; i++) {
    uint32_t t;
    asm("fma.rn.bf16x2 %0, %1, %2, %3;" : "=r"(t) : "r"(mk[i]), "r"(0x40DE40DEu), "r"(b[i]));
    s[4 * (i & 7) + 2 * (i >> 3)] = __uint_as_float(t << 16);
    s[4 * (i & 7) + 2 * (i >> 3) + 1] = __uint_as_float(t & 0xffff0000u);
  }
}
__device__ __forceinline__ void softmax(float (&s)[32], uint32_t (&p)[16]) {
  float m0 = fmaxf(s[0], s[1]), m1 = fmaxf(s[2], s[3]);
#pragma unroll
  for (int j = 1; j < 8; j++) {
    m0 = fmaxf(m0, fmaxf(s[4 * j], s[4 * j + 1]));
    m1 = fmaxf(m1, fmaxf(s[4 * j + 2], s[4 * j + 3]));
  }
  m0 = fmaxf(m0, __shfl_xor_sync(0xffffffffu, m0, 1));
  m1 = fmaxf(m1, __shfl_xor_sync(0xffffffffu, m1, 1));
  m0 = fmaxf(m0, __shfl_xor_sync(0xffffffffu, m0, 2));
  m1 = fmaxf(m1, __shfl_xor_sync(0xffffffffu, m1, 2));
  m0 *= -SM_C;
  m1 *= -SM_C;
#pragma unroll
  for (int i = 0; i < 16; i++) {
    float m = (i & 1) ? m1 : m0;
    p[i] = pack_bf16(ex2(fmaf(s[2 * i], SM_C, m)), ex2(fmaf(s[2 * i + 1], SM_C, m)));
  }
}

__global__ void __cluster_dims__(2, 1, 1) __launch_bounds__(384, 1)
swin_attn_kernel(const __grid_constant__ CUtensorMap tm_x, const __grid_constant__ CUtensorMap tm_mask,
                 const __nv_bfloat16* __restrict__ wqkv, const __nv_bfloat16* __restrict__ wo,
                 const __nv_bfloat16* __restrict__ rpb, const int* __restrict__ rp_idx,
                 __nv_bfloat16* __restrict__ out) {
  extern __shared__ __align__(1024) uint8_t smem_raw[];
  const uint32_t sb = (uint32_t)__cvta_generic_to_shared(smem_raw);
  const uint32_t sb16 = (sb & 0x3FFFF) >> 4;
  const int tid = threadIdx.x;
  const int wg = __shfl_sync(0xffffffffu, tid >> 7, 0);
  const int warp = __shfl_sync(0xffffffffu, (tid >> 5) & 3, 0);
  const int lane = tid & 31;
  const int g = lane >> 2, q = lane & 3;
  const int rank = blockIdx.x & 1;
  const int cl = blockIdx.x >> 1;
  const int ncl = gridDim.x >> 1;
  const int nwin = (NWIN - cl + ncl - 1) / ncl;
  const uint32_t bars = sb + OFF_BAR;

  if (tid == 0) {
    if (sb & 1023) __trap();
#pragma unroll
    for (int a = 0; a < 2; a++) {
      mbar_init(bars + B_XFULL + 8 * a, 1);
      mbar_init(bars + B_XEMPTY + 8 * a, 16);
      mbar_init(bars + B_KFULL + 8 * a, 4);
      mbar_init(bars + B_VFULL + 8 * a, 4);
      mbar_init(bars + B_KVEMPTY + 8 * a, 4);
      mbar_init(bars + B_OFULL + 8 * a, 1);
    }
    asm volatile("fence.mbarrier_init.release.cluster;" ::: "memory");
    for (int i = 0; i < PF_DIST && i < nwin; i++) prefetch_window(&tm_x, &tm_mask, cl + i * ncl, rank);
  }
  __syncwarp();
  asm volatile("barrier.cluster.arrive.aligned;" ::: "memory");

  if (wg == KV_WG) {
    asm volatile("setmaxnreg.inc.sync.aligned.u32 216;");
    uint32_t w[3][48];
#pragma unroll
    for (int s = 0; s < 3; s++) {
      int G = 4 * s + warp;
      int col0 = (G < 6 ? 192 + 16 * G : 384 + 16 * (G - 6)) + 96 * rank + 4 * q;
      const __nv_bfloat16* src = wqkv + g * 576 + col0;
#pragma unroll
      for (int k8 = 0; k8 < 24; k8++) {
        uint2 v = __ldg(reinterpret_cast<const uint2*>(src + k8 * 8 * 576));
        w[s][2 * k8] = v.x;
        w[s][2 * k8 + 1] = v.y;
      }
    }
#pragma unroll
    for (int s = 0; s < 3; s++)
#pragma unroll
      for (int i = 0; i < 48; i++) w[s][i] = movm(w[s][i]);

    const uint32_t st0 = sb + OFF_KV + (16 * warp + (lane & 15)) * 128 + (((lane >> 4) ^ (lane & 7)) << 4);
    const uint32_t xe_addr = mapa(bars + B_XEMPTY, lane & 1);
    asm volatile("barrier.cluster.wait.aligned;" ::: "memory");

    for (int i = 0; i < nwin; i++) {
      const int a = i & 1;
      const uint32_t ph = (i >> 1) & 1;
      const uint32_t xd = sb16 + ((OFF_X + a * X_BYTES) >> 4);
      uint32_t st = st0 + a * KV_BYTES;
      mbar_wait(bars + B_XFULL + 8 * a, ph);
#pragma unroll
      for (int s = 0; s < 3; s++) {
        float acc[32];
        wg_fence();
#pragma unroll
        for (int ks = 0; ks < 12; ks++) {
          uint64_t db = desc128(xd + (((ks >> 2) * 1024 + (ks & 3) * 32) >> 4), 3072);
          if (ks == 0) mma_kv_init(acc, w[s][0], w[s][1], w[s][2], w[s][3], db);
          else mma_kv(acc, w[s][4 * ks], w[s][4 * ks + 1], w[s][4 * ks + 2], w[s][4 * ks + 3], db);
        }
        wg_commit();
        wg_wait<0>();
        pin(acc);
        if (s == 2 && lane < 2) mbar_arrive_cluster(xe_addr + 8 * a);
        if (s == 0) mbar_wait(bars + B_KVEMPTY + 8 * a, ph ^ 1);
        if (s == 2 && warp > 0) st += 1024;
#pragma unroll
        for (int jj = 0; jj < 4; jj++) {
          stsm4((st ^ (jj << 5)) + s * 8192, pack_bf16(acc[8 * jj], acc[8 * jj + 1]), pack_bf16(acc[8 * jj + 2], acc[8 * jj + 3]),
                pack_bf16(acc[8 * jj + 4], acc[8 * jj + 5]), pack_bf16(acc[8 * jj + 6], acc[8 * jj + 7]));
        }
        if (s >= 1) {
          fence_async();
          __syncwarp();
          if (lane == 0) mbar_arrive(bars + (s == 1 ? B_KFULL : B_VFULL) + 8 * a);
        }
      }
    }
  } else {
    asm volatile("setmaxnreg.dec.sync.aligned.u32 144;");
    const int a = wg - (KV_WG == 0 ? 1 : 0);
    const int t128 = tid & 127;
    const uint32_t xs = sb + OFF_X + a * X_BYTES, ms = sb + OFF_MASK + a * M_BYTES;
    const uint32_t bar = bars + 8 * a;
    {
      uint4 v[18];
      const int i4 = lane >> 3, j8 = lane & 7;
#pragma unroll
      for (int it = 0; it < 18; it++) {
        int m = warp * 6 + it / 3, nb = it % 3;
        int k = 8 * m + g;
        const __nv_bfloat16* src;
        if (a == 0) {
          src = wqkv + k * 576;
        } else {
          int half = k >= 96, t = k - 96 * half;
          src = wo + (96 * (rank ^ half) + (t & ~15) + sigma16(t & 15)) * 192;
        }
        v[it] = __ldg(reinterpret_cast<const uint4*>(src + 96 * rank + 32 * nb + 8 * q));
      }
      int nl = a == 0 ? 16 * (j8 >> 2) + 8 * (i4 & 1) + 4 * ((j8 >> 1) & 1) + 2 * (i4 >> 1) + (j8 & 1) : lane;
#pragma unroll
      for (int it = 0; it < 18; it++) {
        int m = warp * 6 + it / 3, nb = it % 3;
        int n = 32 * nb + nl;
        stsm4t(sb + OFF_WQ + a * 36864 + (m >> 3) * 12288 + n * 128 + (((m & 7) ^ (n & 7)) << 4), v[it]);
      }
      asm volatile("st.shared.v2.b32 [%0], {%1,%1};" ::"r"(sb + OFF_KV + a * KV_BYTES + 144 * 128 + t128 * 8), "r"(0x3F803F80u) : "memory");
    }
    asm volatile("barrier.cluster.wait.aligned;" ::: "memory");
    if (t128 == 0 && a < nwin) load_window(&tm_x, &tm_mask, xs, ms, bar + B_XFULL, cl + a * ncl, rank);

    const int ty = 4 * (warp >> 1) + (g >> 1), tx = 4 * (warp & 1) + (g & 1);
    const uint32_t bias_addr = sb + OFF_BIAS + t128 * 16;
#pragma unroll
    for (int c4 = 0; c4 < 2; c4++) {
      const int4* ip = reinterpret_cast<const int4*>(rp_idx + (ty * 8 + tx + 2 * a) * 64 + 8 * (q + 4 * c4));
      int4 i0 = __ldg(ip), i1 = __ldg(ip + 1);
      int id[8] = {i0.x, i0.y, i0.z, i0.w, i1.x, i1.y, i1.z, i1.w};
      uint32_t bias0[4], bias1[4];
#pragma unroll
      for (int jj = 0; jj < 4; jj++) {
        uint32_t b0 = __ldg(reinterpret_cast<const uint32_t*>(rpb) + id[2 * jj] * 2 + rank);
        uint32_t b1 = __ldg(reinterpret_cast<const uint32_t*>(rpb) + id[2 * jj + 1] * 2 + rank);
        bias0[jj] = pack_bf16(__uint_as_float(b0 << 16) * SQRT_HD, __uint_as_float(b1 << 16) * SQRT_HD);
        bias1[jj] = pack_bf16(__uint_as_float(b0 & 0xffff0000u) * SQRT_HD, __uint_as_float(b1 & 0xffff0000u) * SQRT_HD);
      }
      asm volatile("st.shared.v4.b32 [%0], {%1,%2,%3,%4};" ::"r"(bias_addr + (2 * a + c4) * 2048), "r"(bias0[0]), "r"(bias0[1]), "r"(bias0[2]), "r"(bias0[3]) : "memory");
      asm volatile("st.shared.v4.b32 [%0], {%1,%2,%3,%4};" ::"r"(bias_addr + 8192 + (2 * a + c4) * 2048), "r"(bias1[0]), "r"(bias1[1]), "r"(bias1[2]), "r"(bias1[3]) : "memory");
    }
    fence_async();
    asm volatile("bar.sync 1, 256;" ::: "memory");

    const int mrow = 16 * warp + (g >> 1) + 4 * (g & 1);
    const uint32_t mk_addr = ms + mrow * 128 + ((q ^ (mrow & 7)) << 4);
    const uint32_t oin = sb + OFF_OIN + a * O_BYTES + t128 * 16;
    const uint32_t oin_rem = mapa(oin, rank ^ 1);
    const uint32_t ofull_rem = mapa(bar + B_OFULL, rank ^ 1);
    const uint32_t xe_addr = mapa(bar + B_XEMPTY, lane & 1);
    const uint32_t xd = sb16 + ((OFF_X + a * X_BYTES) >> 4);
    const uint32_t kd = sb16 + ((OFF_KV + a * KV_BYTES) >> 4);
    char* outp = reinterpret_cast<char*>(out) + rank * 192 + q * 16;

    uint32_t ph = 0;
    for (int i = a; i < nwin; i += 2, ph ^= 1) {
      const int win = cl + i * ncl;
      mbar_wait(bar + B_XFULL, ph);
      float qa[48];
      wg_fence();
#pragma unroll
      for (int ks = 0; ks < 12; ks++) {
        uint64_t da = desc128(xd + (((ks >> 2) * 1024 + (ks & 3) * 32) >> 4), 3072);
        uint64_t db = desc128(sb16 + ((OFF_WQ + (ks >> 2) * 12288 + (ks & 3) * 32) >> 4), 1024);
        if (ks == 0) mma_q_init(qa, da, db);
        else mma_q(qa, da, db);
      }
      wg_commit();
      uint32_t mk[16];
      lds128(mk_addr, mk[0], mk[1], mk[2], mk[3]);
      lds128(mk_addr ^ 64, mk[4], mk[5], mk[6], mk[7]);
      lds128(mk_addr + 1024, mk[8], mk[9], mk[10], mk[11]);
      lds128((mk_addr ^ 64) + 1024, mk[12], mk[13], mk[14], mk[15]);
      float s0[32], s1[32];
      s_init(s0, mk, bias_addr);
      pin(s0);
      wg_wait<0>();
      pin(qa);
      if (lane < 2) mbar_arrive_cluster(xe_addr);
      if (t128 == 0) mbar_expect_tx(bar + B_OFULL, O_BYTES);
      uint32_t qf[24];
#pragma unroll
      for (int j = 0; j < 24; j++) qf[j] = pack_bf16(qa[2 * j], qa[2 * j + 1]);
      s_init(s1, mk, bias_addr + 8192);
      pin(qf);
      pin(s1);
      mbar_wait(bar + B_KFULL, ph);
      wg_fence();
#pragma unroll
      for (int ks = 0; ks < 3; ks++)
        mma_s(s0, qf[4 * ks], qf[4 * ks + 1], qf[4 * ks + 2], qf[4 * ks + 3], desc128(kd + ((ks * 2048) >> 4), 1024));
      wg_commit();
#pragma unroll
      for (int ks = 3; ks < 6; ks++)
        mma_s(s1, qf[4 * ks], qf[4 * ks + 1], qf[4 * ks + 2], qf[4 * ks + 3], desc128(kd + ((ks * 2048) >> 4), 1024));
      wg_commit();
      wg_wait<1>();
      pin(s0);
      uint32_t p0[16], p1[16];
      softmax(s0, p0);
      pin(p0);
      float o0[28], o1[28];
      mbar_wait(bar + B_VFULL, ph);
      wg_fence();
#pragma unroll
      for (int ks = 0; ks < 4; ks++) {
        uint64_t db = desc128(kd + ((96 * 128 + ks * 32) >> 4), 1024);
        if (ks == 0) mma_p_init(o0, p0[0], p0[1], p0[2], p0[3], db);
        else mma_p(o0, p0[4 * ks], p0[4 * ks + 1], p0[4 * ks + 2], p0[4 * ks + 3], db);
      }
      wg_commit();
      mbar_wait(bar + B_XEMPTY, ph);
      if (t128 == 0) {
        if (i + 2 < nwin) load_window(&tm_x, &tm_mask, xs, ms, bar + B_XFULL, win + 2 * ncl, rank);
        if (i + PF_DIST < nwin) prefetch_window(&tm_x, &tm_mask, win + PF_DIST * ncl, rank);
      }
      __syncwarp();
      wg_wait<1>();
      pin(s1);
      pin(qf);
      softmax(s1, p1);
      pin(p1);
      wg_fence();
#pragma unroll
      for (int ks = 0; ks < 4; ks++) {
        uint64_t db = desc128(kd + ((144 * 128 + ks * 32) >> 4), 1024);
        if (ks == 0) mma_p_init(o1, p1[0], p1[1], p1[2], p1[3], db);
        else mma_p(o1, p1[4 * ks], p1[4 * ks + 1], p1[4 * ks + 2], p1[4 * ks + 3], db);
      }
      wg_commit();
      uint32_t of[24];
      wg_wait<1>();
      pin(o0);
      pin(p0);
      {
        float r0 = rcp(o0[24]), r1 = rcp(o0[26]);
#pragma unroll
        for (int j = 0; j < 12; j++) {
          float r = (j & 1) ? r1 : r0;
          of[j] = pack_bf16(o0[2 * j] * r, o0[2 * j + 1] * r);
        }
      }
#pragma unroll
      for (int c = 0; c < 3; c++)
        asm volatile("st.async.shared::cluster.mbarrier::complete_tx::bytes.v4.b32 [%0], {%1,%2,%3,%4}, [%5];" ::"r"(oin_rem + c * 2048),
                     "r"(of[4 * c]), "r"(of[4 * c + 1]), "r"(of[4 * c + 2]), "r"(of[4 * c + 3]), "r"(ofull_rem)
                     : "memory");
      wg_wait<0>();
      pin(o1);
      pin(p1);
      if (lane == 0) mbar_arrive(bar + B_KVEMPTY);
      {
        float r0 = rcp(o1[0]), r1 = rcp(o1[2]);
#pragma unroll
        for (int j = 0; j < 12; j++) {
          float r = (j & 1) ? r1 : r0;
          of[12 + j] = pack_bf16(o1[4 + 2 * j] * r, o1[5 + 2 * j] * r);
        }
      }
#pragma unroll
      for (int c = 3; c < 6; c++)
        asm volatile("st.async.shared::cluster.mbarrier::complete_tx::bytes.v4.b32 [%0], {%1,%2,%3,%4}, [%5];" ::"r"(oin_rem + c * 2048),
                     "r"(of[4 * c]), "r"(of[4 * c + 1]), "r"(of[4 * c + 2]), "r"(of[4 * c + 3]), "r"(ofull_rem)
                     : "memory");
      pin(of);
      float oa[48];
      wg_fence();
#pragma unroll
      for (int ks = 0; ks < 6; ks++) {
        uint64_t db = desc128(sb16 + ((OFF_WO + (ks >> 2) * 12288 + (ks & 3) * 32) >> 4), 1024);
        if (ks == 0) mma_o_init(oa, of[0], of[1], of[2], of[3], db);
        else mma_o(oa, of[4 * ks], of[4 * ks + 1], of[4 * ks + 2], of[4 * ks + 3], db);
      }
      wg_commit();
      uint32_t og[24];
      mbar_wait(bar + B_OFULL, ph);
#pragma unroll
      for (int c = 0; c < 6; c++) lds128(oin + c * 2048, og[4 * c], og[4 * c + 1], og[4 * c + 2], og[4 * c + 3]);
      pin(og);
      wg_fence();
#pragma unroll
      for (int ks = 6; ks < 12; ks++) {
        uint64_t db = desc128(sb16 + ((OFF_WO + (ks >> 2) * 12288 + (ks & 3) * 32) >> 4), 1024);
        mma_o(oa, og[4 * ks - 24], og[4 * ks - 23], og[4 * ks - 22], og[4 * ks - 21], db);
      }
      wg_commit();
      const int y = ((win >> 6) * 8 + 4 + ty) & 511, x = ((win & 63) * 8 + 4 + tx) & 511;
      char* dst = outp + (size_t)((y * 512 + x) * 384);
      wg_wait<0>();
      pin(oa);
      pin(of);
      pin(og);
#pragma unroll
      for (int h = 0; h < 2; h++)
#pragma unroll
        for (int c = 0; c < 3; c++) {
          uint4 v;
          v.x = pack_bf16(oa[16 * c + 2 * h], oa[16 * c + 2 * h + 1]);
          v.y = pack_bf16(oa[16 * c + 4 + 2 * h], oa[16 * c + 4 + 2 * h + 1]);
          v.z = pack_bf16(oa[16 * c + 8 + 2 * h], oa[16 * c + 8 + 2 * h + 1]);
          v.w = pack_bf16(oa[16 * c + 12 + 2 * h], oa[16 * c + 12 + 2 * h + 1]);
          *reinterpret_cast<uint4*>(dst + h * 768 + c * 64) = v;
        }
    }
  }
  asm volatile("barrier.cluster.arrive.aligned;" ::: "memory");
  asm volatile("barrier.cluster.wait.aligned;" ::: "memory");
}

typedef CUresult (*EncodeFn)(CUtensorMap*, CUtensorMapDataType, cuuint32_t, void*, const cuuint64_t*, const cuuint64_t*,
                             const cuuint32_t*, const cuuint32_t*, CUtensorMapInterleave, CUtensorMapSwizzle,
                             CUtensorMapL2promotion, CUtensorMapFloatOOBfill);

}

#include <stdio.h>
extern "C" void kernel_launch(void* const* d_in, const int* in_sizes, int n_in, void* d_out, int out_size) {
  static EncodeFn encode = nullptr;
  static int grid = 0;
  if (!encode) {
    cudaDriverEntryPointQueryResult qr;
    void* fn = nullptr;
    cudaGetDriverEntryPoint("cuTensorMapEncodeTiled", &fn, cudaEnableDefault, &qr);
    encode = (EncodeFn)fn;
    cudaFuncSetAttribute(swin_attn_kernel, cudaFuncAttributeMaxDynamicSharedMemorySize, SMEM_BYTES);
    cudaLaunchConfig_t cfg = {};
    cfg.gridDim = dim3(132);
    cfg.blockDim = dim3(384);
    cfg.dynamicSmemBytes = SMEM_BYTES;
    cudaLaunchAttribute at;
    at.id = cudaLaunchAttributeClusterDimension;
    at.val.clusterDim.x = 2;
    at.val.clusterDim.y = 1;
    at.val.clusterDim.z = 1;
    cfg.attrs = &at;
    cfg.numAttrs = 1;
    int ncl = 0;
    if (cudaOccupancyMaxActiveClusters(&ncl, swin_attn_kernel, &cfg) != cudaSuccess || ncl < 1) {
      (void)cudaGetLastError();
      ncl = 66;
    }
    grid = 2 * ncl;
  }
  CUtensorMap tm_x, tm_mask;
  const cuuint32_t es[5] = {1, 1, 1, 1, 1};
  {
    const cuuint64_t dim[5] = {64, 2, 512, 3, 256};
    const cuuint64_t str[4] = {384, 512 * 384, 128, 768};
    const cuuint32_t box[5] = {64, 2, 4, 3, 2};
    CUresult r = encode(&tm_x, CU_TENSOR_MAP_DATA_TYPE_BFLOAT16, 5, d_in[0], dim, str, box, es, CU_TENSOR_MAP_INTERLEAVE_NONE,
                        CU_TENSOR_MAP_SWIZZLE_128B, CU_TENSOR_MAP_L2_PROMOTION_L2_128B, CU_TENSOR_MAP_FLOAT_OOB_FILL_NONE);
    if (r != CUDA_SUCCESS) fprintf(stderr, "tensor map x failed: %d\n", (int)r);
  }
  {
    const cuuint64_t dim[5] = {64, 4, 2, 4, 8192};
    const cuuint64_t str[4] = {1024, 128, 256, 4096};
    const cuuint32_t box[5] = {64, 4, 2, 4, 1};
    CUresult r = encode(&tm_mask, CU_TENSOR_MAP_DATA_TYPE_BFLOAT16, 5, d_in[5], dim, str, box, es, CU_TENSOR_MAP_INTERLEAVE_NONE,
                        CU_TENSOR_MAP_SWIZZLE_128B, CU_TENSOR_MAP_L2_PROMOTION_L2_128B, CU_TENSOR_MAP_FLOAT_OOB_FILL_NONE);
    if (r != CUDA_SUCCESS) fprintf(stderr, "tensor map mask failed: %d\n", (int)r);
  }
  swin_attn_kernel<<<grid, 384, SMEM_BYTES>>>(tm_x, tm_mask, (const __nv_bfloat16*)d_in[1], (const __nv_bfloat16*)d_in[2],
                                              (const __nv_bfloat16*)d_in[3], (const int*)d_in[4], (__nv_bfloat16*)d_out);
}
```

```cpp
#include <cuda_runtime.h>
#include <cuda_bf16.h>
#include <cuda.h>
#include <stdint.h>
#include <stdio.h>

namespace {

constexpr int NWIN = 4096;
#define KV_WG 0
#define PF_DIST 3

constexpr uint32_t SM_BASE  = 1024;
constexpr uint32_t OFF_WQ   = 0;
constexpr uint32_t OFF_WO   = 36864;
constexpr uint32_t STAGE    = 70656;
constexpr uint32_t OFF_X    = 73728;
constexpr uint32_t X_BYTES  = 24576;
constexpr uint32_t OFF_MASK = OFF_X + X_BYTES;
constexpr uint32_t M_BYTES  = 8192;
constexpr uint32_t OFF_KV   = OFF_MASK + M_BYTES;
constexpr uint32_t OFF_OIN  = OFF_KV + 25600;
constexpr uint32_t O_BYTES  = 12288;
constexpr uint32_t OFF_BIAS = 215040;
constexpr uint32_t OFF_BAR  = 231424;
constexpr uint32_t SMEM_BYTES = OFF_BAR + 1024;
constexpr uint32_t B_XFULL = 0, B_XEMPTY = 16, B_KFULL = 32, B_VFULL = 48, B_KVEMPTY = 64, B_OFULL = 80, B_OEMPTY = 96,
                   B_WKV = 112, B_WQ = 120, B_WO = 128;

struct Maps { CUtensorMap x, mask, out, wqkv, wo; };

__device__ __forceinline__ void mma_q_init(float (&d)[48], uint64_t descA, uint64_t descB) {
  asm volatile("wgmma.mma_async.sync.aligned.m64n96k16.f32.bf16.bf16 {%0, %1, %2, %3, %4, %5, %6, %7, %8, %9, %10, %11, %12, %13, %14, %15, %16, %17, %18, %19, %20, %21, %22, %23, %24, %25, %26, %27, %28, %29, %30, %31, %32, %33, %34, %35, %36, %37, %38, %39, %40, %41, %42, %43, %44, %45, %46, %47}, "
    "%48, %49, 0, 1, 1, 0, 1;"
    : "+f"(d[0]), "+f"(d[1]), "+f"(d[2]), "+f"(d[3]), "+f"(d[4]), "+f"(d[5]), "+f"(d[6]), "+f"(d[7]), "+f"(d[8]), "+f"(d[9]), "+f"(d[10]), "+f"(d[11]), "+f"(d[12]), "+f"(d[13]), "+f"(d[14]), "+f"(d[15]), "+f"(d[16]), "+f"(d[17]), "+f"(d[18]), "+f"(d[19]), "+f"(d[20]), "+f"(d[21]), "+f"(d[22]), "+f"(d[23]), "+f"(d[24]), "+f"(d[25]), "+f"(d[26]), "+f"(d[27]), "+f"(d[28]), "+f"(d[29]), "+f"(d[30]), "+f"(d[31]), "+f"(d[32]), "+f"(d[33]), "+f"(d[34]), "+f"(d[35]), "+f"(d[36]), "+f"(d[37]), "+f"(d[38]), "+f"(d[39]), "+f"(d[40]), "+f"(d[41]), "+f"(d[42]), "+f"(d[43]), "+f"(d[44]), "+f"(d[45]), "+f"(d[46]), "+f"(d[47])
    : "l"(descA), "l"(descB));
}
__device__ __forceinline__ void mma_q(float (&d)[48], uint64_t descA, uint64_t descB) {
  asm volatile("wgmma.mma_async.sync.aligned.m64n96k16.f32.bf16.bf16 {%0, %1, %2, %3, %4, %5, %6, %7, %8, %9, %10, %11, %12, %13, %14, %15, %16, %17, %18, %19, %20, %21, %22, %23, %24, %25, %26, %27, %28, %29, %30, %31, %32, %33, %34, %35, %36, %37, %38, %39, %40, %41, %42, %43, %44, %45, %46, %47}, "
    "%48, %49, 1, 1, 1, 0, 1;"
    : "+f"(d[0]), "+f"(d[1]), "+f"(d[2]), "+f"(d[3]), "+f"(d[4]), "+f"(d[5]), "+f"(d[6]), "+f"(d[7]), "+f"(d[8]), "+f"(d[9]), "+f"(d[10]), "+f"(d[11]), "+f"(d[12]), "+f"(d[13]), "+f"(d[14]), "+f"(d[15]), "+f"(d[16]), "+f"(d[17]), "+f"(d[18]), "+f"(d[19]), "+f"(d[20]), "+f"(d[21]), "+f"(d[22]), "+f"(d[23]), "+f"(d[24]), "+f"(d[25]), "+f"(d[26]), "+f"(d[27]), "+f"(d[28]), "+f"(d[29]), "+f"(d[30]), "+f"(d[31]), "+f"(d[32]), "+f"(d[33]), "+f"(d[34]), "+f"(d[35]), "+f"(d[36]), "+f"(d[37]), "+f"(d[38]), "+f"(d[39]), "+f"(d[40]), "+f"(d[41]), "+f"(d[42]), "+f"(d[43]), "+f"(d[44]), "+f"(d[45]), "+f"(d[46]), "+f"(d[47])
    : "l"(descA), "l"(descB));
}
__device__ __forceinline__ void mma_kv_init(float (&d)[32], uint32_t a0, uint32_t a1, uint32_t a2, uint32_t a3, uint64_t descB) {
  asm volatile("wgmma.mma_async.sync.aligned.m64n64k16.f32.bf16.bf16 {%0, %1, %2, %3, %4, %5, %6, %7, %8, %9, %10, %11, %12, %13, %14, %15, %16, %17, %18, %19, %20, %21, %22, %23, %24, %25, %26, %27, %28, %29, %30, %31}, "
    "{%32, %33, %34, %35}, %36, 0, 1, 1, 0;"
    : "+f"(d[0]), "+f"(d[1]), "+f"(d[2]), "+f"(d[3]), "+f"(d[4]), "+f"(d[5]), "+f"(d[6]), "+f"(d[7]), "+f"(d[8]), "+f"(d[9]), "+f"(d[10]), "+f"(d[11]), "+f"(d[12]), "+f"(d[13]), "+f"(d[14]), "+f"(d[15]), "+f"(d[16]), "+f"(d[17]), "+f"(d[18]), "+f"(d[19]), "+f"(d[20]), "+f"(d[21]), "+f"(d[22]), "+f"(d[23]), "+f"(d[24]), "+f"(d[25]), "+f"(d[26]), "+f"(d[27]), "+f"(d[28]), "+f"(d[29]), "+f"(d[30]), "+f"(d[31])
    : "r"(a0), "r"(a1), "r"(a2), "r"(a3), "l"(descB));
}
__device__ __forceinline__ void mma_kv(float (&d)[32], uint32_t a0, uint32_t a1, uint32_t a2, uint32_t a3, uint64_t descB) {
  asm volatile("wgmma.mma_async.sync.aligned.m64n64k16.f32.bf16.bf16 {%0, %1, %2, %3, %4, %5, %6, %7, %8, %9, %10, %11, %12, %13, %14, %15, %16, %17, %18, %19, %20, %21, %22, %23, %24, %25, %26, %27, %28, %29, %30, %31}, "
    "{%32, %33, %34, %35}, %36, 1, 1, 1, 0;"
    : "+f"(d[0]), "+f"(d[1]), "+f"(d[2]), "+f"(d[3]), "+f"(d[4]), "+f"(d[5]), "+f"(d[6]), "+f"(d[7]), "+f"(d[8]), "+f"(d[9]), "+f"(d[10]), "+f"(d[11]), "+f"(d[12]), "+f"(d[13]), "+f"(d[14]), "+f"(d[15]), "+f"(d[16]), "+f"(d[17]), "+f"(d[18]), "+f"(d[19]), "+f"(d[20]), "+f"(d[21]), "+f"(d[22]), "+f"(d[23]), "+f"(d[24]), "+f"(d[25]), "+f"(d[26]), "+f"(d[27]), "+f"(d[28]), "+f"(d[29]), "+f"(d[30]), "+f"(d[31])
    : "r"(a0), "r"(a1), "r"(a2), "r"(a3), "l"(descB));
}
__device__ __forceinline__ void mma_s(float (&d)[32], uint32_t a0, uint32_t a1, uint32_t a2, uint32_t a3, uint64_t descB) {
  asm volatile("wgmma.mma_async.sync.aligned.m64n64k16.f32.bf16.bf16 {%0, %1, %2, %3, %4, %5, %6, %7, %8, %9, %10, %11, %12, %13, %14, %15, %16, %17, %18, %19, %20, %21, %22, %23, %24, %25, %26, %27, %28, %29, %30, %31}, "
    "{%32, %33, %34, %35}, %36, 1, 1, 1, 1;"
    : "+f"(d[0]), "+f"(d[1]), "+f"(d[2]), "+f"(d[3]), "+f"(d[4]), "+f"(d[5]), "+f"(d[6]), "+f"(d[7]), "+f"(d[8]), "+f"(d[9]), "+f"(d[10]), "+f"(d[11]), "+f"(d[12]), "+f"(d[13]), "+f"(d[14]), "+f"(d[15]), "+f"(d[16]), "+f"(d[17]), "+f"(d[18]), "+f"(d[19]), "+f"(d[20]), "+f"(d[21]), "+f"(d[22]), "+f"(d[23]), "+f"(d[24]), "+f"(d[25]), "+f"(d[26]), "+f"(d[27]), "+f"(d[28]), "+f"(d[29]), "+f"(d[30]), "+f"(d[31])
    : "r"(a0), "r"(a1), "r"(a2), "r"(a3), "l"(descB));
}
__device__ __forceinline__ void mma_p_init(float (&d)[28], uint32_t a0, uint32_t a1, uint32_t a2, uint32_t a3, uint64_t descB) {
  asm volatile("wgmma.mma_async.sync.aligned.m64n56k16.f32.bf16.bf16 {%0, %1, %2, %3, %4, %5, %6, %7, %8, %9, %10, %11, %12, %13, %14, %15, %16, %17, %18, %19, %20, %21, %22, %23, %24, %25, %26, %27}, "
    "{%28, %29, %30, %31}, %32, 0, 1, 1, 0;"
    : "=f"(d[0]), "=f"(d[1]), "=f"(d[2]), "=f"(d[3]), "=f"(d[4]), "=f"(d[5]), "=f"(d[6]), "=f"(d[7]), "=f"(d[8]), "=f"(d[9]), "=f"(d[10]), "=f"(d[11]), "=f"(d[12]), "=f"(d[13]), "=f"(d[14]), "=f"(d[15]), "=f"(d[16]), "=f"(d[17]), "=f"(d[18]), "=f"(d[19]), "=f"(d[20]), "=f"(d[21]), "=f"(d[22]), "=f"(d[23]), "=f"(d[24]), "=f"(d[25]), "=f"(d[26]), "=f"(d[27])
    : "r"(a0), "r"(a1), "r"(a2), "r"(a3), "l"(descB));
}
__device__ __forceinline__ void mma_p(float (&d)[28], uint32_t a0, uint32_t a1, uint32_t a2, uint32_t a3, uint64_t descB) {
  asm volatile("wgmma.mma_async.sync.aligned.m64n56k16.f32.bf16.bf16 {%0, %1, %2, %3, %4, %5, %6, %7, %8, %9, %10, %11, %12, %13, %14, %15, %16, %17, %18, %19, %20, %21, %22, %23, %24, %25, %26, %27}, "
    "{%28, %29, %30, %31}, %32, 1, 1, 1, 0;"
    : "+f"(d[0]), "+f"(d[1]), "+f"(d[2]), "+f"(d[3]), "+f"(d[4]), "+f"(d[5]), "+f"(d[6]), "+f"(d[7]), "+f"(d[8]), "+f"(d[9]), "+f"(d[10]), "+f"(d[11]), "+f"(d[12]), "+f"(d[13]), "+f"(d[14]), "+f"(d[15]), "+f"(d[16]), "+f"(d[17]), "+f"(d[18]), "+f"(d[19]), "+f"(d[20]), "+f"(d[21]), "+f"(d[22]), "+f"(d[23]), "+f"(d[24]), "+f"(d[25]), "+f"(d[26]), "+f"(d[27])
    : "r"(a0), "r"(a1), "r"(a2), "r"(a3), "l"(descB));
}
__device__ __forceinline__ void mma_o_init(float (&d)[48], uint32_t a0, uint32_t a1, uint32_t a2, uint32_t a3, uint64_t descB) {
  asm volatile("wgmma.mma_async.sync.aligned.m64n96k16.f32.bf16.bf16 {%0, %1, %2, %3, %4, %5, %6, %7, %8, %9, %10, %11, %12, %13, %14, %15, %16, %17, %18, %19, %20, %21, %22, %23, %24, %25, %26, %27, %28, %29, %30, %31, %32, %33, %34, %35, %36, %37, %38, %39, %40, %41, %42, %43, %44, %45, %46, %47}, "
    "{%48, %49, %50, %51}, %52, 0, 1, 1, 1;"
    : "=f"(d[0]), "=f"(d[1]), "=f"(d[2]), "=f"(d[3]), "=f"(d[4]), "=f"(d[5]), "=f"(d[6]), "=f"(d[7]), "=f"(d[8]), "=f"(d[9]), "=f"(d[10]), "=f"(d[11]), "=f"(d[12]), "=f"(d[13]), "=f"(d[14]), "=f"(d[15]), "=f"(d[16]), "=f"(d[17]), "=f"(d[18]), "=f"(d[19]), "=f"(d[20]), "=f"(d[21]), "=f"(d[22]), "=f"(d[23]), "=f"(d[24]), "=f"(d[25]), "=f"(d[26]), "=f"(d[27]), "=f"(d[28]), "=f"(d[29]), "=f"(d[30]), "=f"(d[31]), "=f"(d[32]), "=f"(d[33]), "=f"(d[34]), "=f"(d[35]), "=f"(d[36]), "=f"(d[37]), "=f"(d[38]), "=f"(d[39]), "=f"(d[40]), "=f"(d[41]), "=f"(d[42]), "=f"(d[43]), "=f"(d[44]), "=f"(d[45]), "=f"(d[46]), "=f"(d[47])
    : "r"(a0), "r"(a1), "r"(a2), "r"(a3), "l"(descB));
}
__device__ __forceinline__ void mma_o(float (&d)[48], uint32_t a0, uint32_t a1, uint32_t a2, uint32_t a3, uint64_t descB) {
  asm volatile("wgmma.mma_async.sync.aligned.m64n96k16.f32.bf16.bf16 {%0, %1, %2, %3, %4, %5, %6, %7, %8, %9, %10, %11, %12, %13, %14, %15, %16, %17, %18, %19, %20, %21, %22, %23, %24, %25, %26, %27, %28, %29, %30, %31, %32, %33, %34, %35, %36, %37, %38, %39, %40, %41, %42, %43, %44, %45, %46, %47}, "
    "{%48, %49, %50, %51}, %52, 1, 1, 1, 1;"
    : "+f"(d[0]), "+f"(d[1]), "+f"(d[2]), "+f"(d[3]), "+f"(d[4]), "+f"(d[5]), "+f"(d[6]), "+f"(d[7]), "+f"(d[8]), "+f"(d[9]), "+f"(d[10]), "+f"(d[11]), "+f"(d[12]), "+f"(d[13]), "+f"(d[14]), "+f"(d[15]), "+f"(d[16]), "+f"(d[17]), "+f"(d[18]), "+f"(d[19]), "+f"(d[20]), "+f"(d[21]), "+f"(d[22]), "+f"(d[23]), "+f"(d[24]), "+f"(d[25]), "+f"(d[26]), "+f"(d[27]), "+f"(d[28]), "+f"(d[29]), "+f"(d[30]), "+f"(d[31]), "+f"(d[32]), "+f"(d[33]), "+f"(d[34]), "+f"(d[35]), "+f"(d[36]), "+f"(d[37]), "+f"(d[38]), "+f"(d[39]), "+f"(d[40]), "+f"(d[41]), "+f"(d[42]), "+f"(d[43]), "+f"(d[44]), "+f"(d[45]), "+f"(d[46]), "+f"(d[47])
    : "r"(a0), "r"(a1), "r"(a2), "r"(a3), "l"(descB));
}

__device__ __forceinline__ void wg_fence() { asm volatile("wgmma.fence.sync.aligned;" ::: "memory"); }
__device__ __forceinline__ void wg_commit() { asm volatile("wgmma.commit_group.sync.aligned;" ::: "memory"); }
template <int N> __device__ __forceinline__ void wg_wait() { asm volatile("wgmma.wait_group.sync.aligned %0;" ::"n"(N) : "memory"); }
template <int N> __device__ __forceinline__ void pin(float (&d)[N]) {
#pragma unroll
  for (int i = 0; i < N; i++) asm volatile("" : "+f"(d[i])::"memory");
}
template <int N> __device__ __forceinline__ void pin(uint32_t (&d)[N]) {
#pragma unroll
  for (int i = 0; i < N; i++) asm volatile("" : "+r"(d[i])::"memory");
}
__device__ __forceinline__ uint64_t mkdesc(uint32_t lo, uint32_t hi) { return ((uint64_t)hi << 32) | lo; }
constexpr uint32_t HI_X = (3072 >> 4) | (1u << 30);
constexpr uint32_t HI_KV = (1024 >> 4) | (1u << 30);
constexpr uint32_t HI_W = (512 >> 4) | (2u << 30);
constexpr uint32_t LO_WQ = ((12288 >> 4) << 16) + ((SM_BASE + OFF_WQ) >> 4);
constexpr uint32_t LO_WO = ((6144 >> 4) << 16) + ((SM_BASE + OFF_WO) >> 4);
constexpr uint32_t LO_X = (1u << 16) + ((SM_BASE + OFF_X) >> 4);
constexpr uint32_t LO_KV = (1u << 16) + ((SM_BASE + OFF_KV) >> 4);

__device__ __forceinline__ uint32_t pack_bf16(float lo, float hi) {
  uint32_t r;
  asm("cvt.rn.bf16x2.f32 %0, %1, %2;" : "=r"(r) : "f"(hi), "f"(lo));
  return r;
}
__device__ __forceinline__ float ex2(float x) {
  float r;
  asm("ex2.approx.ftz.f32 %0, %1;" : "=f"(r) : "f"(x));
  return r;
}
__device__ __forceinline__ float rcp(float x) {
  float r;
  asm("rcp.approx.ftz.f32 %0, %1;" : "=f"(r) : "f"(x));
  return r;
}
__device__ __forceinline__ bool elect() {
  uint32_t p;
  asm volatile("{\n.reg .pred P;\nelect.sync _|P, 0xffffffff;\nselp.u32 %0, 1, 0, P;\n}" : "=r"(p));
  return p;
}
__device__ __forceinline__ void mbar_init(uint32_t bar, uint32_t cnt) {
  asm volatile("mbarrier.init.shared::cta.b64 [%0], %1;" ::"r"(bar), "r"(cnt) : "memory");
}
__device__ __forceinline__ void mbar_wait(uint32_t bar, uint32_t parity) {
  asm volatile(
      "{\n.reg .pred p;\n.reg .u32 n;\n"
      "mbarrier.try_wait.parity.shared::cta.b64 p, [%0], %1;\n"
      "@p bra DONE;\n"
      "mov.u32 n, 0;\n"
      "LOOP:\n"
      "mbarrier.try_wait.parity.shared::cta.b64 p, [%0], %1;\n"
      "@p bra DONE;\n"
      "add.u32 n, n, 1;\n"
      "setp.lt.u32 p, n, 0x400000;\n"
      "@p bra LOOP;\n"
      "trap;\n"
      "DONE:\n}\n" ::"r"(bar), "r"(parity)
      : "memory");
}
__device__ __forceinline__ void mbar_arrive(uint32_t bar) {
  asm volatile("mbarrier.arrive.shared::cta.b64 _, [%0];" ::"r"(bar) : "memory");
}
__device__ __forceinline__ void mbar_arrive_cluster(uint32_t bar) {
  asm volatile("mbarrier.arrive.shared::cluster.b64 _, [%0];" ::"r"(bar) : "memory");
}
__device__ __forceinline__ void mbar_expect_tx(uint32_t bar, uint32_t bytes) {
  asm volatile("mbarrier.arrive.expect_tx.shared::cta.b64 _, [%0], %1;" ::"r"(bar), "r"(bytes) : "memory");
}
__device__ __forceinline__ uint32_t mapa(uint32_t addr, uint32_t rank) {
  uint32_t r;
  asm("mapa.shared::cluster.u32 %0, %1, %2;" : "=r"(r) : "r"(addr), "r"(rank));
  return r;
}
__device__ __forceinline__ void fence_async() { asm volatile("fence.proxy.async.shared::cta;" ::: "memory"); }
__device__ __forceinline__ void stsm4(uint32_t addr, uint32_t r0, uint32_t r1, uint32_t r2, uint32_t r3) {
  asm volatile("stmatrix.sync.aligned.m8n8.x4.shared.b16 [%0], {%1,%2,%3,%4};" ::"r"(addr), "r"(r0), "r"(r1), "r"(r2), "r"(r3) : "memory");
}
__device__ __forceinline__ void lds128(uint32_t addr, uint32_t& r0, uint32_t& r1, uint32_t& r2, uint32_t& r3) {
  asm volatile("ld.shared.v4.b32 {%0,%1,%2,%3}, [%4];" : "=r"(r0), "=r"(r1), "=r"(r2), "=r"(r3) : "r"(addr) : "memory");
}
template <int OFF>
__device__ __forceinline__ void st_async(uint32_t addr, uint32_t bar, uint32_t r0, uint32_t r1, uint32_t r2, uint32_t r3) {
  asm volatile("st.async.shared::cluster.mbarrier::complete_tx::bytes.v4.b32 [%0+%6], {%1,%2,%3,%4}, [%5];" ::"r"(addr), "r"(r0),
               "r"(r1), "r"(r2), "r"(r3), "r"(bar), "n"(OFF)
               : "memory");
}
__device__ __forceinline__ void tma5_mc(uint32_t dst, const CUtensorMap* tm, uint32_t bar, int c2, int c4) {
  asm volatile(
      "cp.async.bulk.tensor.5d.shared::cluster.global.mbarrier::complete_tx::bytes.multicast::cluster "
      "[%0], [%1, {0, 0, %3, 0, %4}], [%2], %5;" ::"r"(dst), "l"(tm), "r"(bar), "r"(c2), "r"(c4), "h"((uint16_t)3)
      : "memory");
}
__device__ __forceinline__ void tma5_pf(const CUtensorMap* tm, int c2, int c4) {
  asm volatile("cp.async.bulk.prefetch.tensor.5d.L2.global [%0, {0, 0, %1, 0, %2}];" ::"l"(tm), "r"(c2), "r"(c4) : "memory");
}
__device__ __forceinline__ void tma3(uint32_t dst, const CUtensorMap* tm, uint32_t bar, int c1, int c2) {
  asm volatile("cp.async.bulk.tensor.3d.shared::cluster.global.mbarrier::complete_tx::bytes [%0], [%1, {0, %3, %4}], [%2];" ::"r"(dst),
               "l"(tm), "r"(bar), "r"(c1), "r"(c2)
               : "memory");
}
__device__ __forceinline__ void piece_coords(int p, int win, int rank, int& c2, int& c4) {
  c2 = p < 2 ? ((win >> 6) * 8 + 4 + 4 * rank) & 511 : 0;
  c4 = p < 2 ? ((win & 63) * 4 + 2 + 2 * p) & 255 : 2 * win + rank;
}

#define TR_SETUP(kv)
#define TR(k)
#define TRP(k)

constexpr float SQRT_HD = 6.92820323027551f;
constexpr float SM_C = 1.4426950408889634f / SQRT_HD;

__device__ __forceinline__ void s_init(float (&s)[32], const uint32_t (&mk)[16], uint32_t bias_addr) {
  uint32_t b[16];
#pragma unroll
  for (int c = 0; c < 4; c++) lds128(bias_addr + c * 2048, b[4 * c], b[4 * c + 1], b[4 * c + 2], b[4 * c + 3]);
#pragma unroll
  for (int i = 0; i < 16; i++) {
    uint32_t t;
    asm("fma.rn.bf16x2 %0, %1, %2, %3;" : "=r"(t) : "r"(mk[i]), "r"(0x40DE40DEu), "r"(b[i]));
    s[4 * (i & 7) + 2 * (i >> 3)] = __uint_as_float(t << 16);
    s[4 * (i & 7) + 2 * (i >> 3) + 1] = __uint_as_float(t & 0xffff0000u);
  }
}
__device__ __forceinline__ void softmax(float (&s)[32], uint32_t (&p)[16]) {
  float m0 = fmaxf(s[0], s[1]), m1 = fmaxf(s[2], s[3]);
#pragma unroll
  for (int j = 1; j < 8; j++) {
    m0 = fmaxf(m0, fmaxf(s[4 * j], s[4 * j + 1]));
    m1 = fmaxf(m1, fmaxf(s[4 * j + 2], s[4 * j + 3]));
  }
  m0 = fmaxf(m0, __shfl_xor_sync(0xffffffffu, m0, 1));
  m1 = fmaxf(m1, __shfl_xor_sync(0xffffffffu, m1, 1));
  m0 = fmaxf(m0, __shfl_xor_sync(0xffffffffu, m0, 2));
  m1 = fmaxf(m1, __shfl_xor_sync(0xffffffffu, m1, 2));
  m0 *= -SM_C;
  m1 *= -SM_C;
#pragma unroll
  for (int i = 0; i < 16; i++) {
    float m = (i & 1) ? m1 : m0;
    p[i] = pack_bf16(ex2(fmaf(s[2 * i], SM_C, m)), ex2(fmaf(s[2 * i + 1], SM_C, m)));
  }
}

__device__ __forceinline__ void store_out(const uint32_t (&ob)[24], uint32_t st_addr, uint32_t stage, const CUtensorMap* tm,
                                          int win, int warp, int rank) {
#pragma unroll
  for (int jj = 0; jj < 6; jj++)
    stsm4((st_addr ^ ((jj & 1) << 5)) + (jj >> 1) * 512, ob[4 * jj], ob[4 * jj + 1], ob[4 * jj + 2], ob[4 * jj + 3]);
  fence_async();
  __syncwarp();
  if (elect()) {
    int y0 = ((win >> 6) * 8 + 4 + 4 * (warp >> 1)) & 511;
    int xh = ((win & 63) * 4 + 2 + 2 * (warp & 1)) & 255;
    asm volatile("cp.async.bulk.tensor.5d.global.shared::cta.bulk_group [%0, {0, 0, %2, %3, %4}], [%1];" ::"l"(tm), "r"(stage), "r"(y0),
                 "r"(3 * rank), "r"(xh)
                 : "memory");
    asm volatile("cp.async.bulk.commit_group;" ::: "memory");
  }
}

__global__ void __cluster_dims__(2, 1, 1) __launch_bounds__(384, 1)
swin_attn_kernel(const __grid_constant__ Maps maps, const __nv_bfloat16* __restrict__ rpb, const int* __restrict__ rp_idx) {
  extern __shared__ __align__(1024) uint8_t smem_raw[];
  const uint32_t sb = (uint32_t)__cvta_generic_to_shared(smem_raw);
  const int tid = threadIdx.x;
  const int wg = __shfl_sync(0xffffffffu, tid >> 7, 0);
  const int warp = __shfl_sync(0xffffffffu, (tid >> 5) & 3, 0);
  const int lane = tid & 31;
  const int rank = blockIdx.x & 1;
  const int cl = blockIdx.x >> 1;
  const int ncl = gridDim.x >> 1;
  const uint32_t bars = sb + OFF_BAR;
  TRP(0);

  if (wg == KV_WG) {
    if (warp == 3) {
      if (elect()) {
        if ((sb & 0x3FFFF) != SM_BASE) __trap();
#pragma unroll
        for (int a = 0; a < 2; a++) {
          mbar_init(bars + B_XFULL + 8 * a, 1);
          mbar_init(bars + B_XEMPTY + 8 * a, 16);
          mbar_init(bars + B_KFULL + 8 * a, 4);
          mbar_init(bars + B_VFULL + 8 * a, 4);
          mbar_init(bars + B_KVEMPTY + 8 * a, 4);
          mbar_init(bars + B_OFULL + 8 * a, 1);
          mbar_init(bars + B_OEMPTY + 8 * a, 4);
        }
        mbar_init(bars + B_WKV, 1);
        mbar_init(bars + B_WQ, 1);
        mbar_init(bars + B_WO, 1);
        asm volatile("fence.mbarrier_init.release.cluster;" ::: "memory");
        fence_async();
        mbar_expect_tx(bars + B_WKV, 73728);
        mbar_expect_tx(bars + B_WQ, 36864);
        mbar_expect_tx(bars + B_WO, 36864);
        mbar_expect_tx(bars + B_XFULL, X_BYTES + M_BYTES);
        mbar_expect_tx(bars + B_XFULL + 8, X_BYTES + M_BYTES);
        tma3(sb + OFF_KV, &maps.wqkv, bars + B_WKV, 0, 6 + 3 * rank);
        tma3(sb + OFF_KV + STAGE, &maps.wqkv, bars + B_WKV, 0, 12 + 3 * rank);
        tma3(sb + OFF_WQ, &maps.wqkv, bars + B_WQ, 0, 3 * rank);
      }
      __syncwarp();
    }
    const CUtensorMap* pmap = warp < 2 ? &maps.x : &maps.mask;
    if (warp < 3 && elect()) {
      for (int j = 0; j < 2 + PF_DIST; j++) {
        int c2, c4;
        piece_coords(warp, cl + j * ncl, rank, c2, c4);
        tma5_pf(pmap, c2, c4);
      }
    }
    __syncwarp();
    asm volatile("barrier.cluster.arrive.relaxed.aligned;" ::: "memory");
    asm volatile("setmaxnreg.inc.sync.aligned.u32 216;");
    asm volatile("barrier.cluster.wait.aligned;" ::: "memory");
    TRP(1);
    const uint32_t pdst = sb + (warp < 2 ? OFF_X + rank * 12288 + warp * 6144 : OFF_MASK + rank * 4096);
    if (elect()) {
      if (warp < 3) {
#pragma unroll
        for (int j = 0; j < 2; j++) {
          int c2, c4;
          piece_coords(warp, cl + j * ncl, rank, c2, c4);
          tma5_mc(pdst + j * STAGE, pmap, bars + B_XFULL + 8 * j, c2, c4);
        }
      } else {
        tma3(sb + OFF_WO, &maps.wo, bars + B_WO, 96 * rank, 3 * rank);
        tma3(sb + OFF_WO + 18432, &maps.wo, bars + B_WO, 96 * (rank ^ 1), 3 * rank);
      }
    }
    __syncwarp();
    uint32_t w[3][48];
    {
      const uint32_t la = sb + OFF_KV + (warp >> 1) * 12288 + (8 * (lane >> 4) + (lane & 7)) * 64 +
                          (((2 * (warp & 1) + ((lane >> 3) & 1)) ^ ((lane & 7) >> 1)) << 4);
      mbar_wait(bars + B_WKV, 0);
      TRP(2);
#pragma unroll
      for (int s = 0; s < 3; s++)
#pragma unroll
        for (int ks = 0; ks < 12; ks++)
          asm volatile("ldmatrix.sync.aligned.m8n8.x4.trans.shared.b16 {%0,%1,%2,%3}, [%4];"
                       : "=r"(w[s][4 * ks]), "=r"(w[s][4 * ks + 1]), "=r"(w[s][4 * ks + 2]), "=r"(w[s][4 * ks + 3])
                       : "r"(la + s * 24576 + (s == 2 || (s == 1 && warp >= 2) ? STAGE - 36864 : 0) + ks * 1024)
                       : "memory");
      asm volatile("bar.sync 2, 128;" ::: "memory");
      asm volatile("st.shared.v4.b32 [%0], {%1,%1,%1,%1};" ::"r"(sb + OFF_KV + (warp >> 1) * STAGE + 144 * 128 + (tid & 63) * 16), "r"(0x3F803F80u) : "memory");
    }
    TRP(3);
    const uint32_t st0 = sb + OFF_KV + (16 * warp + (lane & 15)) * 128 + (((lane >> 4) ^ (lane & 7)) << 4);
    const uint32_t xe_addr = mapa(bars + B_XEMPTY, lane & 1);
    const uint32_t v1off = warp > 0 ? 1024 : 0;

    float acc[32];
    uint32_t pk[16];
    auto issue = [&](int s, uint32_t xd) {
      wg_fence();
#pragma unroll
      for (int ks = 0; ks < 12; ks++) {
        uint64_t db = mkdesc(xd + (((ks >> 2) * 1024 + (ks & 3) * 32) >> 4), HI_X);
        if (ks == 0) mma_kv_init(acc, w[s][0], w[s][1], w[s][2], w[s][3], db);
        else mma_kv(acc, w[s][4 * ks], w[s][4 * ks + 1], w[s][4 * ks + 2], w[s][4 * ks + 3], db);
      }
      wg_commit();
      __syncwarp();
    };
    auto convert = [&]() {
      wg_wait<0>();
      pin(acc);
#pragma unroll
      for (int j = 0; j < 16; j++) pk[j] = pack_bf16(acc[2 * j], acc[2 * j + 1]);
      pin(pk);
    };
    auto store = [&](uint32_t st) {
#pragma unroll
      for (int jj = 0; jj < 4; jj++) stsm4(st ^ (jj << 5), pk[4 * jj], pk[4 * jj + 1], pk[4 * jj + 2], pk[4 * jj + 3]);
    };

    mbar_wait(bars + B_XFULL, 0);
    TRP(4);
    issue(0, LO_X);
    int i = 0;
    for (int win = cl; win < NWIN; win += ncl, i++) {
      const int a = i & 1;
      const uint32_t ph = (i >> 1) & 1;
      const uint32_t xd = LO_X + a * (STAGE >> 4);
      const uint32_t st = st0 + a * STAGE;
      TR_SETUP(1);
      TR(0);
      convert();
      TR(1);
      issue(1, xd);
      TR(2);
      if (i > 0 && win + ncl < NWIN) {
        mbar_wait(bars + B_XEMPTY + 8 * (a ^ 1), ((i - 1) >> 1) & 1);
        if (elect()) {
          if (warp < 3) {
            int c2, c4;
            piece_coords(warp, win + ncl, rank, c2, c4);
            tma5_mc(pdst + (a ^ 1) * STAGE, pmap, bars + B_XFULL + 8 * (a ^ 1), c2, c4);
            if (win + (1 + PF_DIST) * ncl < NWIN) {
              piece_coords(warp, win + (1 + PF_DIST) * ncl, rank, c2, c4);
              tma5_pf(pmap, c2, c4);
            }
          } else {
            mbar_expect_tx(bars + B_XFULL + 8 * (a ^ 1), X_BYTES + M_BYTES);
          }
        }
        __syncwarp();
      }
      TR(3);
      mbar_wait(bars + B_KVEMPTY + 8 * a, ph ^ 1);
      TR(4);
      store(st);
      convert();
      TR(5);
      issue(2, xd);
      store(st + 8192);
      fence_async();
      __syncwarp();
      if (lane == 0) mbar_arrive(bars + B_KFULL + 8 * a);
      TR(6);
      convert();
      TR(7);
      if (lane < 2) mbar_arrive_cluster(xe_addr + 8 * a);
      store(st + 16384 + v1off);
      const bool more = win + ncl < NWIN;
      if (more) mbar_wait(bars + B_XFULL + 8 * (a ^ 1), ((i + 1) >> 1) & 1);
      TR(8);
      issue(0, LO_X + (a ^ 1) * (STAGE >> 4));
      TR(9);
      fence_async();
      __syncwarp();
      if (lane == 0) mbar_arrive(bars + B_VFULL + 8 * a);
      TR(10);
    }
    wg_wait<0>();
    pin(acc);
  } else {
    const int a = wg - (KV_WG == 0 ? 1 : 0);
    const int t128 = tid & 127;
    const int g = lane >> 2, q = lane & 3;
    const uint32_t bar = bars + 8 * a;
    asm volatile("barrier.cluster.arrive.relaxed.aligned;" ::: "memory");
    asm volatile("setmaxnreg.dec.sync.aligned.u32 144;");
    const uint32_t bias_addr = sb + OFF_BIAS + t128 * 16;
    {
      const int ty = 4 * (warp >> 1) + (g >> 1), tx = 4 * (warp & 1) + (g & 1);
#pragma unroll
      for (int c4 = 0; c4 < 2; c4++) {
        const int4* ip = reinterpret_cast<const int4*>(rp_idx + (ty * 8 + tx + 2 * a) * 64 + 8 * (q + 4 * c4));
        int4 i0 = __ldg(ip), i1 = __ldg(ip + 1);
        int id[8] = {i0.x, i0.y, i0.z, i0.w, i1.x, i1.y, i1.z, i1.w};
        uint32_t bias0[4], bias1[4];
#pragma unroll
        for (int jj = 0; jj < 4; jj++) {
          uint32_t b0 = __ldg(reinterpret_cast<const uint32_t*>(rpb) + id[2 * jj] * 2 + rank);
          uint32_t b1 = __ldg(reinterpret_cast<const uint32_t*>(rpb) + id[2 * jj + 1] * 2 + rank);
          bias0[jj] = pack_bf16(__uint_as_float(b0 << 16) * SQRT_HD, __uint_as_float(b1 << 16) * SQRT_HD);
          bias1[jj] = pack_bf16(__uint_as_float(b0 & 0xffff0000u) * SQRT_HD, __uint_as_float(b1 & 0xffff0000u) * SQRT_HD);
        }
        asm volatile("st.shared.v4.b32 [%0], {%1,%2,%3,%4};" ::"r"(bias_addr + (2 * a + c4) * 2048), "r"(bias0[0]), "r"(bias0[1]), "r"(bias0[2]), "r"(bias0[3]) : "memory");
        asm volatile("st.shared.v4.b32 [%0], {%1,%2,%3,%4};" ::"r"(bias_addr + 8192 + (2 * a + c4) * 2048), "r"(bias1[0]), "r"(bias1[1]), "r"(bias1[2]), "r"(bias1[3]) : "memory");
      }
    }
    TRP(1);
    asm volatile("barrier.cluster.wait.aligned;" ::: "memory");
    asm volatile("bar.sync 1, 256;" ::: "memory");
    TRP(2);

    const int mrow = 16 * warp + (g >> 1) + 4 * (g & 1);
    const uint32_t mk_addr = sb + OFF_MASK + a * STAGE + mrow * 128 + ((q ^ (mrow & 7)) << 4);
    const uint32_t ostage = sb + OFF_OIN + a * STAGE + warp * 3072;
    const uint32_t oin = ostage + lane * 16;
    const uint32_t ost = ostage + ((lane >> 3) & 1) * 1536 + (lane & 7) * 64 + (((lane >> 4) ^ ((lane & 7) >> 1)) << 4);
    const uint32_t oin_rem = mapa(oin, rank ^ 1);
    const uint32_t bar_rem = mapa(bar, rank ^ 1);
    const uint32_t xe_addr = mapa(bar + B_XEMPTY, lane & 1);
    mbar_wait(bars + B_WQ, 0);
    TRP(3);

    float qa[48];
    auto issue_q = [&](uint32_t ua) {
      wg_fence();
#pragma unroll
      for (int ks = 0; ks < 12; ks++) {
        uint64_t da = mkdesc(ua + LO_X + (((ks >> 2) * 1024 + (ks & 3) * 32) >> 4), HI_X);
        uint64_t db = mkdesc(LO_WQ + ks * 64, HI_W);
        if (ks == 0) mma_q_init(qa, da, db);
        else mma_q(qa, da, db);
      }
      wg_commit();
      __syncwarp();
    };
    mbar_wait(bar + B_XFULL, 0);
    issue_q(a * (STAGE >> 4));
    mbar_wait(bars + B_WO, 0);
    uint32_t ph = 0;
    [[maybe_unused]] int i = a;
    for (int win = cl + a * ncl; win < NWIN; win += 2 * ncl, ph ^= 1, i += 2) {
      TR_SETUP(0);
      TR(0);
      const uint32_t ua = a * (STAGE >> 4) + (win >> 20);
      const uint32_t kd = ua + LO_KV;
      float s0[32], s1[32];
      uint32_t mk[16];
#pragma unroll
      for (int c = 0; c < 4; c++)
        lds128((mk_addr ^ ((c & 1) << 6)) + (c >> 1) * 1024, mk[4 * c], mk[4 * c + 1], mk[4 * c + 2], mk[4 * c + 3]);
      s_init(s0, mk, bias_addr);
      pin(s0);
      TR(1);
      mbar_wait(bar + B_KFULL, ph);
      TR(2);
      wg_wait<0>();
      pin(qa);
      TR(3);
      if (lane < 2) mbar_arrive_cluster(xe_addr);
      uint32_t qf[24];
#pragma unroll
      for (int j = 0; j < 24; j++) qf[j] = pack_bf16(qa[2 * j], qa[2 * j + 1]);
      pin(qf);
      wg_fence();
#pragma unroll
      for (int ks = 0; ks < 3; ks++)
        mma_s(s0, qf[4 * ks], qf[4 * ks + 1], qf[4 * ks + 2], qf[4 * ks + 3], mkdesc(kd + ks * 128, HI_KV));
      wg_commit();
      __syncwarp();
      s_init(s1, mk, bias_addr + 8192);
      pin(s1);
      wg_fence();
#pragma unroll
      for (int ks = 3; ks < 6; ks++)
        mma_s(s1, qf[4 * ks], qf[4 * ks + 1], qf[4 * ks + 2], qf[4 * ks + 3], mkdesc(kd + ks * 128, HI_KV));
      wg_commit();
      TR(4);
      if (elect()) {
        asm volatile("cp.async.bulk.wait_group.read 0;" ::: "memory");
        if (warp == 0) mbar_expect_tx(bar + B_OFULL, O_BYTES);
        mbar_arrive_cluster(bar_rem + B_OEMPTY);
      }
      __syncwarp();
      wg_wait<1>();
      pin(s0);
      TR(5);
      uint32_t p0[16], p1[16];
      softmax(s0, p0);
      pin(p0);
      TR(6);
      float o0[28], o1[28];
      mbar_wait(bar + B_VFULL, ph);
      wg_fence();
#pragma unroll
      for (int ks = 0; ks < 4; ks++) {
        uint64_t db = mkdesc(kd + ((96 * 128 + ks * 32) >> 4), HI_KV);
        if (ks == 0) mma_p_init(o0, p0[0], p0[1], p0[2], p0[3], db);
        else mma_p(o0, p0[4 * ks], p0[4 * ks + 1], p0[4 * ks + 2], p0[4 * ks + 3], db);
      }
      wg_commit();
      wg_wait<1>();
      pin(s1);
      pin(qf);
      TR(7);
      softmax(s1, p1);
      pin(p1);
      TR(8);
      mbar_wait(bar + B_OEMPTY, ph);
      wg_fence();
#pragma unroll
      for (int ks = 0; ks < 4; ks++) {
        uint64_t db = mkdesc(kd + ((144 * 128 + ks * 32) >> 4), HI_KV);
        if (ks == 0) mma_p_init(o1, p1[0], p1[1], p1[2], p1[3], db);
        else mma_p(o1, p1[4 * ks], p1[4 * ks + 1], p1[4 * ks + 2], p1[4 * ks + 3], db);
      }
      wg_commit();
      uint32_t of[24];
      wg_wait<1>();
      pin(o0);
      pin(p0);
      {
        float r0 = rcp(o0[24]), r1 = rcp(o0[26]);
#pragma unroll
        for (int j = 0; j < 12; j++) {
          float r = (j & 1) ? r1 : r0;
          of[j] = pack_bf16(o0[2 * j] * r, o0[2 * j + 1] * r);
        }
      }
      st_async<0>(oin_rem, bar_rem + B_OFULL, of[0], of[1], of[2], of[3]);
      st_async<512>(oin_rem, bar_rem + B_OFULL, of[4], of[5], of[6], of[7]);
      st_async<1024>(oin_rem, bar_rem + B_OFULL, of[8], of[9], of[10], of[11]);
      wg_wait<0>();
      pin(o1);
      pin(p1);
      TR(9);
      if (lane == 0) mbar_arrive(bar + B_KVEMPTY);
      {
        float r0 = rcp(o1[0]), r1 = rcp(o1[2]);
#pragma unroll
        for (int j = 0; j < 12; j++) {
          float r = (j & 1) ? r1 : r0;
          of[12 + j] = pack_bf16(o1[4 + 2 * j] * r, o1[5 + 2 * j] * r);
        }
      }
      st_async<1536>(oin_rem, bar_rem + B_OFULL, of[12], of[13], of[14], of[15]);
      st_async<2048>(oin_rem, bar_rem + B_OFULL, of[16], of[17], of[18], of[19]);
      st_async<2560>(oin_rem, bar_rem + B_OFULL, of[20], of[21], of[22], of[23]);
      pin(of);
      TR(10);
      float (&oa)[48] = qa;
      wg_fence();
#pragma unroll
      for (int ks = 0; ks < 6; ks++) {
        uint64_t db = mkdesc(LO_WO + ks * 64, HI_W);
        if (ks == 0) mma_o_init(oa, of[0], of[1], of[2], of[3], db);
        else mma_o(oa, of[4 * ks], of[4 * ks + 1], of[4 * ks + 2], of[4 * ks + 3], db);
      }
      wg_commit();
      uint32_t og[24];
      mbar_wait(bar + B_OFULL, ph);
      TR(11);
#pragma unroll
      for (int c = 0; c < 6; c++) lds128(oin + c * 512, og[4 * c], og[4 * c + 1], og[4 * c + 2], og[4 * c + 3]);
      pin(og);
      wg_fence();
#pragma unroll
      for (int ks = 0; ks < 6; ks++)
        mma_o(oa, og[4 * ks], og[4 * ks + 1], og[4 * ks + 2], og[4 * ks + 3], mkdesc(LO_WO + (18432 >> 4) + ks * 64, HI_W));
      wg_commit();
      TR(12);
      if (win + 2 * ncl < NWIN) mbar_wait(bar + B_XFULL, ph ^ 1);
      wg_wait<0>();
      pin(oa);
      pin(of);
      pin(og);
      TR(13);
      uint32_t ob[24];
#pragma unroll
      for (int j = 0; j < 24; j++) ob[j] = pack_bf16(oa[2 * j], oa[2 * j + 1]);
      pin(ob);
      issue_q(ua);
      TR(14);
      store_out(ob, ost, ostage, &maps.out, win, warp, rank);
      __syncwarp();
    }
    wg_wait<0>();
    pin(qa);
    asm volatile("cp.async.bulk.wait_group 0;" ::: "memory");
    __syncwarp();
  }
  asm volatile("barrier.cluster.arrive.relaxed.aligned;" ::: "memory");
  asm volatile("barrier.cluster.wait.aligned;" ::: "memory");
}

typedef CUresult (*EncodeFn)(CUtensorMap*, CUtensorMapDataType, cuuint32_t, void*, const cuuint64_t*, const cuuint64_t*,
                             const cuuint32_t*, const cuuint32_t*, CUtensorMapInterleave, CUtensorMapSwizzle,
                             CUtensorMapL2promotion, CUtensorMapFloatOOBfill);

void encode_map(EncodeFn encode, CUtensorMap* m, void* p, int rank, const cuuint64_t* dim, const cuuint64_t* str,
                const cuuint32_t* box, CUtensorMapSwizzle sw) {
  const cuuint32_t es[5] = {1, 1, 1, 1, 1};
  CUresult r = encode(m, CU_TENSOR_MAP_DATA_TYPE_BFLOAT16, rank, p, dim, str, box, es, CU_TENSOR_MAP_INTERLEAVE_NONE, sw,
                      CU_TENSOR_MAP_L2_PROMOTION_L2_128B, CU_TENSOR_MAP_FLOAT_OOB_FILL_NONE);
  if (r != CUDA_SUCCESS) fprintf(stderr, "tensor map encode failed: %d\n", (int)r);
}

}

extern "C" void kernel_launch(void* const* d_in, const int* in_sizes, int n_in, void* d_out, int out_size) {
  static EncodeFn encode = nullptr;
  static int grid = 0;
  if (!encode) {
    cudaDriverEntryPointQueryResult qr;
    void* fn = nullptr;
    cudaGetDriverEntryPoint("cuTensorMapEncodeTiled", &fn, cudaEnableDefault, &qr);
    encode = (EncodeFn)fn;
    cudaFuncSetAttribute(swin_attn_kernel, cudaFuncAttributeMaxDynamicSharedMemorySize, SMEM_BYTES);
    cudaLaunchConfig_t cfg = {};
    cfg.gridDim = dim3(132);
    cfg.blockDim = dim3(384);
    cfg.dynamicSmemBytes = SMEM_BYTES;
    cudaLaunchAttribute at;
    at.id = cudaLaunchAttributeClusterDimension;
    at.val.clusterDim.x = 2;
    at.val.clusterDim.y = 1;
    at.val.clusterDim.z = 1;
    cfg.attrs = &at;
    cfg.numAttrs = 1;
    int ncl = 0;
    if (cudaOccupancyMaxActiveClusters(&ncl, swin_attn_kernel, &cfg) != cudaSuccess || ncl < 1) {
      (void)cudaGetLastError();
      ncl = 66;
    }
    if (ncl > 256) ncl = 256;
    grid = 2 * ncl;
  }
  Maps maps;
  {
    const cuuint64_t dim[5] = {64, 2, 512, 3, 256}, str[4] = {384, 512 * 384, 128, 768};
    const cuuint32_t box[5] = {64, 2, 4, 3, 2};
    encode_map(encode, &maps.x, d_in[0], 5, dim, str, box, CU_TENSOR_MAP_SWIZZLE_128B);
  }
  {
    const cuuint64_t dim[5] = {64, 4, 2, 4, 8192}, str[4] = {1024, 128, 256, 4096};
    const cuuint32_t box[5] = {64, 4, 2, 4, 1};
    encode_map(encode, &maps.mask, d_in[5], 5, dim, str, box, CU_TENSOR_MAP_SWIZZLE_128B);
  }
  {
    const cuuint64_t dim[5] = {32, 2, 512, 6, 256}, str[4] = {384, 512 * 384, 64, 768};
    const cuuint32_t box[5] = {32, 2, 4, 3, 2};
    encode_map(encode, &maps.out, d_out, 5, dim, str, box, CU_TENSOR_MAP_SWIZZLE_64B);
  }
  {
    const cuuint64_t dim[3] = {32, 192, 18}, str[2] = {576 * 2, 64};
    const cuuint32_t box[3] = {32, 192, 3};
    encode_map(encode, &maps.wqkv, d_in[1], 3, dim, str, box, CU_TENSOR_MAP_SWIZZLE_64B);
    const cuuint64_t dim2[3] = {32, 192, 6}, str2[2] = {192 * 2, 64};
    const cuuint32_t box2[3] = {32, 96, 3};
    encode_map(encode, &maps.wo, d_in[2], 3, dim2, str2, box2, CU_TENSOR_MAP_SWIZZLE_64B);
  }
  swin_attn_kernel<<<grid, 384, SMEM_BYTES>>>(maps, (const __nv_bfloat16*)d_in[3], (const int*)d_in[4]);
}
```

```cpp
#include <cuda_runtime.h>
#include <cuda_bf16.h>
#include <cuda.h>
#include <stdint.h>
#include <stdio.h>

namespace {

constexpr int NWIN = 4096;
#define KV_WG 0
#define ST_AT 3
#define PRE_T 8
#define PF_DIST 0

constexpr uint32_t SM_BASE  = 1024;
constexpr uint32_t OFF_WQ   = 0;
constexpr uint32_t OFF_WO   = 36864;
constexpr uint32_t STAGE    = 70656;
constexpr uint32_t OFF_X    = 73728;
constexpr uint32_t X_BYTES  = 24576;
constexpr uint32_t OFF_MASK = OFF_X + X_BYTES;
constexpr uint32_t M_BYTES  = 8192;
constexpr uint32_t OFF_KV   = OFF_MASK + M_BYTES;
constexpr uint32_t OFF_OIN  = OFF_KV + 25600;
constexpr uint32_t O_BYTES  = 12288;
constexpr uint32_t OFF_BAR  = 215040;
constexpr uint32_t SMEM_BYTES = OFF_BAR + 1024;
constexpr uint32_t B_XFULL = 0, B_XEMPTY = 16, B_OFULL = 32, B_OEMPTY = 48, B_WKV = 64, B_WQ = 72, B_WO = 80;
enum { T0 = 1, T1, T2, T3, T4, T5, T6, T7, BAR_BIAS, BAR_STAGE };

template <int V> struct IC { static constexpr int value = V; };
struct Maps { CUtensorMap x, mask, out, wqkv, wo, wop; };

__device__ __forceinline__ void mma_q_init(float (&d)[48], uint64_t descA, uint64_t descB) {
  asm volatile("wgmma.mma_async.sync.aligned.m64n96k16.f32.bf16.bf16 {%0, %1, %2, %3, %4, %5, %6, %7, %8, %9, %10, %11, %12, %13, %14, %15, %16, %17, %18, %19, %20, %21, %22, %23, %24, %25, %26, %27, %28, %29, %30, %31, %32, %33, %34, %35, %36, %37, %38, %39, %40, %41, %42, %43, %44, %45, %46, %47}, "
    "%48, %49, 0, 1, 1, 0, 1;"
    : "+f"(d[0]), "+f"(d[1]), "+f"(d[2]), "+f"(d[3]), "+f"(d[4]), "+f"(d[5]), "+f"(d[6]), "+f"(d[7]), "+f"(d[8]), "+f"(d[9]), "+f"(d[10]), "+f"(d[11]), "+f"(d[12]), "+f"(d[13]), "+f"(d[14]), "+f"(d[15]), "+f"(d[16]), "+f"(d[17]), "+f"(d[18]), "+f"(d[19]), "+f"(d[20]), "+f"(d[21]), "+f"(d[22]), "+f"(d[23]), "+f"(d[24]), "+f"(d[25]), "+f"(d[26]), "+f"(d[27]), "+f"(d[28]), "+f"(d[29]), "+f"(d[30]), "+f"(d[31]), "+f"(d[32]), "+f"(d[33]), "+f"(d[34]), "+f"(d[35]), "+f"(d[36]), "+f"(d[37]), "+f"(d[38]), "+f"(d[39]), "+f"(d[40]), "+f"(d[41]), "+f"(d[42]), "+f"(d[43]), "+f"(d[44]), "+f"(d[45]), "+f"(d[46]), "+f"(d[47])
    : "l"(descA), "l"(descB));
}
__device__ __forceinline__ void mma_q(float (&d)[48], uint64_t descA, uint64_t descB) {
  asm volatile("wgmma.mma_async.sync.aligned.m64n96k16.f32.bf16.bf16 {%0, %1, %2, %3, %4, %5, %6, %7, %8, %9, %10, %11, %12, %13, %14, %15, %16, %17, %18, %19, %20, %21, %22, %23, %24, %25, %26, %27, %28, %29, %30, %31, %32, %33, %34, %35, %36, %37, %38, %39, %40, %41, %42, %43, %44, %45, %46, %47}, "
    "%48, %49, 1, 1, 1, 0, 1;"
    : "+f"(d[0]), "+f"(d[1]), "+f"(d[2]), "+f"(d[3]), "+f"(d[4]), "+f"(d[5]), "+f"(d[6]), "+f"(d[7]), "+f"(d[8]), "+f"(d[9]), "+f"(d[10]), "+f"(d[11]), "+f"(d[12]), "+f"(d[13]), "+f"(d[14]), "+f"(d[15]), "+f"(d[16]), "+f"(d[17]), "+f"(d[18]), "+f"(d[19]), "+f"(d[20]), "+f"(d[21]), "+f"(d[22]), "+f"(d[23]), "+f"(d[24]), "+f"(d[25]), "+f"(d[26]), "+f"(d[27]), "+f"(d[28]), "+f"(d[29]), "+f"(d[30]), "+f"(d[31]), "+f"(d[32]), "+f"(d[33]), "+f"(d[34]), "+f"(d[35]), "+f"(d[36]), "+f"(d[37]), "+f"(d[38]), "+f"(d[39]), "+f"(d[40]), "+f"(d[41]), "+f"(d[42]), "+f"(d[43]), "+f"(d[44]), "+f"(d[45]), "+f"(d[46]), "+f"(d[47])
    : "l"(descA), "l"(descB));
}
__device__ __forceinline__ void mma_kv_init(float (&d)[32], uint32_t a0, uint32_t a1, uint32_t a2, uint32_t a3, uint64_t descB) {
  asm volatile("wgmma.mma_async.sync.aligned.m64n64k16.f32.bf16.bf16 {%0, %1, %2, %3, %4, %5, %6, %7, %8, %9, %10, %11, %12, %13, %14, %15, %16, %17, %18, %19, %20, %21, %22, %23, %24, %25, %26, %27, %28, %29, %30, %31}, "
    "{%32, %33, %34, %35}, %36, 0, 1, 1, 0;"
    : "+f"(d[0]), "+f"(d[1]), "+f"(d[2]), "+f"(d[3]), "+f"(d[4]), "+f"(d[5]), "+f"(d[6]), "+f"(d[7]), "+f"(d[8]), "+f"(d[9]), "+f"(d[10]), "+f"(d[11]), "+f"(d[12]), "+f"(d[13]), "+f"(d[14]), "+f"(d[15]), "+f"(d[16]), "+f"(d[17]), "+f"(d[18]), "+f"(d[19]), "+f"(d[20]), "+f"(d[21]), "+f"(d[22]), "+f"(d[23]), "+f"(d[24]), "+f"(d[25]), "+f"(d[26]), "+f"(d[27]), "+f"(d[28]), "+f"(d[29]), "+f"(d[30]), "+f"(d[31])
    : "r"(a0), "r"(a1), "r"(a2), "r"(a3), "l"(descB));
}
__device__ __forceinline__ void mma_kv(float (&d)[32], uint32_t a0, uint32_t a1, uint32_t a2, uint32_t a3, uint64_t descB) {
  asm volatile("wgmma.mma_async.sync.aligned.m64n64k16.f32.bf16.bf16 {%0, %1, %2, %3, %4, %5, %6, %7, %8, %9, %10, %11, %12, %13, %14, %15, %16, %17, %18, %19, %20, %21, %22, %23, %24, %25, %26, %27, %28, %29, %30, %31}, "
    "{%32, %33, %34, %35}, %36, 1, 1, 1, 0;"
    : "+f"(d[0]), "+f"(d[1]), "+f"(d[2]), "+f"(d[3]), "+f"(d[4]), "+f"(d[5]), "+f"(d[6]), "+f"(d[7]), "+f"(d[8]), "+f"(d[9]), "+f"(d[10]), "+f"(d[11]), "+f"(d[12]), "+f"(d[13]), "+f"(d[14]), "+f"(d[15]), "+f"(d[16]), "+f"(d[17]), "+f"(d[18]), "+f"(d[19]), "+f"(d[20]), "+f"(d[21]), "+f"(d[22]), "+f"(d[23]), "+f"(d[24]), "+f"(d[25]), "+f"(d[26]), "+f"(d[27]), "+f"(d[28]), "+f"(d[29]), "+f"(d[30]), "+f"(d[31])
    : "r"(a0), "r"(a1), "r"(a2), "r"(a3), "l"(descB));
}
__device__ __forceinline__ void mma_s(float (&d)[32], uint32_t a0, uint32_t a1, uint32_t a2, uint32_t a3, uint64_t descB) {
  asm volatile("wgmma.mma_async.sync.aligned.m64n64k16.f32.bf16.bf16 {%0, %1, %2, %3, %4, %5, %6, %7, %8, %9, %10, %11, %12, %13, %14, %15, %16, %17, %18, %19, %20, %21, %22, %23, %24, %25, %26, %27, %28, %29, %30, %31}, "
    "{%32, %33, %34, %35}, %36, 1, 1, 1, 1;"
    : "+f"(d[0]), "+f"(d[1]), "+f"(d[2]), "+f"(d[3]), "+f"(d[4]), "+f"(d[5]), "+f"(d[6]), "+f"(d[7]), "+f"(d[8]), "+f"(d[9]), "+f"(d[10]), "+f"(d[11]), "+f"(d[12]), "+f"(d[13]), "+f"(d[14]), "+f"(d[15]), "+f"(d[16]), "+f"(d[17]), "+f"(d[18]), "+f"(d[19]), "+f"(d[20]), "+f"(d[21]), "+f"(d[22]), "+f"(d[23]), "+f"(d[24]), "+f"(d[25]), "+f"(d[26]), "+f"(d[27]), "+f"(d[28]), "+f"(d[29]), "+f"(d[30]), "+f"(d[31])
    : "r"(a0), "r"(a1), "r"(a2), "r"(a3), "l"(descB));
}
__device__ __forceinline__ void mma_p_init(float (&d)[28], uint32_t a0, uint32_t a1, uint32_t a2, uint32_t a3, uint64_t descB) {
  asm volatile("wgmma.mma_async.sync.aligned.m64n56k16.f32.bf16.bf16 {%0, %1, %2, %3, %4, %5, %6, %7, %8, %9, %10, %11, %12, %13, %14, %15, %16, %17, %18, %19, %20, %21, %22, %23, %24, %25, %26, %27}, "
    "{%28, %29, %30, %31}, %32, 0, 1, 1, 0;"
    : "=f"(d[0]), "=f"(d[1]), "=f"(d[2]), "=f"(d[3]), "=f"(d[4]), "=f"(d[5]), "=f"(d[6]), "=f"(d[7]), "=f"(d[8]), "=f"(d[9]), "=f"(d[10]), "=f"(d[11]), "=f"(d[12]), "=f"(d[13]), "=f"(d[14]), "=f"(d[15]), "=f"(d[16]), "=f"(d[17]), "=f"(d[18]), "=f"(d[19]), "=f"(d[20]), "=f"(d[21]), "=f"(d[22]), "=f"(d[23]), "=f"(d[24]), "=f"(d[25]), "=f"(d[26]), "=f"(d[27])
    : "r"(a0), "r"(a1), "r"(a2), "r"(a3), "l"(descB));
}
__device__ __forceinline__ void mma_p(float (&d)[28], uint32_t a0, uint32_t a1, uint32_t a2, uint32_t a3, uint64_t descB) {
  asm volatile("wgmma.mma_async.sync.aligned.m64n56k16.f32.bf16.bf16 {%0, %1, %2, %3, %4, %5, %6, %7, %8, %9, %10, %11, %12, %13, %14, %15, %16, %17, %18, %19, %20, %21, %22, %23, %24, %25, %26, %27}, "
    "{%28, %29, %30, %31}, %32, 1, 1, 1, 0;"
    : "+f"(d[0]), "+f"(d[1]), "+f"(d[2]), "+f"(d[3]), "+f"(d[4]), "+f"(d[5]), "+f"(d[6]), "+f"(d[7]), "+f"(d[8]), "+f"(d[9]), "+f"(d[10]), "+f"(d[11]), "+f"(d[12]), "+f"(d[13]), "+f"(d[14]), "+f"(d[15]), "+f"(d[16]), "+f"(d[17]), "+f"(d[18]), "+f"(d[19]), "+f"(d[20]), "+f"(d[21]), "+f"(d[22]), "+f"(d[23]), "+f"(d[24]), "+f"(d[25]), "+f"(d[26]), "+f"(d[27])
    : "r"(a0), "r"(a1), "r"(a2), "r"(a3), "l"(descB));
}
__device__ __forceinline__ void mma_o_init(float (&d)[48], uint32_t a0, uint32_t a1, uint32_t a2, uint32_t a3, uint64_t descB) {
  asm volatile("wgmma.mma_async.sync.aligned.m64n96k16.f32.bf16.bf16 {%0, %1, %2, %3, %4, %5, %6, %7, %8, %9, %10, %11, %12, %13, %14, %15, %16, %17, %18, %19, %20, %21, %22, %23, %24, %25, %26, %27, %28, %29, %30, %31, %32, %33, %34, %35, %36, %37, %38, %39, %40, %41, %42, %43, %44, %45, %46, %47}, "
    "{%48, %49, %50, %51}, %52, 0, 1, 1, 1;"
    : "=f"(d[0]), "=f"(d[1]), "=f"(d[2]), "=f"(d[3]), "=f"(d[4]), "=f"(d[5]), "=f"(d[6]), "=f"(d[7]), "=f"(d[8]), "=f"(d[9]), "=f"(d[10]), "=f"(d[11]), "=f"(d[12]), "=f"(d[13]), "=f"(d[14]), "=f"(d[15]), "=f"(d[16]), "=f"(d[17]), "=f"(d[18]), "=f"(d[19]), "=f"(d[20]), "=f"(d[21]), "=f"(d[22]), "=f"(d[23]), "=f"(d[24]), "=f"(d[25]), "=f"(d[26]), "=f"(d[27]), "=f"(d[28]), "=f"(d[29]), "=f"(d[30]), "=f"(d[31]), "=f"(d[32]), "=f"(d[33]), "=f"(d[34]), "=f"(d[35]), "=f"(d[36]), "=f"(d[37]), "=f"(d[38]), "=f"(d[39]), "=f"(d[40]), "=f"(d[41]), "=f"(d[42]), "=f"(d[43]), "=f"(d[44]), "=f"(d[45]), "=f"(d[46]), "=f"(d[47])
    : "r"(a0), "r"(a1), "r"(a2), "r"(a3), "l"(descB));
}
__device__ __forceinline__ void mma_o(float (&d)[48], uint32_t a0, uint32_t a1, uint32_t a2, uint32_t a3, uint64_t descB) {
  asm volatile("wgmma.mma_async.sync.aligned.m64n96k16.f32.bf16.bf16 {%0, %1, %2, %3, %4, %5, %6, %7, %8, %9, %10, %11, %12, %13, %14, %15, %16, %17, %18, %19, %20, %21, %22, %23, %24, %25, %26, %27, %28, %29, %30, %31, %32, %33, %34, %35, %36, %37, %38, %39, %40, %41, %42, %43, %44, %45, %46, %47}, "
    "{%48, %49, %50, %51}, %52, 1, 1, 1, 1;"
    : "+f"(d[0]), "+f"(d[1]), "+f"(d[2]), "+f"(d[3]), "+f"(d[4]), "+f"(d[5]), "+f"(d[6]), "+f"(d[7]), "+f"(d[8]), "+f"(d[9]), "+f"(d[10]), "+f"(d[11]), "+f"(d[12]), "+f"(d[13]), "+f"(d[14]), "+f"(d[15]), "+f"(d[16]), "+f"(d[17]), "+f"(d[18]), "+f"(d[19]), "+f"(d[20]), "+f"(d[21]), "+f"(d[22]), "+f"(d[23]), "+f"(d[24]), "+f"(d[25]), "+f"(d[26]), "+f"(d[27]), "+f"(d[28]), "+f"(d[29]), "+f"(d[30]), "+f"(d[31]), "+f"(d[32]), "+f"(d[33]), "+f"(d[34]), "+f"(d[35]), "+f"(d[36]), "+f"(d[37]), "+f"(d[38]), "+f"(d[39]), "+f"(d[40]), "+f"(d[41]), "+f"(d[42]), "+f"(d[43]), "+f"(d[44]), "+f"(d[45]), "+f"(d[46]), "+f"(d[47])
    : "r"(a0), "r"(a1), "r"(a2), "r"(a3), "l"(descB));
}

__device__ __forceinline__ void wg_fence() { asm volatile("wgmma.fence.sync.aligned;" ::: "memory"); }
__device__ __forceinline__ void wg_commit() { asm volatile("wgmma.commit_group.sync.aligned;" ::: "memory"); }
template <int N> __device__ __forceinline__ void wg_wait() { asm volatile("wgmma.wait_group.sync.aligned %0;" ::"n"(N) : "memory"); }
template <int N> __device__ __forceinline__ void pin(float (&d)[N]) {
#pragma unroll
  for (int i = 0; i < N; i++) asm volatile("" : "+f"(d[i])::"memory");
}
template <int N> __device__ __forceinline__ void pin(uint32_t (&d)[N]) {
#pragma unroll
  for (int i = 0; i < N; i++) asm volatile("" : "+r"(d[i])::"memory");
}
__device__ __forceinline__ uint64_t mkdesc(uint32_t lo, uint32_t hi) { return ((uint64_t)hi << 32) | lo; }
constexpr uint32_t HI_X = (3072 >> 4) | (1u << 30);
constexpr uint32_t HI_KV = (1024 >> 4) | (1u << 30);
constexpr uint32_t HI_W = (512 >> 4) | (2u << 30);
constexpr uint32_t HI_O = (1536 >> 4) | (2u << 30);
constexpr uint32_t LO_O = (1u << 16) + ((SM_BASE + OFF_OIN) >> 4);
constexpr uint32_t LO_WQ = ((12288 >> 4) << 16) + ((SM_BASE + OFF_WQ) >> 4);
constexpr uint32_t LO_WO = ((6144 >> 4) << 16) + ((SM_BASE + OFF_WO) >> 4);
constexpr uint32_t LO_X = (1u << 16) + ((SM_BASE + OFF_X) >> 4);
constexpr uint32_t LO_KV = (1u << 16) + ((SM_BASE + OFF_KV) >> 4);

__device__ __forceinline__ uint32_t pack_bf16(float lo, float hi) {
  uint32_t r;
  asm("cvt.rn.bf16x2.f32 %0, %1, %2;" : "=r"(r) : "f"(hi), "f"(lo));
  return r;
}
__device__ __forceinline__ float ex2(float x) {
  float r;
  asm("ex2.approx.ftz.f32 %0, %1;" : "=f"(r) : "f"(x));
  return r;
}
__device__ __forceinline__ float rcp(float x) {
  float r;
  asm("rcp.approx.ftz.f32 %0, %1;" : "=f"(r) : "f"(x));
  return r;
}
__device__ __forceinline__ bool elect() {
  uint32_t p;
  asm volatile("{\n.reg .pred P;\nelect.sync _|P, 0xffffffff;\nselp.u32 %0, 1, 0, P;\n}" : "=r"(p));
  return p;
}
__device__ __forceinline__ void mbar_init(uint32_t bar, uint32_t cnt) {
  asm volatile("mbarrier.init.shared::cta.b64 [%0], %1;" ::"r"(bar), "r"(cnt) : "memory");
}
__device__ __forceinline__ void mbar_wait(uint32_t bar, uint32_t parity) {
  asm volatile(
      "{\n.reg .pred p;\n.reg .u32 n;\n"
      "mbarrier.try_wait.parity.shared::cta.b64 p, [%0], %1;\n"
      "@p bra DONE;\n"
      "mov.u32 n, 0;\n"
      "LOOP:\n"
      "mbarrier.try_wait.parity.shared::cta.b64 p, [%0], %1;\n"
      "@p bra DONE;\n"
      "add.u32 n, n, 1;\n"
      "setp.lt.u32 p, n, 0x400000;\n"
      "@p bra LOOP;\n"
      "trap;\n"
      "DONE:\n}\n" ::"r"(bar), "r"(parity)
      : "memory");
}
__device__ __forceinline__ void mbar_arrive_cluster(uint32_t bar) {
  asm volatile("mbarrier.arrive.shared::cluster.b64 _, [%0];" ::"r"(bar) : "memory");
}
__device__ __forceinline__ void mbar_expect_tx(uint32_t bar, uint32_t bytes) {
  asm volatile("mbarrier.arrive.expect_tx.shared::cta.b64 _, [%0], %1;" ::"r"(bar), "r"(bytes) : "memory");
}
__device__ __forceinline__ uint32_t mapa(uint32_t addr, uint32_t rank) {
  uint32_t r;
  asm("mapa.shared::cluster.u32 %0, %1, %2;" : "=r"(r) : "r"(addr), "r"(rank));
  return r;
}
template <int ID> __device__ __forceinline__ void tok_wait() { asm volatile("bar.sync %0, 256;" ::"n"(ID) : "memory"); }
template <int ID> __device__ __forceinline__ void tok_pass() { asm volatile("bar.arrive %0, 256;" ::"n"(ID) : "memory"); }
__device__ __forceinline__ void fence_async() { asm volatile("fence.proxy.async.shared::cta;" ::: "memory"); }
__device__ __forceinline__ void stsm4(uint32_t addr, uint32_t r0, uint32_t r1, uint32_t r2, uint32_t r3) {
  asm volatile("stmatrix.sync.aligned.m8n8.x4.shared.b16 [%0], {%1,%2,%3,%4};" ::"r"(addr), "r"(r0), "r"(r1), "r"(r2), "r"(r3) : "memory");
}
__device__ __forceinline__ void lds128(uint32_t addr, uint32_t& r0, uint32_t& r1, uint32_t& r2, uint32_t& r3) {
  asm volatile("ld.shared.v4.b32 {%0,%1,%2,%3}, [%4];" : "=r"(r0), "=r"(r1), "=r"(r2), "=r"(r3) : "r"(addr) : "memory");
}
template <int OFF>
__device__ __forceinline__ void st_async(uint32_t addr, uint32_t bar, uint32_t r0, uint32_t r1, uint32_t r2, uint32_t r3) {
  asm volatile("st.async.shared::cluster.mbarrier::complete_tx::bytes.v4.b32 [%0+%6], {%1,%2,%3,%4}, [%5];" ::"r"(addr), "r"(r0),
               "r"(r1), "r"(r2), "r"(r3), "r"(bar), "n"(OFF)
               : "memory");
}
__device__ __forceinline__ void tma5_mc(uint32_t dst, const CUtensorMap* tm, uint32_t bar, int c2, int c4) {
  asm volatile(
      "cp.async.bulk.tensor.5d.shared::cluster.global.mbarrier::complete_tx::bytes.multicast::cluster "
      "[%0], [%1, {0, 0, %3, 0, %4}], [%2], %5;" ::"r"(dst), "l"(tm), "r"(bar), "r"(c2), "r"(c4), "h"((uint16_t)3)
      : "memory");
}
__device__ __forceinline__ void tma5_pf(const CUtensorMap* tm, int c2, int c4) {
  asm volatile("cp.async.bulk.prefetch.tensor.5d.L2.global [%0, {0, 0, %1, 0, %2}];" ::"l"(tm), "r"(c2), "r"(c4) : "memory");
}
__device__ __forceinline__ void tma3(uint32_t dst, const CUtensorMap* tm, uint32_t bar, int c1, int c2) {
  asm volatile("cp.async.bulk.tensor.3d.shared::cluster.global.mbarrier::complete_tx::bytes [%0], [%1, {0, %3, %4}], [%2];" ::"r"(dst),
               "l"(tm), "r"(bar), "r"(c1), "r"(c2)
               : "memory");
}
#define TR_SETUP(kv)
#define TR(k)
#define TRP(k)

#define WS_BEGIN
#define WS_END(k)
#define CLKP(k)

constexpr float SQRT_HD = 6.92820323027551f;
constexpr float SM_C = 1.4426950408889634f / SQRT_HD;

template <int LO, int HI>
__device__ __forceinline__ void s_init(float (&s)[32], const uint32_t (&mk)[16], const uint32_t (&b)[16]) {
#pragma unroll
  for (int i = 0; i < 16; i++) {
    if ((i & 7) < LO || (i & 7) >= HI) continue;
    uint32_t t;
    asm("fma.rn.bf16x2 %0, %1, %2, %3;" : "=r"(t) : "r"(mk[i]), "r"(0x40DE40DEu), "r"(b[i]));
    const int o = 4 * (i & 7) + 2 * (i >> 3);
    s[o] = __uint_as_float(t << 16);
    s[o + 1] = __uint_as_float(t);
    asm volatile("" : "+f"(s[o]), "+f"(s[o + 1])::"memory");
  }
}
__device__ __forceinline__ uint32_t pack_bias(float lo, float hi) {
  uint32_t l = pack_bf16(lo, 0.f), h = __float_as_uint(hi);
  int mag = max((int)(h & 0x7fffffffu) - (int)l + 0x8000, 0);
  return (h & 0x80000000u) | (mag & 0x7fff0000u) | l;
}
__device__ __forceinline__ void rowmax_i(const float (&s)[32], int& i0, int& i1) {
#define FI(x) __float_as_int(x)
  i0 = max(FI(s[0]), FI(s[1])), i1 = max(FI(s[2]), FI(s[3]));
  int k0 = __vimax3_s32(FI(s[4]), FI(s[5]), FI(s[8])), k1 = __vimax3_s32(FI(s[6]), FI(s[7]), FI(s[10]));
  i0 = __vimax3_s32(i0, FI(s[9]), FI(s[12]));   i1 = __vimax3_s32(i1, FI(s[11]), FI(s[14]));
  k0 = __vimax3_s32(k0, FI(s[13]), FI(s[16]));  k1 = __vimax3_s32(k1, FI(s[15]), FI(s[18]));
  i0 = __vimax3_s32(i0, FI(s[17]), FI(s[20]));  i1 = __vimax3_s32(i1, FI(s[19]), FI(s[22]));
  k0 = __vimax3_s32(k0, FI(s[21]), FI(s[24]));  k1 = __vimax3_s32(k1, FI(s[23]), FI(s[26]));
  i0 = __vimax3_s32(i0, FI(s[25]), FI(s[28]));  i1 = __vimax3_s32(i1, FI(s[27]), FI(s[30]));
  i0 = __vimax3_s32(i0, k0, FI(s[29]));         i1 = __vimax3_s32(i1, k1, FI(s[31]));
#undef FI
}
__device__ __forceinline__ void quadmax_i(int& i0, int& i1, int x) {
  i0 = max(i0, __shfl_xor_sync(0xffffffffu, i0, x));
  i1 = max(i1, __shfl_xor_sync(0xffffffffu, i1, x));
}
__device__ __forceinline__ void rowmax_f(const float (&s)[32], int& i0, int& i1) {
  float m0 = fmaxf(s[0], s[1]), m1 = fmaxf(s[2], s[3]);
#pragma unroll
  for (int j = 1; j < 8; j++) {
    m0 = fmaxf(m0, fmaxf(s[4 * j], s[4 * j + 1]));
    m1 = fmaxf(m1, fmaxf(s[4 * j + 2], s[4 * j + 3]));
  }
  m0 = fmaxf(m0, __shfl_xor_sync(0xffffffffu, m0, 1));
  m1 = fmaxf(m1, __shfl_xor_sync(0xffffffffu, m1, 1));
  m0 = fmaxf(m0, __shfl_xor_sync(0xffffffffu, m0, 2));
  m1 = fmaxf(m1, __shfl_xor_sync(0xffffffffu, m1, 2));
  i0 = __float_as_int(m0), i1 = __float_as_int(m1);
}
template <int LO, int HI>
__device__ __forceinline__ void exp_part(const float (&s)[32], uint32_t (&p)[16], float m0, float m1) {
#pragma unroll
  for (int i = LO; i < HI; i++) {
    float m = (i & 1) ? m1 : m0;
    p[i] = pack_bf16(ex2(fmaf(s[2 * i], SM_C, m)), ex2(fmaf(s[2 * i + 1], SM_C, m)));
    asm volatile("" : "+r"(p[i])::"memory");
  }
}
template <int SUM, int OFF>
__device__ __forceinline__ void normalize(const float (&o)[28], uint32_t (&f)[12]) {
  float r0 = rcp(o[SUM]), r1 = rcp(o[SUM + 2]);
#pragma unroll
  for (int j = 0; j < 12; j++) {
    float r = (j & 1) ? r1 : r0;
    f[j] = pack_bf16(o[OFF + 2 * j] * r, o[OFF + 2 * j + 1] * r);
  }
}

__global__ void __cluster_dims__(2, 1, 1) __launch_bounds__(384, 1)
swin_attn_kernel(const __grid_constant__ Maps maps, const __nv_bfloat16* __restrict__ rpb, const int* __restrict__ rp_idx) {
  extern __shared__ __align__(1024) uint8_t smem_raw[];
  const uint32_t sb = (uint32_t)__cvta_generic_to_shared(smem_raw);
  const int tid = threadIdx.x;
  const int wg = __shfl_sync(0xffffffffu, tid >> 7, 0);
  const int warp = __shfl_sync(0xffffffffu, (tid >> 5) & 3, 0);
  const int lane = tid & 31;
  const int rank = blockIdx.x & 1;
  const int cl = blockIdx.x >> 1;
  const int ncl = gridDim.x >> 1;
  const uint32_t bars = sb + OFF_BAR;
  TRP(0);
  CLKP(0);

  if (wg == KV_WG) {
    if (warp == 3) {
      if (elect()) {
        if ((sb & 0x3FFFF) != SM_BASE) __trap();
#pragma unroll
        for (int a = 0; a < 2; a++) {
          mbar_init(bars + B_XFULL + 8 * a, 1);
          mbar_init(bars + B_XEMPTY + 8 * a, 1);
          mbar_init(bars + B_OFULL + 8 * a, 1);
          mbar_init(bars + B_OEMPTY + 8 * a, 4);
        }
        mbar_init(bars + B_WKV, 1);
        mbar_init(bars + B_WQ, 1);
        mbar_init(bars + B_WO, 1);
        asm volatile("fence.mbarrier_init.release.cluster;" ::: "memory");
        fence_async();
        mbar_expect_tx(bars + B_WKV, 73728);
        mbar_expect_tx(bars + B_WQ, 36864);
        mbar_expect_tx(bars + B_WO, 36864);
        mbar_expect_tx(bars + B_XFULL, X_BYTES + M_BYTES);
        mbar_expect_tx(bars + B_XFULL + 8, X_BYTES + M_BYTES);
        tma3(sb + OFF_KV, &maps.wqkv, bars + B_WKV, 0, 6 + 3 * rank);
        tma3(sb + OFF_KV + STAGE, &maps.wqkv, bars + B_WKV, 0, 12 + 3 * rank);
        tma3(sb + OFF_WQ, &maps.wqkv, bars + B_WQ, 0, 3 * rank);
      }
      __syncwarp();
    }
    auto prefetch = [&](int win) {
      if (warp < 2) tma5_pf(&maps.x, (((win >> 3) & ~7) + 4 + 4 * rank) & 511, (win * 4 + 2 + 2 * warp) & 255);
      else tma5_pf(&maps.mask, 0, 2 * win + rank);
    };
    auto load = [&](int win, int a) {
      if (warp < 2)
        tma5_mc(sb + OFF_X + a * STAGE + rank * 12288 + warp * 6144, &maps.x, bars + B_XFULL + 8 * a,
                (((win >> 3) & ~7) + 4 + 4 * rank) & 511, (win * 4 + 2 + 2 * warp) & 255);
      else tma5_mc(sb + OFF_MASK + a * STAGE + rank * 4096, &maps.mask, bars + B_XFULL + 8 * a, 0, 2 * win + rank);
    };
    if (warp < 3 && elect()) {
      for (int j = 0; j <= 1 + PF_DIST; j++) prefetch(cl + j * ncl);
    }
    __syncwarp();
    asm volatile("barrier.cluster.arrive.relaxed.aligned;" ::: "memory");
    asm volatile("setmaxnreg.inc.sync.aligned.u32 216;");
    asm volatile("barrier.cluster.wait.aligned;" ::: "memory");
    TRP(1);
    if (elect()) {
      if (warp < 3) {
        load(cl, 0);
        load(cl + ncl, 1);
      } else {
        tma3(sb + OFF_WO, &maps.wo, bars + B_WO, 96 * rank, 3 * rank);
        for (int nb = 0; nb < 3; nb++)
          asm volatile("cp.async.bulk.tensor.5d.shared::cluster.global.mbarrier::complete_tx::bytes [%0], [%1, {%3, 0, 0, 0, %4}], [%2];" ::"r"(
                           sb + OFF_WO + 18432 + nb * 6144), "l"(&maps.wop), "r"(bars + B_WO), "r"(96 * rank + 32 * nb), "r"(3 * (rank ^ 1))
                       : "memory");
      }
    }
    __syncwarp();
    uint32_t w[3][48];
    {
      const uint32_t la = sb + OFF_KV + (warp >> 1) * 12288 + (8 * (lane >> 4) + (lane & 7)) * 64 +
                          (((2 * (warp & 1) + ((lane >> 3) & 1)) ^ ((lane & 7) >> 1)) << 4);
      mbar_wait(bars + B_WKV, 0);
      TRP(2);
#pragma unroll
      for (int s = 0; s < 3; s++)
#pragma unroll
        for (int ks = 0; ks < 12; ks++)
          asm volatile("ldmatrix.sync.aligned.m8n8.x4.trans.shared.b16 {%0,%1,%2,%3}, [%4];"
                       : "=r"(w[s][4 * ks]), "=r"(w[s][4 * ks + 1]), "=r"(w[s][4 * ks + 2]), "=r"(w[s][4 * ks + 3])
                       : "r"(la + s * 24576 + (s == 2 || (s == 1 && warp >= 2) ? STAGE - 36864 : 0) + ks * 1024)
                       : "memory");
      asm volatile("bar.sync %0, 128;" ::"n"((int)BAR_STAGE) : "memory");
      asm volatile("st.shared.v4.b32 [%0], {%1,%1,%1,%1};" ::"r"(sb + OFF_KV + (warp >> 1) * STAGE + 144 * 128 + (tid & 63) * 16), "r"(0x3F803F80u) : "memory");
    }
    TRP(3);
    uint32_t sta[4];
#pragma unroll
    for (int jj = 0; jj < 4; jj++) {
      sta[jj] = sb + OFF_KV + (16 * warp + (lane & 15)) * 128 + (((2 * jj + (lane >> 4)) ^ (lane & 7)) << 4);
      asm volatile("" : "+r"(sta[jj]));
    }
    const uint32_t xe_rem = mapa(bars + B_XEMPTY, rank ^ 1);
    const uint32_t v1off = warp > 0 ? 1024 : 0;

    float acc[32];
    uint32_t pk[16];
    auto store = [&](uint32_t off) {
#pragma unroll
      for (int jj = 0; jj < 4; jj++) stsm4(sta[jj] + off, pk[4 * jj], pk[4 * jj + 1], pk[4 * jj + 2], pk[4 * jj + 3]);
    };
    auto issue = [&](int s, uint32_t xd, bool st, uint32_t off) {
#pragma unroll
      for (int ks = 0; ks < 12; ks++) {
        uint64_t db = mkdesc(xd + (((ks >> 2) * 1024 + (ks & 3) * 32) >> 4), HI_X);
        if (ks == 0) mma_kv_init(acc, w[s][0], w[s][1], w[s][2], w[s][3], db);
        else mma_kv(acc, w[s][4 * ks], w[s][4 * ks + 1], w[s][4 * ks + 2], w[s][4 * ks + 3], db);
        if (ks == ST_AT && st) {
          __syncwarp();
          store(off);
          __syncwarp();
        }
      }
      wg_commit();
    };
    auto convert = [&]() {
      wg_wait<0>();
      pin(acc);
#pragma unroll
      for (int j = 0; j < 16; j++) pk[j] = pack_bf16(acc[2 * j], acc[2 * j + 1]);
      pin(pk);
    };

    mbar_wait(bars + B_XFULL, 0);
    TRP(4);
    wg_fence();
    tok_wait<T0>();
    issue(0, LO_X, false, 0);
    tok_pass<T1>();
    [[maybe_unused]] int i = 0;
    int nxt = cl + ncl;
    uint32_t ph = 0;
    auto step = [&](auto A) -> bool {
      constexpr int a = decltype(A)::value;
      constexpr uint32_t xd = LO_X + a * (STAGE >> 4);
      const bool more = nxt < NWIN;
      TR_SETUP(1);
      TR(0);
      convert();
      TR(1);
      wg_fence();
      tok_wait<T2>();
      TR(2);
      issue(1, xd, true, a * STAGE);
      tok_pass<T3>();
      TR(3);
      if (warp < 3 && nxt + (1 + PF_DIST) * ncl < NWIN && elect()) prefetch(nxt + (1 + PF_DIST) * ncl);
      __syncwarp();
      TR(4);
      convert();
      store(a * STAGE + 8192);
      fence_async();
      TR(5);
      wg_fence();
      tok_wait<T5>();
      TR(6);
      issue(2, xd, false, 0);
      tok_pass<T6>();
      if (more) { WS_BEGIN; mbar_wait(bars + B_XFULL + 8 * (a ^ 1), a ? ph ^ 1 : ph); WS_END(0); WS_END(8 + i); }
      TR(7);
      convert();
      TR(8);
      wg_fence();
      tok_wait<T0>();
      TR(9);
      if (tid == KV_WG * 128) mbar_arrive_cluster(xe_rem + 8 * a);
      issue(0, LO_X + (a ^ 1) * (STAGE >> 4), true, a * STAGE + 16384 + v1off);
      tok_pass<T1>();
      TR(10);
      fence_async();
      tok_pass<T7>();
      nxt += ncl;
      if (nxt < NWIN) {
        { WS_BEGIN; mbar_wait(bars + B_XEMPTY + 8 * a, ph); WS_END(1); }
        if (elect()) {
          if (warp < 3) load(nxt, a);
          else mbar_expect_tx(bars + B_XFULL + 8 * a, X_BYTES + M_BYTES);
        }
        __syncwarp();
      }
      i++;
      return more;
    };
    while (step(IC<0>{}) && step(IC<1>{})) ph ^= 1;
    tok_wait<T2>();
    tok_pass<T3>();
    tok_wait<T5>();
    wg_wait<0>();
    pin(acc);
  } else {
    const int a = wg - (KV_WG == 0 ? 1 : 0);
    const int g = lane >> 2, q = lane & 3;
    const uint32_t bar = bars + 8 * a;
    asm volatile("barrier.cluster.arrive.relaxed.aligned;" ::: "memory");
    asm volatile("setmaxnreg.dec.sync.aligned.u32 144;");
    uint32_t bias0[16], bias1[16];
    {
      const int ty = 4 * (warp >> 1) + (g >> 1), tx = 4 * (warp & 1) + (g & 1);
#pragma unroll
      for (int c = 0; c < 4; c++) {
        const int4* ip = reinterpret_cast<const int4*>(rp_idx + (ty * 8 + tx + 2 * (c >> 1)) * 64 + 8 * (q + 4 * (c & 1)));
        int4 i0 = __ldg(ip), i1 = __ldg(ip + 1);
        int id[8] = {i0.x, i0.y, i0.z, i0.w, i1.x, i1.y, i1.z, i1.w};
#pragma unroll
        for (int jj = 0; jj < 4; jj++) {
          uint32_t b0 = __ldg(reinterpret_cast<const uint32_t*>(rpb) + id[2 * jj] * 2 + rank);
          uint32_t b1 = __ldg(reinterpret_cast<const uint32_t*>(rpb) + id[2 * jj + 1] * 2 + rank);
          bias0[4 * c + jj] = pack_bias(__uint_as_float(b0 << 16) * SQRT_HD, __uint_as_float(b1 << 16) * SQRT_HD);
          bias1[4 * c + jj] = pack_bias(__uint_as_float(b0 & 0xffff0000u) * SQRT_HD, __uint_as_float(b1 & 0xffff0000u) * SQRT_HD);
        }
      }
      pin(bias0);
      pin(bias1);
    }
    TRP(1);
    asm volatile("barrier.cluster.wait.aligned;" ::: "memory");
    TRP(2);

    const int mrow = 16 * warp + (g >> 1) + 4 * (g & 1);
    const uint32_t mk_addr = sb + OFF_MASK + a * STAGE + mrow * 128 + ((q ^ (mrow & 7)) << 4);
    const uint32_t ostage = sb + OFF_OIN + a * STAGE + warp * 3072;
    const uint32_t ost = ostage + ((lane >> 3) & 1) * 1536 + (lane & 7) * 64 + (((lane >> 4) ^ ((lane & 7) >> 1)) << 4);
    const uint32_t oin_rem = mapa(ostage + g * 64 + ((q ^ (g >> 1)) << 4), rank ^ 1);
    const uint32_t bar_rem = mapa(bar, rank ^ 1);
    mbar_wait(bars + B_WQ, 0);
    TRP(3);

    auto store_out = [&](int win) {
      fence_async();
      __syncwarp();
      if (win >= 0 && elect()) {
        int yy = (((win >> 3) & ~7) + 4 + 4 * (warp >> 1)) & 511;
        int xh = (win * 4 + 2 + 2 * (warp & 1)) & 255;
        asm volatile("cp.async.bulk.tensor.5d.global.shared::cta.bulk_group [%0, {0, 0, %2, %3, %4}], [%1];" ::"l"(&maps.out), "r"(ostage),
                     "r"(yy), "r"(3 * rank), "r"(xh)
                     : "memory");
        asm volatile("cp.async.bulk.commit_group;" ::: "memory");
      }
      __syncwarp();
    };
    float qa[48];
    float s0[32];
    uint32_t mk[16];
    auto load_mask = [&](uint32_t z) {
#pragma unroll
      for (int c = 0; c < 4; c++)
        lds128((c & 1 ? mk_addr ^ (64 + z) : mk_addr) + (c >> 1) * 1024, mk[4 * c], mk[4 * c + 1], mk[4 * c + 2], mk[4 * c + 3]);
    };
    auto pre_init = [&]() {
#pragma unroll
      for (int j = 0; j < 16; j++) asm("max.NaN.bf16x2 %0, %0, %1;" : "+r"(mk[j]) : "r"(0xFD80FD80u));
      pin(mk);
      s_init<PRE_T, 8>(s0, mk, bias0);
    };
    auto issue_q = [&](uint32_t ua) {
#pragma unroll
      for (int ks = 0; ks < 12; ks++) {
        uint64_t da = mkdesc(ua + LO_X + (((ks >> 2) * 1024 + (ks & 3) * 32) >> 4), HI_X);
        uint64_t db = mkdesc(LO_WQ + ks * 64, HI_W);
        if (ks == 0) mma_q_init(qa, da, db);
        else mma_q(qa, da, db);
      }
      wg_commit();
    };
    if (a == 1) {
      tok_pass<T0>();
      tok_wait<T4>();
      tok_pass<T5>();
    }
    tok_wait<T1>();
    tok_pass<T2>();
    load_mask(0);
    wg_fence();
    tok_wait<T3>();
    issue_q(a * (STAGE >> 4));
    tok_pass<T4>();
    pre_init();
    mbar_wait(bars + B_WO, 0);
    uint32_t ph = 0;
    [[maybe_unused]] int i = a;
    int win = cl + a * ncl;
    for (; win < NWIN; win += 2 * ncl, ph ^= 1, i += 2) {
      TR_SETUP(0);
      TR(0);
      const uint32_t ua = a * (STAGE >> 4) + (win >> 20);
      const uint32_t kd = ua + LO_KV;
      const bool last = win + ncl >= NWIN;
      float s1[32];
      TR(1);
      wg_wait<0>();
      pin(qa);
      TR(2);
      uint32_t q0[12], q1[12];
#pragma unroll
      for (int j = 0; j < 12; j++) q0[j] = pack_bf16(qa[2 * j], qa[2 * j + 1]);
#pragma unroll
      for (int j = 0; j < 12; j++) q1[j] = pack_bf16(qa[24 + 2 * j], qa[25 + 2 * j]);
      pin(q0);
      pin(q1);
      s_init<0, PRE_T>(s0, mk, bias0);
      s_init<0, 8>(s1, mk, bias1);
      pin(s0);
      pin(s1);
      TR(3);
      wg_fence();
      tok_wait<T6>();
      TR(4);
#pragma unroll
      for (int ks = 0; ks < 3; ks++)
        mma_s(s0, q0[4 * ks], q0[4 * ks + 1], q0[4 * ks + 2], q0[4 * ks + 3], mkdesc(kd + ks * 128, HI_KV));
      wg_commit();
#pragma unroll
      for (int ks = 0; ks < 3; ks++)
        mma_s(s1, q1[4 * ks], q1[4 * ks + 1], q1[4 * ks + 2], q1[4 * ks + 3], mkdesc(kd + (3 + ks) * 128, HI_KV));
      wg_commit();
      tok_pass<T0>();
      store_out(win - 2 * ncl);
      int x0, x1, y0, y1;
      wg_wait<1>();
      pin(s0);
      pin(q0);
      TR(5);
      rowmax_i(s0, x0, x1);
      quadmax_i(x0, x1, 1);
      wg_wait<0>();
      pin(s1);
      pin(q1);
      rowmax_i(s1, y0, y1);
      quadmax_i(x0, x1, 2);
      quadmax_i(y0, y1, 1);
      quadmax_i(y0, y1, 2);
      if (__builtin_expect(__any_sync(0xffffffffu, (x0 | x1 | y0 | y1) < 0), 0)) {
        rowmax_f(s0, x0, x1);
        rowmax_f(s1, y0, y1);
      }
      uint32_t p0[16], p1[16];
      exp_part<0, 16>(s0, p0, __int_as_float(x0) * -SM_C, __int_as_float(x1) * -SM_C);
      TR(6);
      float o0[28], o1[28];
      wg_fence();
      tok_wait<T7>();
#pragma unroll
      for (int ks = 0; ks < 4; ks++) {
        uint64_t db = mkdesc(kd + ((96 * 128 + ks * 32) >> 4), HI_KV);
        if (ks == 0) mma_p_init(o0, p0[0], p0[1], p0[2], p0[3], db);
        else mma_p(o0, p0[4 * ks], p0[4 * ks + 1], p0[4 * ks + 2], p0[4 * ks + 3], db);
      }
      wg_commit();
      if (elect()) {
        { WS_BEGIN; asm volatile("cp.async.bulk.wait_group.read 0;" ::: "memory"); WS_END(4); }
        if (warp == 0) mbar_expect_tx(bar + B_OFULL, O_BYTES);
        mbar_arrive_cluster(bar_rem + B_OEMPTY);
      }
      __syncwarp();
      const float m0 = __int_as_float(y0) * -SM_C, m1 = __int_as_float(y1) * -SM_C;
      exp_part<0, 16>(s1, p1, m0, m1);
      TR(7);
      wg_fence();
      tok_wait<T4>();
      TR(8);
#pragma unroll
      for (int ks = 0; ks < 4; ks++) {
        uint64_t db = mkdesc(kd + ((144 * 128 + ks * 32) >> 4), HI_KV);
        if (ks == 0) mma_p_init(o1, p1[0], p1[1], p1[2], p1[3], db);
        else mma_p(o1, p1[4 * ks], p1[4 * ks + 1], p1[4 * ks + 2], p1[4 * ks + 3], db);
      }
      wg_commit();
      tok_pass<T5>();
      { WS_BEGIN; mbar_wait(bar + B_OEMPTY, ph); WS_END(2); }
      uint32_t f0[12], f1[12];
      wg_wait<1>();
      pin(o0);
      pin(p0);
      normalize<24, 0>(o0, f0);
      st_async<0>(oin_rem, bar_rem + B_OFULL, f0[0], f0[2], f0[4], f0[6]);
      st_async<1536>(oin_rem, bar_rem + B_OFULL, f0[1], f0[3], f0[5], f0[7]);
      wg_wait<0>();
      pin(o1);
      pin(p1);
      TR(9);
      normalize<0, 4>(o1, f1);
      st_async<512>(oin_rem, bar_rem + B_OFULL, f0[8], f0[10], f1[0], f1[2]);
      st_async<2048>(oin_rem, bar_rem + B_OFULL, f0[9], f0[11], f1[1], f1[3]);
      st_async<1024>(oin_rem, bar_rem + B_OFULL, f1[4], f1[6], f1[8], f1[10]);
      st_async<2560>(oin_rem, bar_rem + B_OFULL, f1[5], f1[7], f1[9], f1[11]);
      pin(f0);
      pin(f1);
      float (&oa)[48] = qa;
      TR(10);
      wg_fence();
      if (!last) tok_wait<T1>();
      TR(11);
#pragma unroll
      for (int ks = 0; ks < 3; ks++) {
        uint64_t db = mkdesc(LO_WO + ks * 64, HI_W);
        if (ks == 0) mma_o_init(oa, f0[0], f0[1], f0[2], f0[3], db);
        else mma_o(oa, f0[4 * ks], f0[4 * ks + 1], f0[4 * ks + 2], f0[4 * ks + 3], db);
      }
#pragma unroll
      for (int ks = 0; ks < 3; ks++)
        mma_o(oa, f1[4 * ks], f1[4 * ks + 1], f1[4 * ks + 2], f1[4 * ks + 3], mkdesc(LO_WO + (3 + ks) * 64, HI_W));
      { WS_BEGIN; mbar_wait(bar + B_OFULL, ph); WS_END(3); }
      asm volatile("fence.proxy.async::generic.acquire.sync_restrict::shared::cluster.cluster;" ::: "memory");
      wg_fence();
#pragma unroll
      for (int ks = 0; ks < 6; ks++)
        mma_q(oa, mkdesc(ua + LO_O + (((ks >> 1) * 512 + (ks & 1) * 32) >> 4), HI_O), mkdesc(LO_WO + (18432 >> 4) + ks * 64, HI_W));
      wg_commit();
      if (!last) tok_pass<T2>();
      load_mask(win >> 20);
      wg_wait<0>();
      pin(oa);
      pin(f0);
      pin(f1);
      TR(12);
#pragma unroll
      for (int jj = 0; jj < 6; jj++)
        stsm4((jj & 1 ? ost ^ (32 + (win >> 20)) : ost) + (jj >> 1) * 512, pack_bf16(oa[8 * jj], oa[8 * jj + 1]), pack_bf16(oa[8 * jj + 2], oa[8 * jj + 3]),
              pack_bf16(oa[8 * jj + 4], oa[8 * jj + 5]), pack_bf16(oa[8 * jj + 6], oa[8 * jj + 7]));
      wg_fence();
      if (!last) tok_wait<T3>();
      TR(13);
      issue_q(ua);
      if (!last) tok_pass<T4>();
      TR(14);
      pre_init();
    }
    store_out(win - 2 * ncl);
    wg_wait<0>();
    pin(qa);
    asm volatile("cp.async.bulk.wait_group 0;" ::: "memory");
    __syncwarp();
  }
  asm volatile("barrier.cluster.arrive.relaxed.aligned;" ::: "memory");
  asm volatile("barrier.cluster.wait.aligned;" ::: "memory");
  CLKP(1);
}

typedef CUresult (*EncodeFn)(CUtensorMap*, CUtensorMapDataType, cuuint32_t, void*, const cuuint64_t*, const cuuint64_t*,
                             const cuuint32_t*, const cuuint32_t*, CUtensorMapInterleave, CUtensorMapSwizzle,
                             CUtensorMapL2promotion, CUtensorMapFloatOOBfill);

void encode_map(EncodeFn encode, CUtensorMap* m, void* p, int rank, const cuuint64_t* dim, const cuuint64_t* str,
                const cuuint32_t* box, CUtensorMapSwizzle sw) {
  const cuuint32_t es[5] = {1, 1, 1, 1, 1};
  CUresult r = encode(m, CU_TENSOR_MAP_DATA_TYPE_BFLOAT16, rank, p, dim, str, box, es, CU_TENSOR_MAP_INTERLEAVE_NONE, sw,
                      CU_TENSOR_MAP_L2_PROMOTION_L2_128B, CU_TENSOR_MAP_FLOAT_OOB_FILL_NONE);
  if (r != CUDA_SUCCESS) fprintf(stderr, "tensor map encode failed: %d\n", (int)r);
}

}

extern "C" void kernel_launch(void* const* d_in, const int* in_sizes, int n_in, void* d_out, int out_size) {
  static EncodeFn encode = nullptr;
  static int grid = 0;
  if (!encode) {
    cudaDriverEntryPointQueryResult qr;
    void* fn = nullptr;
    cudaGetDriverEntryPoint("cuTensorMapEncodeTiled", &fn, cudaEnableDefault, &qr);
    encode = (EncodeFn)fn;
    cudaFuncSetAttribute(swin_attn_kernel, cudaFuncAttributeMaxDynamicSharedMemorySize, SMEM_BYTES);
    cudaLaunchConfig_t cfg = {};
    cfg.gridDim = dim3(132);
    cfg.blockDim = dim3(384);
    cfg.dynamicSmemBytes = SMEM_BYTES;
    cudaLaunchAttribute at;
    at.id = cudaLaunchAttributeClusterDimension;
    at.val.clusterDim.x = 2;
    at.val.clusterDim.y = 1;
    at.val.clusterDim.z = 1;
    cfg.attrs = &at;
    cfg.numAttrs = 1;
    int ncl = 0;
    if (cudaOccupancyMaxActiveClusters(&ncl, swin_attn_kernel, &cfg) != cudaSuccess || ncl < 1) {
      (void)cudaGetLastError();
      ncl = 66;
    }
    if (ncl > 256) ncl = 256;
    grid = 2 * ncl;
  }
  Maps maps;
  {
    const cuuint64_t dim[5] = {64, 2, 512, 3, 256}, str[4] = {384, 512 * 384, 128, 768};
    const cuuint32_t box[5] = {64, 2, 4, 3, 2};
    encode_map(encode, &maps.x, d_in[0], 5, dim, str, box, CU_TENSOR_MAP_SWIZZLE_128B);
  }
  {
    const cuuint64_t dim[5] = {64, 4, 2, 4, 8192}, str[4] = {1024, 128, 256, 4096};
    const cuuint32_t box[5] = {64, 4, 2, 4, 1};
    encode_map(encode, &maps.mask, d_in[5], 5, dim, str, box, CU_TENSOR_MAP_SWIZZLE_128B);
  }
  {
    const cuuint64_t dim[5] = {32, 2, 512, 6, 256}, str[4] = {384, 512 * 384, 64, 768};
    const cuuint32_t box[5] = {32, 2, 4, 3, 2};
    encode_map(encode, &maps.out, d_out, 5, dim, str, box, CU_TENSOR_MAP_SWIZZLE_64B);
  }
  {
    const cuuint64_t dim[3] = {32, 192, 18}, str[2] = {576 * 2, 64};
    const cuuint32_t box[3] = {32, 192, 3};
    encode_map(encode, &maps.wqkv, d_in[1], 3, dim, str, box, CU_TENSOR_MAP_SWIZZLE_64B);
    const cuuint64_t dim2[3] = {32, 192, 6}, str2[2] = {192 * 2, 64};
    const cuuint32_t box2[3] = {32, 96, 3};
    encode_map(encode, &maps.wo, d_in[2], 3, dim2, str2, box2, CU_TENSOR_MAP_SWIZZLE_64B);
    const cuuint64_t dim3_[5] = {192, 2, 4, 4, 6}, str3[4] = {384, 8 * 384, 2 * 384, 32 * 384};
    const cuuint32_t box3[5] = {32, 2, 4, 4, 3};
    encode_map(encode, &maps.wop, d_in[2], 5, dim3_, str3, box3, CU_TENSOR_MAP_SWIZZLE_64B);
  }
  swin_attn_kernel<<<grid, 384, SMEM_BYTES>>>(maps, (const __nv_bfloat16*)d_in[3], (const int*)d_in[4]);
}
```

```cpp
#include <cuda_runtime.h>
#include <cuda_bf16.h>
#include <cuda.h>
#include <stdint.h>
#include <stdio.h>

namespace {

constexpr int NWIN = 4096;
#define KV_WG 0
#define ST_AT 3
#define PRE_T 8
#define PF_DIST 0

constexpr uint32_t SM_BASE  = 1024;
constexpr uint32_t OFF_WQ   = 0;
constexpr uint32_t OFF_WO   = 36864;
constexpr uint32_t STAGE    = 70656;
constexpr uint32_t OFF_X    = 73728;
constexpr uint32_t X_BYTES  = 24576;
constexpr uint32_t OFF_MASK = OFF_X + X_BYTES;
constexpr uint32_t M_BYTES  = 8192;
constexpr uint32_t OFF_KV   = OFF_MASK + M_BYTES;
constexpr uint32_t OFF_OIN  = OFF_KV + 25600;
constexpr uint32_t O_BYTES  = 12288;
constexpr uint32_t OFF_BAR  = 215040;
constexpr uint32_t SMEM_BYTES = OFF_BAR + 1024;
constexpr uint32_t B_XFULL = 0, B_XEMPTY = 16, B_OFULL = 32, B_OEMPTY = 48, B_WKV = 64, B_WQ = 72, B_WO = 80;
enum { T0 = 1, T1, T2, T3, T4, T5, T6, T7, BAR_BIAS, BAR_STAGE };

template <int V> struct IC { static constexpr int value = V; };
struct Maps { CUtensorMap x, mask, out, wqkv, wo, wop; };

__device__ __forceinline__ void mma_q_init(float (&d)[48], uint64_t descA, uint64_t descB) {
  asm volatile("wgmma.mma_async.sync.aligned.m64n96k16.f32.bf16.bf16 {%0, %1, %2, %3, %4, %5, %6, %7, %8, %9, %10, %11, %12, %13, %14, %15, %16, %17, %18, %19, %20, %21, %22, %23, %24, %25, %26, %27, %28, %29, %30, %31, %32, %33, %34, %35, %36, %37, %38, %39, %40, %41, %42, %43, %44, %45, %46, %47}, "
    "%48, %49, 0, 1, 1, 0, 1;"
    : "+f"(d[0]), "+f"(d[1]), "+f"(d[2]), "+f"(d[3]), "+f"(d[4]), "+f"(d[5]), "+f"(d[6]), "+f"(d[7]), "+f"(d[8]), "+f"(d[9]), "+f"(d[10]), "+f"(d[11]), "+f"(d[12]), "+f"(d[13]), "+f"(d[14]), "+f"(d[15]), "+f"(d[16]), "+f"(d[17]), "+f"(d[18]), "+f"(d[19]), "+f"(d[20]), "+f"(d[21]), "+f"(d[22]), "+f"(d[23]), "+f"(d[24]), "+f"(d[25]), "+f"(d[26]), "+f"(d[27]), "+f"(d[28]), "+f"(d[29]), "+f"(d[30]), "+f"(d[31]), "+f"(d[32]), "+f"(d[33]), "+f"(d[34]), "+f"(d[35]), "+f"(d[36]), "+f"(d[37]), "+f"(d[38]), "+f"(d[39]), "+f"(d[40]), "+f"(d[41]), "+f"(d[42]), "+f"(d[43]), "+f"(d[44]), "+f"(d[45]), "+f"(d[46]), "+f"(d[47])
    : "l"(descA), "l"(descB));
}
__device__ __forceinline__ void mma_q(float (&d)[48], uint64_t descA, uint64_t descB) {
  asm volatile("wgmma.mma_async.sync.aligned.m64n96k16.f32.bf16.bf16 {%0, %1, %2, %3, %4, %5, %6, %7, %8, %9, %10, %11, %12, %13, %14, %15, %16, %17, %18, %19, %20, %21, %22, %23, %24, %25, %26, %27, %28, %29, %30, %31, %32, %33, %34, %35, %36, %37, %38, %39, %40, %41, %42, %43, %44, %45, %46, %47}, "
    "%48, %49, 1, 1, 1, 0, 1;"
    : "+f"(d[0]), "+f"(d[1]), "+f"(d[2]), "+f"(d[3]), "+f"(d[4]), "+f"(d[5]), "+f"(d[6]), "+f"(d[7]), "+f"(d[8]), "+f"(d[9]), "+f"(d[10]), "+f"(d[11]), "+f"(d[12]), "+f"(d[13]), "+f"(d[14]), "+f"(d[15]), "+f"(d[16]), "+f"(d[17]), "+f"(d[18]), "+f"(d[19]), "+f"(d[20]), "+f"(d[21]), "+f"(d[22]), "+f"(d[23]), "+f"(d[24]), "+f"(d[25]), "+f"(d[26]), "+f"(d[27]), "+f"(d[28]), "+f"(d[29]), "+f"(d[30]), "+f"(d[31]), "+f"(d[32]), "+f"(d[33]), "+f"(d[34]), "+f"(d[35]), "+f"(d[36]), "+f"(d[37]), "+f"(d[38]), "+f"(d[39]), "+f"(d[40]), "+f"(d[41]), "+f"(d[42]), "+f"(d[43]), "+f"(d[44]), "+f"(d[45]), "+f"(d[46]), "+f"(d[47])
    : "l"(descA), "l"(descB));
}
__device__ __forceinline__ void mma_kv_init(float (&d)[32], uint32_t a0, uint32_t a1, uint32_t a2, uint32_t a3, uint64_t descB) {
  asm volatile("wgmma.mma_async.sync.aligned.m64n64k16.f32.bf16.bf16 {%0, %1, %2, %3, %4, %5, %6, %7, %8, %9, %10, %11, %12, %13, %14, %15, %16, %17, %18, %19, %20, %21, %22, %23, %24, %25, %26, %27, %28, %29, %30, %31}, "
    "{%32, %33, %34, %35}, %36, 0, 1, 1, 0;"
    : "+f"(d[0]), "+f"(d[1]), "+f"(d[2]), "+f"(d[3]), "+f"(d[4]), "+f"(d[5]), "+f"(d[6]), "+f"(d[7]), "+f"(d[8]), "+f"(d[9]), "+f"(d[10]), "+f"(d[11]), "+f"(d[12]), "+f"(d[13]), "+f"(d[14]), "+f"(d[15]), "+f"(d[16]), "+f"(d[17]), "+f"(d[18]), "+f"(d[19]), "+f"(d[20]), "+f"(d[21]), "+f"(d[22]), "+f"(d[23]), "+f"(d[24]), "+f"(d[25]), "+f"(d[26]), "+f"(d[27]), "+f"(d[28]), "+f"(d[29]), "+f"(d[30]), "+f"(d[31])
    : "r"(a0), "r"(a1), "r"(a2), "r"(a3), "l"(descB));
}
__device__ __forceinline__ void mma_kv(float (&d)[32], uint32_t a0, uint32_t a1, uint32_t a2, uint32_t a3, uint64_t descB) {
  asm volatile("wgmma.mma_async.sync.aligned.m64n64k16.f32.bf16.bf16 {%0, %1, %2, %3, %4, %5, %6, %7, %8, %9, %10, %11, %12, %13, %14, %15, %16, %17, %18, %19, %20, %21, %22, %23, %24, %25, %26, %27, %28, %29, %30, %31}, "
    "{%32, %33, %34, %35}, %36, 1, 1, 1, 0;"
    : "+f"(d[0]), "+f"(d[1]), "+f"(d[2]), "+f"(d[3]), "+f"(d[4]), "+f"(d[5]), "+f"(d[6]), "+f"(d[7]), "+f"(d[8]), "+f"(d[9]), "+f"(d[10]), "+f"(d[11]), "+f"(d[12]), "+f"(d[13]), "+f"(d[14]), "+f"(d[15]), "+f"(d[16]), "+f"(d[17]), "+f"(d[18]), "+f"(d[19]), "+f"(d[20]), "+f"(d[21]), "+f"(d[22]), "+f"(d[23]), "+f"(d[24]), "+f"(d[25]), "+f"(d[26]), "+f"(d[27]), "+f"(d[28]), "+f"(d[29]), "+f"(d[30]), "+f"(d[31])
    : "r"(a0), "r"(a1), "r"(a2), "r"(a3), "l"(descB));
}
__device__ __forceinline__ void mma_s(float (&d)[32], uint32_t a0, uint32_t a1, uint32_t a2, uint32_t a3, uint64_t descB) {
  asm volatile("wgmma.mma_async.sync.aligned.m64n64k16.f32.bf16.bf16 {%0, %1, %2, %3, %4, %5, %6, %7, %8, %9, %10, %11, %12, %13, %14, %15, %16, %17, %18, %19, %20, %21, %22, %23, %24, %25, %26, %27, %28, %29, %30, %31}, "
    "{%32, %33, %34, %35}, %36, 1, 1, 1, 1;"
    : "+f"(d[0]), "+f"(d[1]), "+f"(d[2]), "+f"(d[3]), "+f"(d[4]), "+f"(d[5]), "+f"(d[6]), "+f"(d[7]), "+f"(d[8]), "+f"(d[9]), "+f"(d[10]), "+f"(d[11]), "+f"(d[12]), "+f"(d[13]), "+f"(d[14]), "+f"(d[15]), "+f"(d[16]), "+f"(d[17]), "+f"(d[18]), "+f"(d[19]), "+f"(d[20]), "+f"(d[21]), "+f"(d[22]), "+f"(d[23]), "+f"(d[24]), "+f"(d[25]), "+f"(d[26]), "+f"(d[27]), "+f"(d[28]), "+f"(d[29]), "+f"(d[30]), "+f"(d[31])
    : "r"(a0), "r"(a1), "r"(a2), "r"(a3), "l"(descB));
}
__device__ __forceinline__ void mma_p_init(float (&d)[28], uint32_t a0, uint32_t a1, uint32_t a2, uint32_t a3, uint64_t descB) {
  asm volatile("wgmma.mma_async.sync.aligned.m64n56k16.f32.bf16.bf16 {%0, %1, %2, %3, %4, %5, %6, %7, %8, %9, %10, %11, %12, %13, %14, %15, %16, %17, %18, %19, %20, %21, %22, %23, %24, %25, %26, %27}, "
    "{%28, %29, %30, %31}, %32, 0, 1, 1, 0;"
    : "=f"(d[0]), "=f"(d[1]), "=f"(d[2]), "=f"(d[3]), "=f"(d[4]), "=f"(d[5]), "=f"(d[6]), "=f"(d[7]), "=f"(d[8]), "=f"(d[9]), "=f"(d[10]), "=f"(d[11]), "=f"(d[12]), "=f"(d[13]), "=f"(d[14]), "=f"(d[15]), "=f"(d[16]), "=f"(d[17]), "=f"(d[18]), "=f"(d[19]), "=f"(d[20]), "=f"(d[21]), "=f"(d[22]), "=f"(d[23]), "=f"(d[24]), "=f"(d[25]), "=f"(d[26]), "=f"(d[27])
    : "r"(a0), "r"(a1), "r"(a2), "r"(a3), "l"(descB));
}
__device__ __forceinline__ void mma_p(float (&d)[28], uint32_t a0, uint32_t a1, uint32_t a2, uint32_t a3, uint64_t descB) {
  asm volatile("wgmma.mma_async.sync.aligned.m64n56k16.f32.bf16.bf16 {%0, %1, %2, %3, %4, %5, %6, %7, %8, %9, %10, %11, %12, %13, %14, %15, %16, %17, %18, %19, %20, %21, %22, %23, %24, %25, %26, %27}, "
    "{%28, %29, %30, %31}, %32, 1, 1, 1, 0;"
    : "+f"(d[0]), "+f"(d[1]), "+f"(d[2]), "+f"(d[3]), "+f"(d[4]), "+f"(d[5]), "+f"(d[6]), "+f"(d[7]), "+f"(d[8]), "+f"(d[9]), "+f"(d[10]), "+f"(d[11]), "+f"(d[12]), "+f"(d[13]), "+f"(d[14]), "+f"(d[15]), "+f"(d[16]), "+f"(d[17]), "+f"(d[18]), "+f"(d[19]), "+f"(d[20]), "+f"(d[21]), "+f"(d[22]), "+f"(d[23]), "+f"(d[24]), "+f"(d[25]), "+f"(d[26]), "+f"(d[27])
    : "r"(a0), "r"(a1), "r"(a2), "r"(a3), "l"(descB));
}
__device__ __forceinline__ void mma_o_init(float (&d)[48], uint32_t a0, uint32_t a1, uint32_t a2, uint32_t a3, uint64_t descB) {
  asm volatile("wgmma.mma_async.sync.aligned.m64n96k16.f32.bf16.bf16 {%0, %1, %2, %3, %4, %5, %6, %7, %8, %9, %10, %11, %12, %13, %14, %15, %16, %17, %18, %19, %20, %21, %22, %23, %24, %25, %26, %27, %28, %29, %30, %31, %32, %33, %34, %35, %36, %37, %38, %39, %40, %41, %42, %43, %44, %45, %46, %47}, "
    "{%48, %49, %50, %51}, %52, 0, 1, 1, 1;"
    : "=f"(d[0]), "=f"(d[1]), "=f"(d[2]), "=f"(d[3]), "=f"(d[4]), "=f"(d[5]), "=f"(d[6]), "=f"(d[7]), "=f"(d[8]), "=f"(d[9]), "=f"(d[10]), "=f"(d[11]), "=f"(d[12]), "=f"(d[13]), "=f"(d[14]), "=f"(d[15]), "=f"(d[16]), "=f"(d[17]), "=f"(d[18]), "=f"(d[19]), "=f"(d[20]), "=f"(d[21]), "=f"(d[22]), "=f"(d[23]), "=f"(d[24]), "=f"(d[25]), "=f"(d[26]), "=f"(d[27]), "=f"(d[28]), "=f"(d[29]), "=f"(d[30]), "=f"(d[31]), "=f"(d[32]), "=f"(d[33]), "=f"(d[34]), "=f"(d[35]), "=f"(d[36]), "=f"(d[37]), "=f"(d[38]), "=f"(d[39]), "=f"(d[40]), "=f"(d[41]), "=f"(d[42]), "=f"(d[43]), "=f"(d[44]), "=f"(d[45]), "=f"(d[46]), "=f"(d[47])
    : "r"(a0), "r"(a1), "r"(a2), "r"(a3), "l"(descB));
}
__device__ __forceinline__ void mma_o(float (&d)[48], uint32_t a0, uint32_t a1, uint32_t a2, uint32_t a3, uint64_t descB) {
  asm volatile("wgmma.mma_async.sync.aligned.m64n96k16.f32.bf16.bf16 {%0, %1, %2, %3, %4, %5, %6, %7, %8, %9, %10, %11, %12, %13, %14, %15, %16, %17, %18, %19, %20, %21, %22, %23, %24, %25, %26, %27, %28, %29, %30, %31, %32, %33, %34, %35, %36, %37, %38, %39, %40, %41, %42, %43, %44, %45, %46, %47}, "
    "{%48, %49, %50, %51}, %52, 1, 1, 1, 1;"
    : "+f"(d[0]), "+f"(d[1]), "+f"(d[2]), "+f"(d[3]), "+f"(d[4]), "+f"(d[5]), "+f"(d[6]), "+f"(d[7]), "+f"(d[8]), "+f"(d[9]), "+f"(d[10]), "+f"(d[11]), "+f"(d[12]), "+f"(d[13]), "+f"(d[14]), "+f"(d[15]), "+f"(d[16]), "+f"(d[17]), "+f"(d[18]), "+f"(d[19]), "+f"(d[20]), "+f"(d[21]), "+f"(d[22]), "+f"(d[23]), "+f"(d[24]), "+f"(d[25]), "+f"(d[26]), "+f"(d[27]), "+f"(d[28]), "+f"(d[29]), "+f"(d[30]), "+f"(d[31]), "+f"(d[32]), "+f"(d[33]), "+f"(d[34]), "+f"(d[35]), "+f"(d[36]), "+f"(d[37]), "+f"(d[38]), "+f"(d[39]), "+f"(d[40]), "+f"(d[41]), "+f"(d[42]), "+f"(d[43]), "+f"(d[44]), "+f"(d[45]), "+f"(d[46]), "+f"(d[47])
    : "r"(a0), "r"(a1), "r"(a2), "r"(a3), "l"(descB));
}

__device__ __forceinline__ void wg_fence() { asm volatile("wgmma.fence.sync.aligned;" ::: "memory"); }
__device__ __forceinline__ void wg_commit() { asm volatile("wgmma.commit_group.sync.aligned;" ::: "memory"); }
template <int N> __device__ __forceinline__ void wg_wait() { asm volatile("wgmma.wait_group.sync.aligned %0;" ::"n"(N) : "memory"); }
template <int N> __device__ __forceinline__ void pin(float (&d)[N]) {
#pragma unroll
  for (int i = 0; i < N; i++) asm volatile("" : "+f"(d[i])::"memory");
}
template <int N> __device__ __forceinline__ void pin(uint32_t (&d)[N]) {
#pragma unroll
  for (int i = 0; i < N; i++) asm volatile("" : "+r"(d[i])::"memory");
}
__device__ __forceinline__ uint64_t mkdesc(uint32_t lo, uint32_t hi) { return ((uint64_t)hi << 32) | lo; }
constexpr uint32_t HI_X = (3072 >> 4) | (1u << 30);
constexpr uint32_t HI_KV = (1024 >> 4) | (1u << 30);
constexpr uint32_t HI_W = (512 >> 4) | (2u << 30);
constexpr uint32_t HI_O = (1536 >> 4) | (2u << 30);
constexpr uint32_t LO_O = (1u << 16) + ((SM_BASE + OFF_OIN) >> 4);
constexpr uint32_t LO_WQ = ((12288 >> 4) << 16) + ((SM_BASE + OFF_WQ) >> 4);
constexpr uint32_t LO_WO = ((6144 >> 4) << 16) + ((SM_BASE + OFF_WO) >> 4);
constexpr uint32_t LO_X = (1u << 16) + ((SM_BASE + OFF_X) >> 4);
constexpr uint32_t LO_KV = (1u << 16) + ((SM_BASE + OFF_KV) >> 4);

__device__ __forceinline__ uint32_t pack_bf16(float lo, float hi) {
  uint32_t r;
  asm("cvt.rn.bf16x2.f32 %0, %1, %2;" : "=r"(r) : "f"(hi), "f"(lo));
  return r;
}
__device__ __forceinline__ float ex2(float x) {
  float r;
  asm("ex2.approx.ftz.f32 %0, %1;" : "=f"(r) : "f"(x));
  return r;
}
__device__ __forceinline__ float rcp(float x) {
  float r;
  asm("rcp.approx.ftz.f32 %0, %1;" : "=f"(r) : "f"(x));
  return r;
}
__device__ __forceinline__ bool elect() {
  uint32_t p;
  asm volatile("{\n.reg .pred P;\nelect.sync _|P, 0xffffffff;\nselp.u32 %0, 1, 0, P;\n}" : "=r"(p));
  return p;
}
__device__ __forceinline__ void mbar_init(uint32_t bar, uint32_t cnt) {
  asm volatile("mbarrier.init.shared::cta.b64 [%0], %1;" ::"r"(bar), "r"(cnt) : "memory");
}
__device__ __forceinline__ void mbar_wait(uint32_t bar, uint32_t parity) {
  asm volatile(
      "{\n.reg .pred p;\n.reg .u32 n;\n"
      "mbarrier.try_wait.parity.shared::cta.b64 p, [%0], %1;\n"
      "@p bra DONE;\n"
      "mov.u32 n, 0;\n"
      "LOOP:\n"
      "mbarrier.try_wait.parity.shared::cta.b64 p, [%0], %1;\n"
      "@p bra DONE;\n"
      "add.u32 n, n, 1;\n"
      "setp.lt.u32 p, n, 0x400000;\n"
      "@p bra LOOP;\n"
      "trap;\n"
      "DONE:\n}\n" ::"r"(bar), "r"(parity)
      : "memory");
}
__device__ __forceinline__ void mbar_arrive_cluster(uint32_t bar) {
  asm volatile("mbarrier.arrive.shared::cluster.b64 _, [%0];" ::"r"(bar) : "memory");
}
__device__ __forceinline__ void mbar_expect_tx(uint32_t bar, uint32_t bytes) {
  asm volatile("mbarrier.arrive.expect_tx.shared::cta.b64 _, [%0], %1;" ::"r"(bar), "r"(bytes) : "memory");
}
__device__ __forceinline__ uint32_t mapa(uint32_t addr, uint32_t rank) {
  uint32_t r;
  asm("mapa.shared::cluster.u32 %0, %1, %2;" : "=r"(r) : "r"(addr), "r"(rank));
  return r;
}
__device__ __forceinline__ void sched_fence(uint32_t& keep, int never) {
  asm volatile("{\n.reg .pred p;\nsetp.ne.s32 p, %1, 0;\n@p mov.u32 %0, %clock;\n}" : "+r"(keep) : "r"(never) : "memory");
}
template <int ID> __device__ __forceinline__ void tok_wait() { asm volatile("bar.sync %0, 256;" ::"n"(ID) : "memory"); }
template <int ID> __device__ __forceinline__ void tok_pass() { asm volatile("bar.arrive %0, 256;" ::"n"(ID) : "memory"); }
__device__ __forceinline__ void fence_async() { asm volatile("fence.proxy.async.shared::cta;" ::: "memory"); }
__device__ __forceinline__ void stsm4(uint32_t addr, uint32_t r0, uint32_t r1, uint32_t r2, uint32_t r3) {
  asm volatile("stmatrix.sync.aligned.m8n8.x4.shared.b16 [%0], {%1,%2,%3,%4};" ::"r"(addr), "r"(r0), "r"(r1), "r"(r2), "r"(r3) : "memory");
}
__device__ __forceinline__ void lds128(uint32_t addr, uint32_t& r0, uint32_t& r1, uint32_t& r2, uint32_t& r3) {
  asm volatile("ld.shared.v4.b32 {%0,%1,%2,%3}, [%4];" : "=r"(r0), "=r"(r1), "=r"(r2), "=r"(r3) : "r"(addr) : "memory");
}
template <int OFF>
__device__ __forceinline__ void st_async(uint32_t addr, uint32_t bar, uint32_t r0, uint32_t r1, uint32_t r2, uint32_t r3) {
  asm volatile("st.async.shared::cluster.mbarrier::complete_tx::bytes.v4.b32 [%0+%6], {%1,%2,%3,%4}, [%5];" ::"r"(addr), "r"(r0),
               "r"(r1), "r"(r2), "r"(r3), "r"(bar), "n"(OFF)
               : "memory");
}
__device__ __forceinline__ void tma5_mc(uint32_t dst, const CUtensorMap* tm, uint32_t bar, int c2, int c4) {
  asm volatile(
      "cp.async.bulk.tensor.5d.shared::cluster.global.mbarrier::complete_tx::bytes.multicast::cluster "
      "[%0], [%1, {0, 0, %3, 0, %4}], [%2], %5;" ::"r"(dst), "l"(tm), "r"(bar), "r"(c2), "r"(c4), "h"((uint16_t)3)
      : "memory");
}
__device__ __forceinline__ void tma5_pf(const CUtensorMap* tm, int c2, int c4) {
  asm volatile("cp.async.bulk.prefetch.tensor.5d.L2.global [%0, {0, 0, %1, 0, %2}];" ::"l"(tm), "r"(c2), "r"(c4) : "memory");
}
__device__ __forceinline__ void tma3(uint32_t dst, const CUtensorMap* tm, uint32_t bar, int c1, int c2) {
  asm volatile("cp.async.bulk.tensor.3d.shared::cluster.global.mbarrier::complete_tx::bytes [%0], [%1, {0, %3, %4}], [%2];" ::"r"(dst),
               "l"(tm), "r"(bar), "r"(c1), "r"(c2)
               : "memory");
}
#define TR_SETUP(kv)
#define TR(k)
#define TRP(k)

#define WS_BEGIN
#define WS_END(k)
#define CLKP(k)

constexpr float SQRT_HD = 6.92820323027551f;
constexpr float SM_C = 1.4426950408889634f / SQRT_HD;

template <int LO, int HI>
__device__ __forceinline__ void s_init(float (&s)[32], const uint32_t (&mk)[16], const uint32_t (&b)[16]) {
#pragma unroll
  for (int i = 0; i < 16; i++) {
    if ((i & 7) < LO || (i & 7) >= HI) continue;
    uint32_t t;
    asm("fma.rn.bf16x2 %0, %1, %2, %3;" : "=r"(t) : "r"(mk[i]), "r"(0x40DE40DEu), "r"(b[i]));
    const int o = 4 * (i & 7) + 2 * (i >> 3);
    s[o] = __uint_as_float(t << 16);
    s[o + 1] = __uint_as_float(t);
    asm volatile("" : "+f"(s[o]), "+f"(s[o + 1])::"memory");
  }
}
__device__ __forceinline__ uint32_t pack_bias(float lo, float hi) {
  uint32_t l = pack_bf16(lo, 0.f), h = __float_as_uint(hi);
  int mag = max((int)(h & 0x7fffffffu) - (int)l + 0x8000, 0);
  return (h & 0x80000000u) | (mag & 0x7fff0000u) | l;
}
__device__ __forceinline__ void rowmax_i(const float (&s)[32], int& i0, int& i1) {
#define FI(x) __float_as_int(x)
  i0 = max(FI(s[0]), FI(s[1])), i1 = max(FI(s[2]), FI(s[3]));
  int k0 = __vimax3_s32(FI(s[4]), FI(s[5]), FI(s[8])), k1 = __vimax3_s32(FI(s[6]), FI(s[7]), FI(s[10]));
  i0 = __vimax3_s32(i0, FI(s[9]), FI(s[12]));   i1 = __vimax3_s32(i1, FI(s[11]), FI(s[14]));
  k0 = __vimax3_s32(k0, FI(s[13]), FI(s[16]));  k1 = __vimax3_s32(k1, FI(s[15]), FI(s[18]));
  i0 = __vimax3_s32(i0, FI(s[17]), FI(s[20]));  i1 = __vimax3_s32(i1, FI(s[19]), FI(s[22]));
  k0 = __vimax3_s32(k0, FI(s[21]), FI(s[24]));  k1 = __vimax3_s32(k1, FI(s[23]), FI(s[26]));
  i0 = __vimax3_s32(i0, FI(s[25]), FI(s[28]));  i1 = __vimax3_s32(i1, FI(s[27]), FI(s[30]));
  i0 = __vimax3_s32(i0, k0, FI(s[29]));         i1 = __vimax3_s32(i1, k1, FI(s[31]));
#undef FI
}
__device__ __forceinline__ void quadmax_i(int& i0, int& i1, int x) {
  i0 = max(i0, __shfl_xor_sync(0xffffffffu, i0, x));
  i1 = max(i1, __shfl_xor_sync(0xffffffffu, i1, x));
}
__device__ __forceinline__ void rowmax_f(const float (&s)[32], int& i0, int& i1) {
  float m0 = fmaxf(s[0], s[1]), m1 = fmaxf(s[2], s[3]);
#pragma unroll
  for (int j = 1; j < 8; j++) {
    m0 = fmaxf(m0, fmaxf(s[4 * j], s[4 * j + 1]));
    m1 = fmaxf(m1, fmaxf(s[4 * j + 2], s[4 * j + 3]));
  }
  m0 = fmaxf(m0, __shfl_xor_sync(0xffffffffu, m0, 1));
  m1 = fmaxf(m1, __shfl_xor_sync(0xffffffffu, m1, 1));
  m0 = fmaxf(m0, __shfl_xor_sync(0xffffffffu, m0, 2));
  m1 = fmaxf(m1, __shfl_xor_sync(0xffffffffu, m1, 2));
  i0 = __float_as_int(m0), i1 = __float_as_int(m1);
}
template <int LO, int HI>
__device__ __forceinline__ void exp_part(const float (&s)[32], uint32_t (&p)[16], float m0, float m1) {
#pragma unroll
  for (int i = LO; i < HI; i++) {
    float m = (i & 1) ? m1 : m0;
    p[i] = pack_bf16(ex2(fmaf(s[2 * i], SM_C, m)), ex2(fmaf(s[2 * i + 1], SM_C, m)));
    asm volatile("" : "+r"(p[i])::"memory");
  }
}
template <int SUM, int OFF>
__device__ __forceinline__ void normalize(const float (&o)[28], uint32_t (&f)[12]) {
  float r0 = rcp(o[SUM]), r1 = rcp(o[SUM + 2]);
#pragma unroll
  for (int j = 0; j < 12; j++) {
    float r = (j & 1) ? r1 : r0;
    f[j] = pack_bf16(o[OFF + 2 * j] * r, o[OFF + 2 * j + 1] * r);
  }
}

__global__ void __cluster_dims__(2, 1, 1) __launch_bounds__(384, 1)
swin_attn_kernel(const __grid_constant__ Maps maps, const __nv_bfloat16* __restrict__ rpb, const int* __restrict__ rp_idx, int never) {
  extern __shared__ __align__(1024) uint8_t smem_raw[];
  const uint32_t sb = (uint32_t)__cvta_generic_to_shared(smem_raw);
  const int tid = threadIdx.x;
  const int wg = __shfl_sync(0xffffffffu, tid >> 7, 0);
  const int warp = __shfl_sync(0xffffffffu, (tid >> 5) & 3, 0);
  const int lane = tid & 31;
  const int rank = blockIdx.x & 1;
  const int cl = blockIdx.x >> 1;
  const int ncl = gridDim.x >> 1;
  const uint32_t bars = sb + OFF_BAR;
  TRP(0);
  CLKP(0);

  if (wg == KV_WG) {
    if (warp == 3) {
      if (elect()) {
        if ((sb & 0x3FFFF) != SM_BASE) __trap();
#pragma unroll
        for (int a = 0; a < 2; a++) {
          mbar_init(bars + B_XFULL + 8 * a, 1);
          mbar_init(bars + B_XEMPTY + 8 * a, 1);
          mbar_init(bars + B_OFULL + 8 * a, 1);
          mbar_init(bars + B_OEMPTY + 8 * a, 4);
        }
        mbar_init(bars + B_WKV, 1);
        mbar_init(bars + B_WQ, 1);
        mbar_init(bars + B_WO, 1);
        asm volatile("fence.mbarrier_init.release.cluster;" ::: "memory");
        fence_async();
        mbar_expect_tx(bars + B_WKV, 73728);
        mbar_expect_tx(bars + B_WQ, 36864);
        mbar_expect_tx(bars + B_WO, 36864);
        mbar_expect_tx(bars + B_XFULL, X_BYTES + M_BYTES);
        mbar_expect_tx(bars + B_XFULL + 8, X_BYTES + M_BYTES);
        tma3(sb + OFF_KV, &maps.wqkv, bars + B_WKV, 0, 6 + 3 * rank);
        tma3(sb + OFF_KV + STAGE, &maps.wqkv, bars + B_WKV, 0, 12 + 3 * rank);
        tma3(sb + OFF_WQ, &maps.wqkv, bars + B_WQ, 0, 3 * rank);
      }
      __syncwarp();
    }
    auto prefetch = [&](int win) {
      if (warp < 2) tma5_pf(&maps.x, (((win >> 3) & ~7) + 4 + 4 * rank) & 511, (win * 4 + 2 + 2 * warp) & 255);
      else tma5_pf(&maps.mask, 0, 2 * win + rank);
    };
    auto load = [&](int win, int a) {
      if (warp < 2)
        tma5_mc(sb + OFF_X + a * STAGE + rank * 12288 + warp * 6144, &maps.x, bars + B_XFULL + 8 * a,
                (((win >> 3) & ~7) + 4 + 4 * rank) & 511, (win * 4 + 2 + 2 * warp) & 255);
      else tma5_mc(sb + OFF_MASK + a * STAGE + rank * 4096, &maps.mask, bars + B_XFULL + 8 * a, 0, 2 * win + rank);
    };
    if (warp < 3 && elect()) {
      for (int j = 0; j <= 1 + PF_DIST; j++) prefetch(cl + j * ncl);
    }
    __syncwarp();
    asm volatile("barrier.cluster.arrive.relaxed.aligned;" ::: "memory");
    asm volatile("setmaxnreg.inc.sync.aligned.u32 216;");
    asm volatile("barrier.cluster.wait.aligned;" ::: "memory");
    TRP(1);
    if (elect()) {
      if (warp < 3) {
        load(cl, 0);
        load(cl + ncl, 1);
      } else {
        tma3(sb + OFF_WO, &maps.wo, bars + B_WO, 96 * rank, 3 * rank);
        for (int nb = 0; nb < 3; nb++)
          asm volatile("cp.async.bulk.tensor.5d.shared::cluster.global.mbarrier::complete_tx::bytes [%0], [%1, {%3, 0, 0, 0, %4}], [%2];" ::"r"(
                           sb + OFF_WO + 18432 + nb * 6144), "l"(&maps.wop), "r"(bars + B_WO), "r"(96 * rank + 32 * nb), "r"(3 * (rank ^ 1))
                       : "memory");
      }
    }
    __syncwarp();
    uint32_t w[3][48];
    {
      const uint32_t la = sb + OFF_KV + (warp >> 1) * 12288 + (8 * (lane >> 4) + (lane & 7)) * 64 +
                          (((2 * (warp & 1) + ((lane >> 3) & 1)) ^ ((lane & 7) >> 1)) << 4);
      mbar_wait(bars + B_WKV, 0);
      TRP(2);
#pragma unroll
      for (int s = 0; s < 3; s++)
#pragma unroll
        for (int ks = 0; ks < 12; ks++)
          asm volatile("ldmatrix.sync.aligned.m8n8.x4.trans.shared.b16 {%0,%1,%2,%3}, [%4];"
                       : "=r"(w[s][4 * ks]), "=r"(w[s][4 * ks + 1]), "=r"(w[s][4 * ks + 2]), "=r"(w[s][4 * ks + 3])
                       : "r"(la + s * 24576 + (s == 2 || (s == 1 && warp >= 2) ? STAGE - 36864 : 0) + ks * 1024)
                       : "memory");
      asm volatile("bar.sync %0, 128;" ::"n"((int)BAR_STAGE) : "memory");
      asm volatile("st.shared.v4.b32 [%0], {%1,%1,%1,%1};" ::"r"(sb + OFF_KV + (warp >> 1) * STAGE + 144 * 128 + (tid & 63) * 16), "r"(0x3F803F80u) : "memory");
    }
    TRP(3);
    uint32_t sta[4];
#pragma unroll
    for (int jj = 0; jj < 4; jj++) {
      sta[jj] = sb + OFF_KV + (16 * warp + (lane & 15)) * 128 + (((2 * jj + (lane >> 4)) ^ (lane & 7)) << 4);
      asm volatile("" : "+r"(sta[jj]));
    }
    const uint32_t xe_rem = mapa(bars + B_XEMPTY, rank ^ 1);
    const uint32_t v1off = warp > 0 ? 1024 : 0;

#define SF sched_fence(sta[0], never)
    float acc[32];
    uint32_t pk[16];
    auto store = [&](uint32_t off) {
#pragma unroll
      for (int jj = 0; jj < 4; jj++) stsm4(sta[jj] + off, pk[4 * jj], pk[4 * jj + 1], pk[4 * jj + 2], pk[4 * jj + 3]);
    };
    auto issue = [&](int s, uint32_t xd, bool st, uint32_t off) {
#pragma unroll
      for (int ks = 0; ks < 12; ks++) {
        uint64_t db = mkdesc(xd + (((ks >> 2) * 1024 + (ks & 3) * 32) >> 4), HI_X);
        if (ks == 0) mma_kv_init(acc, w[s][0], w[s][1], w[s][2], w[s][3], db);
        else mma_kv(acc, w[s][4 * ks], w[s][4 * ks + 1], w[s][4 * ks + 2], w[s][4 * ks + 3], db);
        if (ks == ST_AT && st) {
          __syncwarp();
          store(off);
          __syncwarp();
        }
      }
      wg_commit();
    };
    auto convert = [&]() {
      wg_wait<0>();
      pin(acc);
#pragma unroll
      for (int j = 0; j < 16; j++) pk[j] = pack_bf16(acc[2 * j], acc[2 * j + 1]);
      pin(pk);
    };

    mbar_wait(bars + B_XFULL, 0);
    TRP(4);
    wg_fence();
    tok_wait<T0>();
    issue(0, LO_X, false, 0);
    tok_pass<T1>();
    [[maybe_unused]] int i = 0;
    int nxt = cl + ncl;
    uint32_t ph = 0;
    auto step = [&](auto A) -> bool {
      constexpr int a = decltype(A)::value;
      constexpr uint32_t xd = LO_X + a * (STAGE >> 4);
      const bool more = nxt < NWIN;
      TR_SETUP(1);
      TR(0);
      convert();
      TR(1);
      wg_fence();
      SF;
      tok_wait<T2>();
      TR(2);
      issue(1, xd, true, a * STAGE);
      tok_pass<T3>();
      TR(3);
      if (warp < 3 && nxt + (1 + PF_DIST) * ncl < NWIN && elect()) prefetch(nxt + (1 + PF_DIST) * ncl);
      __syncwarp();
      TR(4);
      convert();
      store(a * STAGE + 8192);
      fence_async();
      TR(5);
      wg_fence();
      tok_wait<T5>();
      TR(6);
      issue(2, xd, false, 0);
      tok_pass<T6>();
      if (!more) {
        convert();
        store(a * STAGE + 16384 + v1off);
        fence_async();
        return false;
      }
      { WS_BEGIN; mbar_wait(bars + B_XFULL + 8 * (a ^ 1), a ? ph ^ 1 : ph); WS_END(0); WS_END(8 + i); }
      TR(7);
      convert();
      TR(8);
      wg_fence();
      SF;
      tok_wait<T0>();
      TR(9);
      if (tid == KV_WG * 128) mbar_arrive_cluster(xe_rem + 8 * a);
      issue(0, LO_X + (a ^ 1) * (STAGE >> 4), true, a * STAGE + 16384 + v1off);
      tok_pass<T1>();
      TR(10);
      fence_async();
      tok_pass<T7>();
      nxt += ncl;
      if (nxt < NWIN) {
        { WS_BEGIN; mbar_wait(bars + B_XEMPTY + 8 * a, ph); WS_END(1); }
        if (elect()) {
          if (warp < 3) load(nxt, a);
          else mbar_expect_tx(bars + B_XFULL + 8 * a, X_BYTES + M_BYTES);
        }
        __syncwarp();
      }
      i++;
      return true;
    };
    while (step(IC<0>{}) && step(IC<1>{})) ph ^= 1;
    tok_wait<T0>();
    tok_pass<T1>();
    tok_pass<T7>();
    tok_wait<T2>();
    tok_pass<T3>();
    tok_wait<T5>();
  } else {
    const int a = wg - (KV_WG == 0 ? 1 : 0);
    const int g = lane >> 2, q = lane & 3;
    const uint32_t bar = bars + 8 * a;
    asm volatile("barrier.cluster.arrive.relaxed.aligned;" ::: "memory");
    asm volatile("setmaxnreg.dec.sync.aligned.u32 144;");
    uint32_t bias0[16], bias1[16];
    {
      const int ty = 4 * (warp >> 1) + (g >> 1), tx = 4 * (warp & 1) + (g & 1);
#pragma unroll
      for (int c = 0; c < 4; c++) {
        const int4* ip = reinterpret_cast<const int4*>(rp_idx + (ty * 8 + tx + 2 * (c >> 1)) * 64 + 8 * (q + 4 * (c & 1)));
        int4 i0 = __ldg(ip), i1 = __ldg(ip + 1);
        int id[8] = {i0.x, i0.y, i0.z, i0.w, i1.x, i1.y, i1.z, i1.w};
#pragma unroll
        for (int jj = 0; jj < 4; jj++) {
          uint32_t b0 = __ldg(reinterpret_cast<const uint32_t*>(rpb) + id[2 * jj] * 2 + rank);
          uint32_t b1 = __ldg(reinterpret_cast<const uint32_t*>(rpb) + id[2 * jj + 1] * 2 + rank);
          bias0[4 * c + jj] = pack_bias(__uint_as_float(b0 << 16) * SQRT_HD, __uint_as_float(b1 << 16) * SQRT_HD);
          bias1[4 * c + jj] = pack_bias(__uint_as_float(b0 & 0xffff0000u) * SQRT_HD, __uint_as_float(b1 & 0xffff0000u) * SQRT_HD);
        }
      }
      pin(bias0);
      pin(bias1);
    }
    TRP(1);
    asm volatile("barrier.cluster.wait.aligned;" ::: "memory");
    TRP(2);

    const int mrow = 16 * warp + (g >> 1) + 4 * (g & 1);
#undef SF
#define SF sched_fence(mk_addr, never)
    uint32_t mk_addr = sb + OFF_MASK + a * STAGE + mrow * 128 + ((q ^ (mrow & 7)) << 4);
    const uint32_t ostage = sb + OFF_OIN + a * STAGE + warp * 3072;
    const uint32_t ost = ostage + ((lane >> 3) & 1) * 1536 + (lane & 7) * 64 + (((lane >> 4) ^ ((lane & 7) >> 1)) << 4);
    const uint32_t oin_rem = mapa(ostage + g * 64 + ((q ^ (g >> 1)) << 4), rank ^ 1);
    const uint32_t bar_rem = mapa(bar, rank ^ 1);
    mbar_wait(bars + B_WQ, 0);
    TRP(3);

    auto store_out = [&](int win) {
      fence_async();
      __syncwarp();
      if (win >= 0 && elect()) {
        int yy = (((win >> 3) & ~7) + 4 + 4 * (warp >> 1)) & 511;
        int xh = (win * 4 + 2 + 2 * (warp & 1)) & 255;
        asm volatile("cp.async.bulk.tensor.5d.global.shared::cta.bulk_group [%0, {0, 0, %2, %3, %4}], [%1];" ::"l"(&maps.out), "r"(ostage),
                     "r"(yy), "r"(3 * rank), "r"(xh)
                     : "memory");
        asm volatile("cp.async.bulk.commit_group;" ::: "memory");
      }
      __syncwarp();
    };
    float qa[48];
    float s0[32];
    uint32_t mk[16];
    auto load_mask = [&](uint32_t z) {
#pragma unroll
      for (int c = 0; c < 4; c++)
        lds128((c & 1 ? mk_addr ^ (64 + z) : mk_addr) + (c >> 1) * 1024, mk[4 * c], mk[4 * c + 1], mk[4 * c + 2], mk[4 * c + 3]);
    };
    auto pre_init = [&]() {
      SF;
#pragma unroll
      for (int j = 0; j < 16; j++) asm("max.NaN.bf16x2 %0, %0, %1;" : "+r"(mk[j]) : "r"(0xFD80FD80u));
      pin(mk);
      s_init<PRE_T, 8>(s0, mk, bias0);
    };
    auto issue_q = [&](uint32_t ua) {
#pragma unroll
      for (int ks = 0; ks < 12; ks++) {
        uint64_t da = mkdesc(ua + LO_X + (((ks >> 2) * 1024 + (ks & 3) * 32) >> 4), HI_X);
        uint64_t db = mkdesc(LO_WQ + ks * 64, HI_W);
        if (ks == 0) mma_q_init(qa, da, db);
        else mma_q(qa, da, db);
      }
      wg_commit();
    };
    if (a == 1) {
      tok_pass<T0>();
      tok_wait<T4>();
      tok_pass<T5>();
    }
    tok_wait<T1>();
    tok_pass<T2>();
    load_mask(0);
    wg_fence();
    tok_wait<T3>();
    issue_q(a * (STAGE >> 4));
    tok_pass<T4>();
    pre_init();
    mbar_wait(bars + B_WO, 0);
    uint32_t ph = 0;
    [[maybe_unused]] int i = a;
    int win = cl + a * ncl;
    for (;; win += 2 * ncl, ph ^= 1, i += 2) {
      TR_SETUP(0);
      TR(0);
      const uint32_t ua = a * (STAGE >> 4) + (win >> 20);
      const uint32_t kd = ua + LO_KV;
      const bool last = win + ncl >= NWIN;
      float s1[32];
      TR(1);
      wg_wait<0>();
      pin(qa);
      TR(2);
      uint32_t q0[12], q1[12];
#pragma unroll
      for (int j = 0; j < 12; j++) q0[j] = pack_bf16(qa[2 * j], qa[2 * j + 1]);
#pragma unroll
      for (int j = 0; j < 12; j++) q1[j] = pack_bf16(qa[24 + 2 * j], qa[25 + 2 * j]);
      pin(q0);
      pin(q1);
      s_init<0, PRE_T>(s0, mk, bias0);
      s_init<0, 8>(s1, mk, bias1);
      pin(s0);
      pin(s1);
      TR(3);
      wg_fence();
      tok_wait<T6>();
      TR(4);
#pragma unroll
      for (int ks = 0; ks < 3; ks++)
        mma_s(s0, q0[4 * ks], q0[4 * ks + 1], q0[4 * ks + 2], q0[4 * ks + 3], mkdesc(kd + ks * 128, HI_KV));
      wg_commit();
#pragma unroll
      for (int ks = 0; ks < 3; ks++)
        mma_s(s1, q1[4 * ks], q1[4 * ks + 1], q1[4 * ks + 2], q1[4 * ks + 3], mkdesc(kd + (3 + ks) * 128, HI_KV));
      wg_commit();
      tok_pass<T0>();
      store_out(win - 2 * ncl);
      int x0, x1, y0, y1;
      wg_wait<1>();
      pin(s0);
      pin(q0);
      TR(5);
      rowmax_i(s0, x0, x1);
      quadmax_i(x0, x1, 1);
      wg_wait<0>();
      pin(s1);
      pin(q1);
      rowmax_i(s1, y0, y1);
      quadmax_i(x0, x1, 2);
      quadmax_i(y0, y1, 1);
      quadmax_i(y0, y1, 2);
      if (__builtin_expect(__any_sync(0xffffffffu, (x0 | x1 | y0 | y1) < 0), 0)) {
        rowmax_f(s0, x0, x1);
        rowmax_f(s1, y0, y1);
      }
      uint32_t p0[16], p1[16];
      exp_part<0, 16>(s0, p0, __int_as_float(x0) * -SM_C, __int_as_float(x1) * -SM_C);
      TR(6);
      float o0[28], o1[28];
      wg_fence();
      SF;
      tok_wait<T7>();
#pragma unroll
      for (int ks = 0; ks < 4; ks++) {
        uint64_t db = mkdesc(kd + ((96 * 128 + ks * 32) >> 4), HI_KV);
        if (ks == 0) mma_p_init(o0, p0[0], p0[1], p0[2], p0[3], db);
        else mma_p(o0, p0[4 * ks], p0[4 * ks + 1], p0[4 * ks + 2], p0[4 * ks + 3], db);
      }
      wg_commit();
      if (elect()) {
        { WS_BEGIN; asm volatile("cp.async.bulk.wait_group.read 0;" ::: "memory"); WS_END(4); }
        if (warp == 0) mbar_expect_tx(bar + B_OFULL, O_BYTES);
        mbar_arrive_cluster(bar_rem + B_OEMPTY);
      }
      __syncwarp();
      SF;
      const float m0 = __int_as_float(y0) * -SM_C, m1 = __int_as_float(y1) * -SM_C;
      exp_part<0, 16>(s1, p1, m0, m1);
      TR(7);
      wg_fence();
      SF;
      tok_wait<T4>();
      TR(8);
#pragma unroll
      for (int ks = 0; ks < 4; ks++) {
        uint64_t db = mkdesc(kd + ((144 * 128 + ks * 32) >> 4), HI_KV);
        if (ks == 0) mma_p_init(o1, p1[0], p1[1], p1[2], p1[3], db);
        else mma_p(o1, p1[4 * ks], p1[4 * ks + 1], p1[4 * ks + 2], p1[4 * ks + 3], db);
      }
      wg_commit();
      tok_pass<T5>();
      { WS_BEGIN; mbar_wait(bar + B_OEMPTY, ph); WS_END(2); }
      uint32_t f0[12], f1[12];
      wg_wait<1>();
      pin(o0);
      pin(p0);
      normalize<24, 0>(o0, f0);
      st_async<0>(oin_rem, bar_rem + B_OFULL, f0[0], f0[2], f0[4], f0[6]);
      st_async<1536>(oin_rem, bar_rem + B_OFULL, f0[1], f0[3], f0[5], f0[7]);
      wg_wait<0>();
      pin(o1);
      pin(p1);
      TR(9);
      normalize<0, 4>(o1, f1);
      st_async<512>(oin_rem, bar_rem + B_OFULL, f0[8], f0[10], f1[0], f1[2]);
      st_async<2048>(oin_rem, bar_rem + B_OFULL, f0[9], f0[11], f1[1], f1[3]);
      st_async<1024>(oin_rem, bar_rem + B_OFULL, f1[4], f1[6], f1[8], f1[10]);
      st_async<2560>(oin_rem, bar_rem + B_OFULL, f1[5], f1[7], f1[9], f1[11]);
      pin(f0);
      pin(f1);
      float (&oa)[48] = qa;
      TR(10);
      wg_fence();
      if (!last) tok_wait<T1>();
      TR(11);
#pragma unroll
      for (int ks = 0; ks < 3; ks++) {
        uint64_t db = mkdesc(LO_WO + ks * 64, HI_W);
        if (ks == 0) mma_o_init(oa, f0[0], f0[1], f0[2], f0[3], db);
        else mma_o(oa, f0[4 * ks], f0[4 * ks + 1], f0[4 * ks + 2], f0[4 * ks + 3], db);
      }
#pragma unroll
      for (int ks = 0; ks < 3; ks++)
        mma_o(oa, f1[4 * ks], f1[4 * ks + 1], f1[4 * ks + 2], f1[4 * ks + 3], mkdesc(LO_WO + (3 + ks) * 64, HI_W));
      { WS_BEGIN; mbar_wait(bar + B_OFULL, ph); WS_END(3); }
      asm volatile("fence.proxy.async::generic.acquire.sync_restrict::shared::cluster.cluster;" ::: "memory");
      wg_fence();
#pragma unroll
      for (int ks = 0; ks < 6; ks++)
        mma_q(oa, mkdesc(ua + LO_O + (((ks >> 1) * 512 + (ks & 1) * 32) >> 4), HI_O), mkdesc(LO_WO + (18432 >> 4) + ks * 64, HI_W));
      wg_commit();
      if (!last) tok_pass<T2>();
      load_mask(win >> 20);
      wg_wait<0>();
      pin(oa);
      pin(f0);
      pin(f1);
      TR(12);
#pragma unroll
      for (int jj = 0; jj < 6; jj++)
        stsm4((jj & 1 ? ost ^ (32 + (win >> 20)) : ost) + (jj >> 1) * 512, pack_bf16(oa[8 * jj], oa[8 * jj + 1]), pack_bf16(oa[8 * jj + 2], oa[8 * jj + 3]),
              pack_bf16(oa[8 * jj + 4], oa[8 * jj + 5]), pack_bf16(oa[8 * jj + 6], oa[8 * jj + 7]));
      if (win + 2 * ncl >= NWIN) {
        if (!last) {
          tok_wait<T3>();
          tok_pass<T4>();
        }
        break;
      }
      wg_fence();
      tok_wait<T3>();
      TR(13);
      issue_q(ua);
      tok_pass<T4>();
      TR(14);
      pre_init();
    }
    store_out(win);
    asm volatile("cp.async.bulk.wait_group 0;" ::: "memory");
    __syncwarp();
  }
  asm volatile("barrier.cluster.arrive.relaxed.aligned;" ::: "memory");
  asm volatile("barrier.cluster.wait.aligned;" ::: "memory");
  CLKP(1);
}

typedef CUresult (*EncodeFn)(CUtensorMap*, CUtensorMapDataType, cuuint32_t, void*, const cuuint64_t*, const cuuint64_t*,
                             const cuuint32_t*, const cuuint32_t*, CUtensorMapInterleave, CUtensorMapSwizzle,
                             CUtensorMapL2promotion, CUtensorMapFloatOOBfill);

void encode_map(EncodeFn encode, CUtensorMap* m, void* p, int rank, const cuuint64_t* dim, const cuuint64_t* str,
                const cuuint32_t* box, CUtensorMapSwizzle sw) {
  const cuuint32_t es[5] = {1, 1, 1, 1, 1};
  CUresult r = encode(m, CU_TENSOR_MAP_DATA_TYPE_BFLOAT16, rank, p, dim, str, box, es, CU_TENSOR_MAP_INTERLEAVE_NONE, sw,
                      CU_TENSOR_MAP_L2_PROMOTION_L2_128B, CU_TENSOR_MAP_FLOAT_OOB_FILL_NONE);
  if (r != CUDA_SUCCESS) fprintf(stderr, "tensor map encode failed: %d\n", (int)r);
}

}

extern "C" void kernel_launch(void* const* d_in, const int* in_sizes, int n_in, void* d_out, int out_size) {
  static EncodeFn encode = nullptr;
  static int grid = 0;
  if (!encode) {
    cudaDriverEntryPointQueryResult qr;
    void* fn = nullptr;
    cudaGetDriverEntryPoint("cuTensorMapEncodeTiled", &fn, cudaEnableDefault, &qr);
    encode = (EncodeFn)fn;
    cudaFuncSetAttribute(swin_attn_kernel, cudaFuncAttributeMaxDynamicSharedMemorySize, SMEM_BYTES);
    cudaLaunchConfig_t cfg = {};
    cfg.gridDim = dim3(132);
    cfg.blockDim = dim3(384);
    cfg.dynamicSmemBytes = SMEM_BYTES;
    cudaLaunchAttribute at;
    at.id = cudaLaunchAttributeClusterDimension;
    at.val.clusterDim.x = 2;
    at.val.clusterDim.y = 1;
    at.val.clusterDim.z = 1;
    cfg.attrs = &at;
    cfg.numAttrs = 1;
    int ncl = 0;
    if (cudaOccupancyMaxActiveClusters(&ncl, swin_attn_kernel, &cfg) != cudaSuccess || ncl < 1) {
      (void)cudaGetLastError();
      ncl = 66;
    }
    if (ncl > 256) ncl = 256;
    grid = 2 * ncl;
  }
  Maps maps;
  {
    const cuuint64_t dim[5] = {64, 2, 512, 3, 256}, str[4] = {384, 512 * 384, 128, 768};
    const cuuint32_t box[5] = {64, 2, 4, 3, 2};
    encode_map(encode, &maps.x, d_in[0], 5, dim, str, box, CU_TENSOR_MAP_SWIZZLE_128B);
  }
  {
    const cuuint64_t dim[5] = {64, 4, 2, 4, 8192}, str[4] = {1024, 128, 256, 4096};
    const cuuint32_t box[5] = {64, 4, 2, 4, 1};
    encode_map(encode, &maps.mask, d_in[5], 5, dim, str, box, CU_TENSOR_MAP_SWIZZLE_128B);
  }
  {
    const cuuint64_t dim[5] = {32, 2, 512, 6, 256}, str[4] = {384, 512 * 384, 64, 768};
    const cuuint32_t box[5] = {32, 2, 4, 3, 2};
    encode_map(encode, &maps.out, d_out, 5, dim, str, box, CU_TENSOR_MAP_SWIZZLE_64B);
  }
  {
    const cuuint64_t dim[3] = {32, 192, 18}, str[2] = {576 * 2, 64};
    const cuuint32_t box[3] = {32, 192, 3};
    encode_map(encode, &maps.wqkv, d_in[1], 3, dim, str, box, CU_TENSOR_MAP_SWIZZLE_64B);
    const cuuint64_t dim2[3] = {32, 192, 6}, str2[2] = {192 * 2, 64};
    const cuuint32_t box2[3] = {32, 96, 3};
    encode_map(encode, &maps.wo, d_in[2], 3, dim2, str2, box2, CU_TENSOR_MAP_SWIZZLE_64B);
    const cuuint64_t dim3_[5] = {192, 2, 4, 4, 6}, str3[4] = {384, 8 * 384, 2 * 384, 32 * 384};
    const cuuint32_t box3[5] = {32, 2, 4, 4, 3};
    encode_map(encode, &maps.wop, d_in[2], 5, dim3_, str3, box3, CU_TENSOR_MAP_SWIZZLE_64B);
  }
  swin_attn_kernel<<<grid, 384, SMEM_BYTES>>>(maps, (const __nv_bfloat16*)d_in[3], (const int*)d_in[4], 0);
}
```

```cpp
#include <cuda_runtime.h>
#include <cuda_bf16.h>
#include <cuda.h>
#include <stdint.h>
#include <stdio.h>

namespace {

constexpr int NWIN = 4096;
#define KV_WG 0
#define ST_AT 3
#define PRE_T 8

constexpr uint32_t SM_BASE  = 1024;
constexpr uint32_t OFF_WQ   = 0;
constexpr uint32_t OFF_WO   = 36864;
constexpr uint32_t STAGE    = 70656;
constexpr uint32_t OFF_X    = 73728;
constexpr uint32_t X_BYTES  = 24576;
constexpr uint32_t OFF_MASK = OFF_X + X_BYTES;
constexpr uint32_t M_BYTES  = 8192;
constexpr uint32_t OFF_KV   = OFF_MASK + M_BYTES;
constexpr uint32_t OFF_OIN  = OFF_KV + 25600;
constexpr uint32_t O_BYTES  = 12288;
constexpr uint32_t OFF_BAR  = 215040;
constexpr uint32_t OFF_RPB  = OFF_BAR + 1024;
constexpr uint32_t SMEM_BYTES = OFF_RPB + 1024;
constexpr uint32_t B_XFULL = 0, B_XEMPTY = 16, B_OFULL = 32, B_OEMPTY = 48, B_WKV = 64  , B_WQ = 88, B_WO = 96,
                   B_TICK = 104, W_TICK = 112;
enum { T0 = 1, T1, T2, T3, T4, T5, T6, T7, BAR_BIAS, BAR_STAGE };

__device__ unsigned int g_ticket;

template <int V> struct IC { static constexpr int value = V; };
struct Maps { CUtensorMap x, mask, out, wqkv, wo, wop; };

__device__ __forceinline__ void mma_q_init(float (&d)[48], uint64_t descA, uint64_t descB) {
  asm volatile("wgmma.mma_async.sync.aligned.m64n96k16.f32.bf16.bf16 {%0, %1, %2, %3, %4, %5, %6, %7, %8, %9, %10, %11, %12, %13, %14, %15, %16, %17, %18, %19, %20, %21, %22, %23, %24, %25, %26, %27, %28, %29, %30, %31, %32, %33, %34, %35, %36, %37, %38, %39, %40, %41, %42, %43, %44, %45, %46, %47}, "
    "%48, %49, 0, 1, 1, 0, 1;"
    : "+f"(d[0]), "+f"(d[1]), "+f"(d[2]), "+f"(d[3]), "+f"(d[4]), "+f"(d[5]), "+f"(d[6]), "+f"(d[7]), "+f"(d[8]), "+f"(d[9]), "+f"(d[10]), "+f"(d[11]), "+f"(d[12]), "+f"(d[13]), "+f"(d[14]), "+f"(d[15]), "+f"(d[16]), "+f"(d[17]), "+f"(d[18]), "+f"(d[19]), "+f"(d[20]), "+f"(d[21]), "+f"(d[22]), "+f"(d[23]), "+f"(d[24]), "+f"(d[25]), "+f"(d[26]), "+f"(d[27]), "+f"(d[28]), "+f"(d[29]), "+f"(d[30]), "+f"(d[31]), "+f"(d[32]), "+f"(d[33]), "+f"(d[34]), "+f"(d[35]), "+f"(d[36]), "+f"(d[37]), "+f"(d[38]), "+f"(d[39]), "+f"(d[40]), "+f"(d[41]), "+f"(d[42]), "+f"(d[43]), "+f"(d[44]), "+f"(d[45]), "+f"(d[46]), "+f"(d[47])
    : "l"(descA), "l"(descB));
}
__device__ __forceinline__ void mma_q(float (&d)[48], uint64_t descA, uint64_t descB) {
  asm volatile("wgmma.mma_async.sync.aligned.m64n96k16.f32.bf16.bf16 {%0, %1, %2, %3, %4, %5, %6, %7, %8, %9, %10, %11, %12, %13, %14, %15, %16, %17, %18, %19, %20, %21, %22, %23, %24, %25, %26, %27, %28, %29, %30, %31, %32, %33, %34, %35, %36, %37, %38, %39, %40, %41, %42, %43, %44, %45, %46, %47}, "
    "%48, %49, 1, 1, 1, 0, 1;"
    : "+f"(d[0]), "+f"(d[1]), "+f"(d[2]), "+f"(d[3]), "+f"(d[4]), "+f"(d[5]), "+f"(d[6]), "+f"(d[7]), "+f"(d[8]), "+f"(d[9]), "+f"(d[10]), "+f"(d[11]), "+f"(d[12]), "+f"(d[13]), "+f"(d[14]), "+f"(d[15]), "+f"(d[16]), "+f"(d[17]), "+f"(d[18]), "+f"(d[19]), "+f"(d[20]), "+f"(d[21]), "+f"(d[22]), "+f"(d[23]), "+f"(d[24]), "+f"(d[25]), "+f"(d[26]), "+f"(d[27]), "+f"(d[28]), "+f"(d[29]), "+f"(d[30]), "+f"(d[31]), "+f"(d[32]), "+f"(d[33]), "+f"(d[34]), "+f"(d[35]), "+f"(d[36]), "+f"(d[37]), "+f"(d[38]), "+f"(d[39]), "+f"(d[40]), "+f"(d[41]), "+f"(d[42]), "+f"(d[43]), "+f"(d[44]), "+f"(d[45]), "+f"(d[46]), "+f"(d[47])
    : "l"(descA), "l"(descB));
}
__device__ __forceinline__ void mma_kv_init(float (&d)[32], uint32_t a0, uint32_t a1, uint32_t a2, uint32_t a3, uint64_t descB) {
  asm volatile("wgmma.mma_async.sync.aligned.m64n64k16.f32.bf16.bf16 {%0, %1, %2, %3, %4, %5, %6, %7, %8, %9, %10, %11, %12, %13, %14, %15, %16, %17, %18, %19, %20, %21, %22, %23, %24, %25, %26, %27, %28, %29, %30, %31}, "
    "{%32, %33, %34, %35}, %36, 0, 1, 1, 0;"
    : "+f"(d[0]), "+f"(d[1]), "+f"(d[2]), "+f"(d[3]), "+f"(d[4]), "+f"(d[5]), "+f"(d[6]), "+f"(d[7]), "+f"(d[8]), "+f"(d[9]), "+f"(d[10]), "+f"(d[11]), "+f"(d[12]), "+f"(d[13]), "+f"(d[14]), "+f"(d[15]), "+f"(d[16]), "+f"(d[17]), "+f"(d[18]), "+f"(d[19]), "+f"(d[20]), "+f"(d[21]), "+f"(d[22]), "+f"(d[23]), "+f"(d[24]), "+f"(d[25]), "+f"(d[26]), "+f"(d[27]), "+f"(d[28]), "+f"(d[29]), "+f"(d[30]), "+f"(d[31])
    : "r"(a0), "r"(a1), "r"(a2), "r"(a3), "l"(descB));
}
__device__ __forceinline__ void mma_kv(float (&d)[32], uint32_t a0, uint32_t a1, uint32_t a2, uint32_t a3, uint64_t descB) {
  asm volatile("wgmma.mma_async.sync.aligned.m64n64k16.f32.bf16.bf16 {%0, %1, %2, %3, %4, %5, %6, %7, %8, %9, %10, %11, %12, %13, %14, %15, %16, %17, %18, %19, %20, %21, %22, %23, %24, %25, %26, %27, %28, %29, %30, %31}, "
    "{%32, %33, %34, %35}, %36, 1, 1, 1, 0;"
    : "+f"(d[0]), "+f"(d[1]), "+f"(d[2]), "+f"(d[3]), "+f"(d[4]), "+f"(d[5]), "+f"(d[6]), "+f"(d[7]), "+f"(d[8]), "+f"(d[9]), "+f"(d[10]), "+f"(d[11]), "+f"(d[12]), "+f"(d[13]), "+f"(d[14]), "+f"(d[15]), "+f"(d[16]), "+f"(d[17]), "+f"(d[18]), "+f"(d[19]), "+f"(d[20]), "+f"(d[21]), "+f"(d[22]), "+f"(d[23]), "+f"(d[24]), "+f"(d[25]), "+f"(d[26]), "+f"(d[27]), "+f"(d[28]), "+f"(d[29]), "+f"(d[30]), "+f"(d[31])
    : "r"(a0), "r"(a1), "r"(a2), "r"(a3), "l"(descB));
}
__device__ __forceinline__ void mma_s(float (&d)[32], uint32_t a0, uint32_t a1, uint32_t a2, uint32_t a3, uint64_t descB) {
  asm volatile("wgmma.mma_async.sync.aligned.m64n64k16.f32.bf16.bf16 {%0, %1, %2, %3, %4, %5, %6, %7, %8, %9, %10, %11, %12, %13, %14, %15, %16, %17, %18, %19, %20, %21, %22, %23, %24, %25, %26, %27, %28, %29, %30, %31}, "
    "{%32, %33, %34, %35}, %36, 1, 1, 1, 1;"
    : "+f"(d[0]), "+f"(d[1]), "+f"(d[2]), "+f"(d[3]), "+f"(d[4]), "+f"(d[5]), "+f"(d[6]), "+f"(d[7]), "+f"(d[8]), "+f"(d[9]), "+f"(d[10]), "+f"(d[11]), "+f"(d[12]), "+f"(d[13]), "+f"(d[14]), "+f"(d[15]), "+f"(d[16]), "+f"(d[17]), "+f"(d[18]), "+f"(d[19]), "+f"(d[20]), "+f"(d[21]), "+f"(d[22]), "+f"(d[23]), "+f"(d[24]), "+f"(d[25]), "+f"(d[26]), "+f"(d[27]), "+f"(d[28]), "+f"(d[29]), "+f"(d[30]), "+f"(d[31])
    : "r"(a0), "r"(a1), "r"(a2), "r"(a3), "l"(descB));
}
__device__ __forceinline__ void mma_p_init(float (&d)[28], uint32_t a0, uint32_t a1, uint32_t a2, uint32_t a3, uint64_t descB) {
  asm volatile("wgmma.mma_async.sync.aligned.m64n56k16.f32.bf16.bf16 {%0, %1, %2, %3, %4, %5, %6, %7, %8, %9, %10, %11, %12, %13, %14, %15, %16, %17, %18, %19, %20, %21, %22, %23, %24, %25, %26, %27}, "
    "{%28, %29, %30, %31}, %32, 0, 1, 1, 0;"
    : "=f"(d[0]), "=f"(d[1]), "=f"(d[2]), "=f"(d[3]), "=f"(d[4]), "=f"(d[5]), "=f"(d[6]), "=f"(d[7]), "=f"(d[8]), "=f"(d[9]), "=f"(d[10]), "=f"(d[11]), "=f"(d[12]), "=f"(d[13]), "=f"(d[14]), "=f"(d[15]), "=f"(d[16]), "=f"(d[17]), "=f"(d[18]), "=f"(d[19]), "=f"(d[20]), "=f"(d[21]), "=f"(d[22]), "=f"(d[23]), "=f"(d[24]), "=f"(d[25]), "=f"(d[26]), "=f"(d[27])
    : "r"(a0), "r"(a1), "r"(a2), "r"(a3), "l"(descB));
}
__device__ __forceinline__ void mma_p(float (&d)[28], uint32_t a0, uint32_t a1, uint32_t a2, uint32_t a3, uint64_t descB) {
  asm volatile("wgmma.mma_async.sync.aligned.m64n56k16.f32.bf16.bf16 {%0, %1, %2, %3, %4, %5, %6, %7, %8, %9, %10, %11, %12, %13, %14, %15, %16, %17, %18, %19, %20, %21, %22, %23, %24, %25, %26, %27}, "
    "{%28, %29, %30, %31}, %32, 1, 1, 1, 0;"
    : "+f"(d[0]), "+f"(d[1]), "+f"(d[2]), "+f"(d[3]), "+f"(d[4]), "+f"(d[5]), "+f"(d[6]), "+f"(d[7]), "+f"(d[8]), "+f"(d[9]), "+f"(d[10]), "+f"(d[11]), "+f"(d[12]), "+f"(d[13]), "+f"(d[14]), "+f"(d[15]), "+f"(d[16]), "+f"(d[17]), "+f"(d[18]), "+f"(d[19]), "+f"(d[20]), "+f"(d[21]), "+f"(d[22]), "+f"(d[23]), "+f"(d[24]), "+f"(d[25]), "+f"(d[26]), "+f"(d[27])
    : "r"(a0), "r"(a1), "r"(a2), "r"(a3), "l"(descB));
}
__device__ __forceinline__ void mma_o_init(float (&d)[48], uint32_t a0, uint32_t a1, uint32_t a2, uint32_t a3, uint64_t descB) {
  asm volatile("wgmma.mma_async.sync.aligned.m64n96k16.f32.bf16.bf16 {%0, %1, %2, %3, %4, %5, %6, %7, %8, %9, %10, %11, %12, %13, %14, %15, %16, %17, %18, %19, %20, %21, %22, %23, %24, %25, %26, %27, %28, %29, %30, %31, %32, %33, %34, %35, %36, %37, %38, %39, %40, %41, %42, %43, %44, %45, %46, %47}, "
    "{%48, %49, %50, %51}, %52, 0, 1, 1, 1;"
    : "=f"(d[0]), "=f"(d[1]), "=f"(d[2]), "=f"(d[3]), "=f"(d[4]), "=f"(d[5]), "=f"(d[6]), "=f"(d[7]), "=f"(d[8]), "=f"(d[9]), "=f"(d[10]), "=f"(d[11]), "=f"(d[12]), "=f"(d[13]), "=f"(d[14]), "=f"(d[15]), "=f"(d[16]), "=f"(d[17]), "=f"(d[18]), "=f"(d[19]), "=f"(d[20]), "=f"(d[21]), "=f"(d[22]), "=f"(d[23]), "=f"(d[24]), "=f"(d[25]), "=f"(d[26]), "=f"(d[27]), "=f"(d[28]), "=f"(d[29]), "=f"(d[30]), "=f"(d[31]), "=f"(d[32]), "=f"(d[33]), "=f"(d[34]), "=f"(d[35]), "=f"(d[36]), "=f"(d[37]), "=f"(d[38]), "=f"(d[39]), "=f"(d[40]), "=f"(d[41]), "=f"(d[42]), "=f"(d[43]), "=f"(d[44]), "=f"(d[45]), "=f"(d[46]), "=f"(d[47])
    : "r"(a0), "r"(a1), "r"(a2), "r"(a3), "l"(descB));
}
__device__ __forceinline__ void mma_o(float (&d)[48], uint32_t a0, uint32_t a1, uint32_t a2, uint32_t a3, uint64_t descB) {
  asm volatile("wgmma.mma_async.sync.aligned.m64n96k16.f32.bf16.bf16 {%0, %1, %2, %3, %4, %5, %6, %7, %8, %9, %10, %11, %12, %13, %14, %15, %16, %17, %18, %19, %20, %21, %22, %23, %24, %25, %26, %27, %28, %29, %30, %31, %32, %33, %34, %35, %36, %37, %38, %39, %40, %41, %42, %43, %44, %45, %46, %47}, "
    "{%48, %49, %50, %51}, %52, 1, 1, 1, 1;"
    : "+f"(d[0]), "+f"(d[1]), "+f"(d[2]), "+f"(d[3]), "+f"(d[4]), "+f"(d[5]), "+f"(d[6]), "+f"(d[7]), "+f"(d[8]), "+f"(d[9]), "+f"(d[10]), "+f"(d[11]), "+f"(d[12]), "+f"(d[13]), "+f"(d[14]), "+f"(d[15]), "+f"(d[16]), "+f"(d[17]), "+f"(d[18]), "+f"(d[19]), "+f"(d[20]), "+f"(d[21]), "+f"(d[22]), "+f"(d[23]), "+f"(d[24]), "+f"(d[25]), "+f"(d[26]), "+f"(d[27]), "+f"(d[28]), "+f"(d[29]), "+f"(d[30]), "+f"(d[31]), "+f"(d[32]), "+f"(d[33]), "+f"(d[34]), "+f"(d[35]), "+f"(d[36]), "+f"(d[37]), "+f"(d[38]), "+f"(d[39]), "+f"(d[40]), "+f"(d[41]), "+f"(d[42]), "+f"(d[43]), "+f"(d[44]), "+f"(d[45]), "+f"(d[46]), "+f"(d[47])
    : "r"(a0), "r"(a1), "r"(a2), "r"(a3), "l"(descB));
}

__device__ __forceinline__ void wg_fence() { asm volatile("wgmma.fence.sync.aligned;" ::: "memory"); }
__device__ __forceinline__ void wg_commit() { asm volatile("wgmma.commit_group.sync.aligned;" ::: "memory"); }
template <int N> __device__ __forceinline__ void wg_wait() { asm volatile("wgmma.wait_group.sync.aligned %0;" ::"n"(N) : "memory"); }
template <int N> __device__ __forceinline__ void pin(float (&d)[N]) {
#pragma unroll
  for (int i = 0; i < N; i++) asm volatile("" : "+f"(d[i])::"memory");
}
template <int N> __device__ __forceinline__ void pin(uint32_t (&d)[N]) {
#pragma unroll
  for (int i = 0; i < N; i++) asm volatile("" : "+r"(d[i])::"memory");
}
__device__ __forceinline__ uint64_t mkdesc(uint32_t lo, uint32_t hi) { return ((uint64_t)hi << 32) | lo; }
constexpr uint32_t HI_X = (3072 >> 4) | (1u << 30);
constexpr uint32_t HI_KV = (1024 >> 4) | (1u << 30);
constexpr uint32_t HI_W = (512 >> 4) | (2u << 30);
constexpr uint32_t HI_O = (1536 >> 4) | (2u << 30);
constexpr uint32_t LO_O = (1u << 16) + ((SM_BASE + OFF_OIN) >> 4);
constexpr uint32_t LO_WQ = ((12288 >> 4) << 16) + ((SM_BASE + OFF_WQ) >> 4);
constexpr uint32_t LO_WO = ((6144 >> 4) << 16) + ((SM_BASE + OFF_WO) >> 4);
constexpr uint32_t LO_X = (1u << 16) + ((SM_BASE + OFF_X) >> 4);
constexpr uint32_t LO_KV = (1u << 16) + ((SM_BASE + OFF_KV) >> 4);

__device__ __forceinline__ uint32_t pack_bf16(float lo, float hi) {
  uint32_t r;
  asm("cvt.rn.bf16x2.f32 %0, %1, %2;" : "=r"(r) : "f"(hi), "f"(lo));
  return r;
}
__device__ __forceinline__ float ex2(float x) {
  float r;
  asm("ex2.approx.ftz.f32 %0, %1;" : "=f"(r) : "f"(x));
  return r;
}
__device__ __forceinline__ float rcp(float x) {
  float r;
  asm("rcp.approx.ftz.f32 %0, %1;" : "=f"(r) : "f"(x));
  return r;
}
__device__ __forceinline__ bool elect() {
  uint32_t p;
  asm volatile("{\n.reg .pred P;\nelect.sync _|P, 0xffffffff;\nselp.u32 %0, 1, 0, P;\n}" : "=r"(p));
  return p;
}
__device__ __forceinline__ void mbar_init(uint32_t bar, uint32_t cnt) {
  asm volatile("mbarrier.init.shared::cta.b64 [%0], %1;" ::"r"(bar), "r"(cnt) : "memory");
}
__device__ __forceinline__ void mbar_wait(uint32_t bar, uint32_t parity) {
  asm volatile(
      "{\n.reg .pred p;\n.reg .u32 n;\n"
      "mbarrier.try_wait.parity.shared::cta.b64 p, [%0], %1;\n"
      "@p bra DONE;\n"
      "mov.u32 n, 0;\n"
      "LOOP:\n"
      "mbarrier.try_wait.parity.shared::cta.b64 p, [%0], %1;\n"
      "@p bra DONE;\n"
      "add.u32 n, n, 1;\n"
      "setp.lt.u32 p, n, 0x400000;\n"
      "@p bra LOOP;\n"
      "trap;\n"
      "DONE:\n}\n" ::"r"(bar), "r"(parity)
      : "memory");
}
__device__ __forceinline__ void mbar_arrive_cluster(uint32_t bar) {
  asm volatile("mbarrier.arrive.shared::cluster.b64 _, [%0];" ::"r"(bar) : "memory");
}
__device__ __forceinline__ void mbar_expect_tx(uint32_t bar, uint32_t bytes) {
  asm volatile("mbarrier.arrive.expect_tx.shared::cta.b64 _, [%0], %1;" ::"r"(bar), "r"(bytes) : "memory");
}
__device__ __forceinline__ uint32_t mapa(uint32_t addr, uint32_t rank) {
  uint32_t r;
  asm("mapa.shared::cluster.u32 %0, %1, %2;" : "=r"(r) : "r"(addr), "r"(rank));
  return r;
}
__device__ __forceinline__ void sched_fence(uint32_t& keep, int never) {
  asm volatile("{\n.reg .pred p;\nsetp.ne.s32 p, %1, 0;\n@p mov.u32 %0, %clock;\n}" : "+r"(keep) : "r"(never) : "memory");
}
template <int ID> __device__ __forceinline__ void tok_wait() { asm volatile("bar.sync %0, 256;" ::"n"(ID) : "memory"); }
template <int ID> __device__ __forceinline__ void tok_pass() { asm volatile("bar.arrive %0, 256;" ::"n"(ID) : "memory"); }
__device__ __forceinline__ void fence_async() { asm volatile("fence.proxy.async.shared::cta;" ::: "memory"); }
__device__ __forceinline__ void stsm4(uint32_t addr, uint32_t r0, uint32_t r1, uint32_t r2, uint32_t r3) {
  asm volatile("stmatrix.sync.aligned.m8n8.x4.shared.b16 [%0], {%1,%2,%3,%4};" ::"r"(addr), "r"(r0), "r"(r1), "r"(r2), "r"(r3) : "memory");
}
__device__ __forceinline__ void lds128(uint32_t addr, uint32_t& r0, uint32_t& r1, uint32_t& r2, uint32_t& r3) {
  asm volatile("ld.shared.v4.b32 {%0,%1,%2,%3}, [%4];" : "=r"(r0), "=r"(r1), "=r"(r2), "=r"(r3) : "r"(addr) : "memory");
}
template <int OFF>
__device__ __forceinline__ void st_async(uint32_t addr, uint32_t bar, uint32_t r0, uint32_t r1, uint32_t r2, uint32_t r3) {
  asm volatile("st.async.shared::cluster.mbarrier::complete_tx::bytes.v4.b32 [%0+%6], {%1,%2,%3,%4}, [%5];" ::"r"(addr), "r"(r0),
               "r"(r1), "r"(r2), "r"(r3), "r"(bar), "n"(OFF)
               : "memory");
}
__device__ __forceinline__ void tma5_mc(uint32_t dst, const CUtensorMap* tm, uint32_t bar, int c2, int c4) {
  asm volatile(
      "cp.async.bulk.tensor.5d.shared::cluster.global.mbarrier::complete_tx::bytes.multicast::cluster "
      "[%0], [%1, {0, 0, %3, 0, %4}], [%2], %5;" ::"r"(dst), "l"(tm), "r"(bar), "r"(c2), "r"(c4), "h"((uint16_t)3)
      : "memory");
}
__device__ __forceinline__ void tma5_pf(const CUtensorMap* tm, int c2, int c4) {
  asm volatile("cp.async.bulk.prefetch.tensor.5d.L2.global [%0, {0, 0, %1, 0, %2}];" ::"l"(tm), "r"(c2), "r"(c4) : "memory");
}
__device__ __forceinline__ void tma3(uint32_t dst, const CUtensorMap* tm, uint32_t bar, int c1, int c2) {
  asm volatile("cp.async.bulk.tensor.3d.shared::cluster.global.mbarrier::complete_tx::bytes [%0], [%1, {0, %3, %4}], [%2];" ::"r"(dst),
               "l"(tm), "r"(bar), "r"(c1), "r"(c2)
               : "memory");
}
#define TR_SETUP(kv)
#define TR(k)
#define TRP(k)

#define WS_BEGIN
#define WS_END(k)
#define CLKP(k)

constexpr float SQRT_HD = 6.92820323027551f;
constexpr float SM_C = 1.4426950408889634f / SQRT_HD;

template <int LO, int HI>
__device__ __forceinline__ void s_init(float (&s)[32], const uint32_t (&mk)[16], const uint32_t (&b)[16]) {
#pragma unroll
  for (int i = 0; i < 16; i++) {
    if ((i & 7) < LO || (i & 7) >= HI) continue;
    uint32_t t;
    asm("fma.rn.bf16x2 %0, %1, %2, %3;" : "=r"(t) : "r"(mk[i]), "r"(0x40DE40DEu), "r"(b[i]));
    const int o = 4 * (i & 7) + 2 * (i >> 3);
    s[o] = __uint_as_float(t << 16);
    s[o + 1] = __uint_as_float(t);
    asm volatile("" : "+f"(s[o]), "+f"(s[o + 1])::"memory");
  }
}
__device__ __forceinline__ uint32_t pack_bias(float lo, float hi) {
  uint32_t l = pack_bf16(lo * SQRT_HD, 0.f), h = __float_as_uint(fmaf(hi, SQRT_HD, 0x1p-100f));
  return ((h - l + 0x8000u) & 0xffff0000u) | l;
}
__device__ __forceinline__ void rowmax_i(const float (&s)[32], int& i0, int& i1) {
#define FI(x) __float_as_int(x)
  i0 = max(FI(s[0]), FI(s[1])), i1 = max(FI(s[2]), FI(s[3]));
  int k0 = __vimax3_s32(FI(s[4]), FI(s[5]), FI(s[8])), k1 = __vimax3_s32(FI(s[6]), FI(s[7]), FI(s[10]));
  i0 = __vimax3_s32(i0, FI(s[9]), FI(s[12]));   i1 = __vimax3_s32(i1, FI(s[11]), FI(s[14]));
  k0 = __vimax3_s32(k0, FI(s[13]), FI(s[16]));  k1 = __vimax3_s32(k1, FI(s[15]), FI(s[18]));
  i0 = __vimax3_s32(i0, FI(s[17]), FI(s[20]));  i1 = __vimax3_s32(i1, FI(s[19]), FI(s[22]));
  k0 = __vimax3_s32(k0, FI(s[21]), FI(s[24]));  k1 = __vimax3_s32(k1, FI(s[23]), FI(s[26]));
  i0 = __vimax3_s32(i0, FI(s[25]), FI(s[28]));  i1 = __vimax3_s32(i1, FI(s[27]), FI(s[30]));
  i0 = __vimax3_s32(i0, k0, FI(s[29]));         i1 = __vimax3_s32(i1, k1, FI(s[31]));
#undef FI
}
__device__ __forceinline__ void quadmax_i(int& i0, int& i1, int x) {
  i0 = max(i0, __shfl_xor_sync(0xffffffffu, i0, x));
  i1 = max(i1, __shfl_xor_sync(0xffffffffu, i1, x));
}
__device__ __forceinline__ void rowmax_f(const float (&s)[32], int& i0, int& i1) {
  float m0 = fmaxf(s[0], s[1]), m1 = fmaxf(s[2], s[3]);
#pragma unroll
  for (int j = 1; j < 8; j++) {
    m0 = fmaxf(m0, fmaxf(s[4 * j], s[4 * j + 1]));
    m1 = fmaxf(m1, fmaxf(s[4 * j + 2], s[4 * j + 3]));
  }
  m0 = fmaxf(m0, __shfl_xor_sync(0xffffffffu, m0, 1));
  m1 = fmaxf(m1, __shfl_xor_sync(0xffffffffu, m1, 1));
  m0 = fmaxf(m0, __shfl_xor_sync(0xffffffffu, m0, 2));
  m1 = fmaxf(m1, __shfl_xor_sync(0xffffffffu, m1, 2));
  i0 = __float_as_int(m0), i1 = __float_as_int(m1);
}
template <int LO, int HI>
__device__ __forceinline__ void exp_part(const float (&s)[32], uint32_t (&p)[16], float m0, float m1) {
#pragma unroll
  for (int i = LO; i < HI; i++) {
    float m = (i & 1) ? m1 : m0;
    p[i] = pack_bf16(ex2(fmaf(s[2 * i], SM_C, m)), ex2(fmaf(s[2 * i + 1], SM_C, m)));
    asm volatile("" : "+r"(p[i])::"memory");
  }
}
template <int SUM, int OFF>
__device__ __forceinline__ void normalize(const float (&o)[28], uint32_t (&f)[12]) {
  float r0 = rcp(o[SUM]), r1 = rcp(o[SUM + 2]);
#pragma unroll
  for (int j = 0; j < 12; j++) {
    float r = (j & 1) ? r1 : r0;
    f[j] = pack_bf16(o[OFF + 2 * j] * r, o[OFF + 2 * j + 1] * r);
  }
}

__global__ void __cluster_dims__(2, 1, 1) __launch_bounds__(384, 1)
swin_attn_kernel(const __grid_constant__ Maps maps, const __nv_bfloat16* __restrict__ rpb, const int* __restrict__ rp_idx, int base, int never) {
  extern __shared__ __align__(1024) uint8_t smem_raw[];
  const uint32_t sb = (uint32_t)__cvta_generic_to_shared(smem_raw);
  const int tid = threadIdx.x;
  const int wg = __shfl_sync(0xffffffffu, tid >> 7, 0);
  const int warp = __shfl_sync(0xffffffffu, (tid >> 5) & 3, 0);
  const int lane = tid & 31;
  const int rank = blockIdx.x & 1;
  const int cl = blockIdx.x >> 1;
  const int ncl = gridDim.x >> 1;
  const uint32_t bars = sb + OFF_BAR;
  int extra = NWIN;
  auto read_ticket = [&]() {
    mbar_wait(bars + B_TICK, 0);
    uint32_t t;
    asm volatile("ld.shared.b32 %0, [%1];" : "=r"(t) : "r"(bars + W_TICK) : "memory");
    extra = base + __shfl_sync(0xffffffffu, t, 0);
  };
  auto window = [&](int v) { return v < base ? v : (v < base + ncl ? extra : NWIN); };
  TRP(0);
  CLKP(0);

  if (wg == KV_WG) {
    auto prefetch = [&](int p, int win) {
      if (p < 2) tma5_pf(&maps.x, (((win >> 3) & ~7) + 4 + 4 * rank) & 511, (win * 4 + 2 + 2 * p) & 255);
      else tma5_pf(&maps.mask, 0, 2 * win + rank);
    };
    auto load = [&](int p, int win, int a) {
      if (p < 2)
        tma5_mc(sb + OFF_X + a * STAGE + rank * 12288 + p * 6144, &maps.x, bars + B_XFULL + 8 * a,
                (((win >> 3) & ~7) + 4 + 4 * rank) & 511, (win * 4 + 2 + 2 * p) & 255);
      else tma5_mc(sb + OFF_MASK + a * STAGE + rank * 4096, &maps.mask, bars + B_XFULL + 8 * a, 0, 2 * win + rank);
    };
    auto load_wkv = [&](int b) {
      tma3(sb + OFF_KV + (b < 3 ? b * 12288 : STAGE + (b - 3) * 12288), &maps.wqkv, bars + B_WKV + 8 * (b >> 1), 0,
           (b < 3 ? 6 : 9) + b + 3 * rank);
    };
    if (warp == 3) {
      if (elect()) {
        if ((sb & 0x3FFFF) != SM_BASE) __trap();
#pragma unroll
        for (int a = 0; a < 2; a++) {
          mbar_init(bars + B_XFULL + 8 * a, 1);
          mbar_init(bars + B_XEMPTY + 8 * a, 1);
          mbar_init(bars + B_OFULL + 8 * a, 1);
          mbar_init(bars + B_OEMPTY + 8 * a, 4);
        }
#pragma unroll
        for (int k = 0; k < 6; k++) mbar_init(bars + B_WKV + 8 * k, 1);
        asm volatile("fence.mbarrier_init.release.cluster;" ::: "memory");
        fence_async();
        mbar_expect_tx(bars + B_WKV, 24576);
        load_wkv(0);
        load_wkv(1);
        mbar_expect_tx(bars + B_TICK, 4);
      }
      __syncwarp();
    }
    asm volatile("barrier.cluster.arrive.relaxed.aligned;" ::: "memory");
    asm volatile("setmaxnreg.inc.sync.aligned.u32 216;");
    asm volatile("barrier.cluster.wait.aligned;" ::: "memory");
    TRP(1);
    if (warp == 3 && elect()) {
      mbar_expect_tx(bars + B_XFULL, X_BYTES + M_BYTES);
      for (int p = 0; p < 3; p++) load(p, cl, 0);
      mbar_expect_tx(bars + B_WKV + 8, 24576);
      load_wkv(2);
      load_wkv(3);
      mbar_expect_tx(bars + B_WQ, 36864);
      for (int nb = 0; nb < 3; nb++) tma3(sb + OFF_WQ + nb * 12288, &maps.wqkv, bars + B_WQ, 0, 3 * rank + nb);
      mbar_expect_tx(bars + B_WKV + 16, 24576);
      load_wkv(4);
      load_wkv(5);
      mbar_expect_tx(bars + B_XFULL + 8, X_BYTES + M_BYTES);
      for (int p = 0; p < 3; p++) load(p, cl + ncl, 1);
      mbar_expect_tx(bars + B_WO, 36864);
      tma3(sb + OFF_WO, &maps.wo, bars + B_WO, 96 * rank, 3 * rank);
      for (int nb = 0; nb < 3; nb++)
        asm volatile("cp.async.bulk.tensor.5d.shared::cluster.global.mbarrier::complete_tx::bytes [%0], [%1, {%3, 0, 0, 0, %4}], [%2];" ::"r"(
                         sb + OFF_WO + 18432 + nb * 6144), "l"(&maps.wop), "r"(bars + B_WO), "r"(96 * rank + 32 * nb), "r"(3 * (rank ^ 1))
                     : "memory");
    }
    __syncwarp();
    uint32_t w[3][48];
    auto load_frags = [&](int s) {
      const uint32_t la = sb + OFF_KV + (warp >> 1) * 12288 + (8 * (lane >> 4) + (lane & 7)) * 64 +
                          (((2 * (warp & 1) + ((lane >> 3) & 1)) ^ ((lane & 7) >> 1)) << 4);
      mbar_wait(bars + B_WKV + 8 * s, 0);
      TRP(6 + s);
#pragma unroll
      for (int ks = 0; ks < 12; ks++)
        asm volatile("ldmatrix.sync.aligned.m8n8.x4.trans.shared.b16 {%0,%1,%2,%3}, [%4];"
                     : "=r"(w[s][4 * ks]), "=r"(w[s][4 * ks + 1]), "=r"(w[s][4 * ks + 2]), "=r"(w[s][4 * ks + 3])
                     : "r"(la + s * 24576 + (s == 2 || (s == 1 && warp >= 2) ? STAGE - 36864 : 0) + ks * 1024)
                     : "memory");
    };
    TRP(2);
    load_frags(0);
    TRP(3);
    uint32_t sta[4];
#pragma unroll
    for (int jj = 0; jj < 4; jj++) {
      sta[jj] = sb + OFF_KV + (16 * warp + (lane & 15)) * 128 + (((2 * jj + (lane >> 4)) ^ (lane & 7)) << 4);
      asm volatile("" : "+r"(sta[jj]));
    }
    const uint32_t xe_rem = mapa(bars + B_XEMPTY, rank ^ 1);
    const uint32_t v1off = warp > 0 ? 1024 : 0;

#define SF sched_fence(sta[0], never)
    float acc[32];
    uint32_t pk[16];
    auto store = [&](uint32_t off) {
#pragma unroll
      for (int jj = 0; jj < 4; jj++) stsm4(sta[jj] + off, pk[4 * jj], pk[4 * jj + 1], pk[4 * jj + 2], pk[4 * jj + 3]);
    };
    auto issue = [&](int s, uint32_t xd, bool st, uint32_t off) {
#pragma unroll
      for (int ks = 0; ks < 12; ks++) {
        uint64_t db = mkdesc(xd + (((ks >> 2) * 1024 + (ks & 3) * 32) >> 4), HI_X);
        if (ks == 0) mma_kv_init(acc, w[s][0], w[s][1], w[s][2], w[s][3], db);
        else mma_kv(acc, w[s][4 * ks], w[s][4 * ks + 1], w[s][4 * ks + 2], w[s][4 * ks + 3], db);
        if (ks == ST_AT && st) {
          __syncwarp();
          store(off);
          __syncwarp();
        }
      }
      wg_commit();
    };
    auto convert = [&]() {
      wg_wait<0>();
      pin(acc);
#pragma unroll
      for (int j = 0; j < 16; j++) pk[j] = pack_bf16(acc[2 * j], acc[2 * j + 1]);
      pin(pk);
    };

    mbar_wait(bars + B_XFULL, 0);
    TRP(4);
    wg_fence();
    issue(0, LO_X, false, 0);
    load_frags(1);
    TRP(5);
    [[maybe_unused]] int i = 0;
    int nxt = cl + ncl;
    uint32_t ph = 0;
    auto step = [&](auto A) -> bool {
      constexpr int a = decltype(A)::value;
      constexpr uint32_t xd = LO_X + a * (STAGE >> 4);
      if (nxt + ncl >= base && nxt < base) read_ticket();
      const bool more = window(nxt) < NWIN;
      const int wn2 = window(nxt + ncl);
      TR_SETUP(1);
      TR(0);
      convert();
      TR(1);
      wg_fence();
      SF;
      tok_wait<T2>();
      TR(2);
      issue(1, xd, true, a * STAGE);
      tok_pass<T3>();
      TR(3);
      if (warp < 3 && wn2 < NWIN && elect()) prefetch(warp, wn2);
      __syncwarp();
      TR(4);
      convert();
      store(a * STAGE + 8192);
      fence_async();
      const bool first = a == 0 && nxt == cl + ncl;
      if (first) {
        load_frags(2);
        asm volatile("bar.sync %0, 128;" ::"n"((int)BAR_STAGE) : "memory");
        asm volatile("st.shared.v4.b32 [%0], {%1,%1,%1,%1};" ::"r"(sb + OFF_KV + (warp >> 1) * STAGE + 144 * 128 + (tid & 63) * 16), "r"(0x3F803F80u) : "memory");
      }
      TR(5);
      wg_fence();
      tok_wait<T5>();
      TR(6);
      issue(2, xd, false, 0);
      tok_pass<T6>();
      if (!more) {
        convert();
        store(a * STAGE + 16384 + v1off);
        fence_async();
        return false;
      }
      { WS_BEGIN; mbar_wait(bars + B_XFULL + 8 * (a ^ 1), a ? ph ^ 1 : ph); WS_END(0); WS_END(8 + i); }
      TR(7);
      convert();
      TR(8);
      wg_fence();
      SF;
      tok_wait<T0>();
      TR(9);
      if (tid == KV_WG * 128) mbar_arrive_cluster(xe_rem + 8 * a);
      issue(0, LO_X + (a ^ 1) * (STAGE >> 4), true, a * STAGE + 16384 + v1off);
      tok_pass<T1>();
      TR(10);
      fence_async();
      tok_pass<T7>();
      nxt += ncl;
      if (wn2 < NWIN) {
        { WS_BEGIN; mbar_wait(bars + B_XEMPTY + 8 * a, ph); WS_END(1); }
        if (elect()) {
          if (warp < 3) load(warp, wn2, a);
          else mbar_expect_tx(bars + B_XFULL + 8 * a, X_BYTES + M_BYTES);
        }
        __syncwarp();
      }
      i++;
      return true;
    };
    while (step(IC<0>{}) && step(IC<1>{})) ph ^= 1;
    tok_wait<T0>();
    tok_pass<T1>();
    tok_pass<T7>();
    tok_wait<T2>();
    tok_pass<T3>();
    tok_wait<T5>();
  } else {
    const int a = wg - (KV_WG == 0 ? 1 : 0);
    const int g = lane >> 2, q = lane & 3;
    const uint32_t bar = bars + 8 * a;
    asm volatile("barrier.cluster.arrive.relaxed.aligned;" ::: "memory");
    if (a == 0) tok_pass<T2>();
    else tok_pass<T5>();
    asm volatile("setmaxnreg.dec.sync.aligned.u32 144;");
    uint32_t braw[32];
    {
      const int ty = 4 * (warp >> 1) + (g >> 1), tx = 4 * (warp & 1) + (g & 1);
      const int* ip = rp_idx + (ty * 8 + tx) * 64 + 8 * q;
#pragma unroll
      for (int c = 0; c < 8; c++)
        asm volatile("ld.global.nc.v4.b32 {%0,%1,%2,%3}, [%4];"
                     : "=r"(braw[4 * c]), "=r"(braw[4 * c + 1]), "=r"(braw[4 * c + 2]), "=r"(braw[4 * c + 3])
                     : "l"(ip + (c >> 2) * 128 + ((c >> 1) & 1) * 32 + (c & 1) * 4));
      const int e = a * 128 + (tid & 127);
      if (e < 225) {
        uint32_t v = __ldg(reinterpret_cast<const uint32_t*>(rpb) + e * 2 + rank);
        asm volatile("st.shared.b32 [%0], %1;" ::"r"(sb + OFF_RPB + e * 4), "r"(v) : "memory");
      }
      tok_wait<BAR_BIAS>();
#pragma unroll
      for (int j = 0; j < 32; j++)
        asm volatile("ld.shared.b32 %0, [%1];" : "=r"(braw[j]) : "r"(sb + OFF_RPB + braw[j] * 4) : "memory");
    }
    TRP(1);
    asm volatile("barrier.cluster.wait.aligned;" ::: "memory");
    TRP(2);

    const int mrow = 16 * warp + (g >> 1) + 4 * (g & 1);
#undef SF
#define SF sched_fence(mk_addr, never)
    uint32_t mk_addr = sb + OFF_MASK + a * STAGE + mrow * 128 + ((q ^ (mrow & 7)) << 4);
    const uint32_t ostage = sb + OFF_OIN + a * STAGE + warp * 3072;
    const uint32_t ost = ostage + ((lane >> 3) & 1) * 1536 + (lane & 7) * 64 + (((lane >> 4) ^ ((lane & 7) >> 1)) << 4);
    const uint32_t oin_rem = mapa(ostage + g * 64 + ((q ^ (g >> 1)) << 4), rank ^ 1);
    const uint32_t bar_rem = mapa(bar, rank ^ 1);

    auto store_out = [&](int win) {
      fence_async();
      __syncwarp();
      if (win >= 0 && elect()) {
        int yy = (((win >> 3) & ~7) + 4 + 4 * (warp >> 1)) & 511;
        int xh = (win * 4 + 2 + 2 * (warp & 1)) & 255;
        asm volatile("cp.async.bulk.tensor.5d.global.shared::cta.bulk_group [%0, {0, 0, %2, %3, %4}], [%1];" ::"l"(&maps.out), "r"(ostage),
                     "r"(yy), "r"(3 * rank), "r"(xh)
                     : "memory");
        asm volatile("cp.async.bulk.commit_group;" ::: "memory");
      }
      __syncwarp();
    };
    float qa[48];
    float s0[32];
    uint32_t bias0[16], bias1[16];
    uint32_t mk[16];
    auto load_mask = [&](uint32_t z) {
#pragma unroll
      for (int c = 0; c < 4; c++)
        lds128((c & 1 ? mk_addr ^ (64 + z) : mk_addr) + (c >> 1) * 1024, mk[4 * c], mk[4 * c + 1], mk[4 * c + 2], mk[4 * c + 3]);
    };
    auto pre_init = [&]() {
      SF;
#pragma unroll
      for (int j = 0; j < 16; j++) asm("max.NaN.bf16x2 %0, %0, %1;" : "+r"(mk[j]) : "r"(0xFD80FD80u));
      pin(mk);
      s_init<PRE_T, 8>(s0, mk, bias0);
    };
    auto issue_q = [&](uint32_t ua) {
#pragma unroll
      for (int ks = 0; ks < 12; ks++) {
        uint64_t da = mkdesc(ua + LO_X + (((ks >> 2) * 1024 + (ks & 3) * 32) >> 4), HI_X);
        uint64_t db = mkdesc(LO_WQ + ks * 64, HI_W);
        if (ks == 0) mma_q_init(qa, da, db);
        else mma_q(qa, da, db);
      }
      wg_commit();
    };
#pragma unroll
    for (int j = 0; j < 16; j++) {
      const uint32_t b0 = braw[2 * j], b1 = braw[2 * j + 1];
      bias0[j] = pack_bias(__uint_as_float(b0 << 16), __uint_as_float(b1 << 16));
      bias1[j] = pack_bias(__uint_as_float(b0 & 0xffff0000u), __uint_as_float(b1 & 0xffff0000u));
    }
    pin(bias0);
    pin(bias1);
    SF;
    TRP(5);
    if (a == 0) {
      mbar_wait(bars + B_XFULL, 0);
    } else {
      tok_wait<T1>();
      tok_pass<T2>();
    }
    load_mask(0);
    mbar_wait(bars + B_WQ, 0);
    TRP(3);
    wg_fence();
    if (a == 1) tok_wait<T3>();
    issue_q(a * (STAGE >> 4));
    if (a == 1) tok_pass<T4>();
    else tok_wait<T3>();
    TRP(4);
    pre_init();
    uint32_t ph = 0;
    [[maybe_unused]] int i = a;
    int win = cl + a * ncl;
    for (;; win += 2 * ncl, ph ^= 1, i += 2) {
      TR_SETUP(0);
      TR(0);
      const uint32_t ua = a * (STAGE >> 4) + (win >> 20);
      const uint32_t kd = ua + LO_KV;
      float s1[32];
      TR(1);
      wg_wait<0>();
      pin(qa);
      TR(2);
      uint32_t q0[12], q1[12];
#pragma unroll
      for (int j = 0; j < 12; j++) q0[j] = pack_bf16(qa[2 * j], qa[2 * j + 1]);
#pragma unroll
      for (int j = 0; j < 12; j++) q1[j] = pack_bf16(qa[24 + 2 * j], qa[25 + 2 * j]);
      pin(q0);
      pin(q1);
      s_init<0, PRE_T>(s0, mk, bias0);
      s_init<0, 8>(s1, mk, bias1);
      pin(s0);
      pin(s1);
      TR(3);
      wg_fence();
      tok_wait<T6>();
      TR(4);
#pragma unroll
      for (int ks = 0; ks < 3; ks++)
        mma_s(s0, q0[4 * ks], q0[4 * ks + 1], q0[4 * ks + 2], q0[4 * ks + 3], mkdesc(kd + ks * 128, HI_KV));
      wg_commit();
#pragma unroll
      for (int ks = 0; ks < 3; ks++)
        mma_s(s1, q1[4 * ks], q1[4 * ks + 1], q1[4 * ks + 2], q1[4 * ks + 3], mkdesc(kd + (3 + ks) * 128, HI_KV));
      wg_commit();
      tok_pass<T0>();
      store_out(win - 2 * ncl);
      const bool draw = rank == 0 && warp == 0 && win + 5 * ncl >= base && win + 4 * ncl < base;
      uint32_t ticket;
      if (draw && lane == 0) asm volatile("atom.global.inc.u32 %0, [%1], %2;" : "=r"(ticket) : "l"(&g_ticket), "r"(ncl - 1) : "memory");
      int x0, x1, y0, y1;
      wg_wait<1>();
      pin(s0);
      pin(q0);
      TR(5);
      rowmax_i(s0, x0, x1);
      quadmax_i(x0, x1, 1);
      wg_wait<0>();
      pin(s1);
      pin(q1);
      rowmax_i(s1, y0, y1);
      quadmax_i(x0, x1, 2);
      quadmax_i(y0, y1, 1);
      quadmax_i(y0, y1, 2);
      if (__builtin_expect(__any_sync(0xffffffffu, (x0 | x1 | y0 | y1) < 0), 0)) {
        rowmax_f(s0, x0, x1);
        rowmax_f(s1, y0, y1);
      }
      uint32_t p0[16], p1[16];
      exp_part<0, 16>(s0, p0, __int_as_float(x0) * -SM_C, __int_as_float(x1) * -SM_C);
      TR(6);
      float o0[28], o1[28];
      wg_fence();
      SF;
      tok_wait<T7>();
#pragma unroll
      for (int ks = 0; ks < 4; ks++) {
        uint64_t db = mkdesc(kd + ((96 * 128 + ks * 32) >> 4), HI_KV);
        if (ks == 0) mma_p_init(o0, p0[0], p0[1], p0[2], p0[3], db);
        else mma_p(o0, p0[4 * ks], p0[4 * ks + 1], p0[4 * ks + 2], p0[4 * ks + 3], db);
      }
      wg_commit();
      if (elect()) {
        { WS_BEGIN; asm volatile("cp.async.bulk.wait_group.read 0;" ::: "memory"); WS_END(4); }
        if (warp == 0) mbar_expect_tx(bar + B_OFULL, O_BYTES);
        mbar_arrive_cluster(bar_rem + B_OEMPTY);
      }
      __syncwarp();
      SF;
      const float m0 = __int_as_float(y0) * -SM_C, m1 = __int_as_float(y1) * -SM_C;
      exp_part<0, 16>(s1, p1, m0, m1);
      TR(7);
      wg_fence();
      SF;
      tok_wait<T4>();
      TR(8);
#pragma unroll
      for (int ks = 0; ks < 4; ks++) {
        uint64_t db = mkdesc(kd + ((144 * 128 + ks * 32) >> 4), HI_KV);
        if (ks == 0) mma_p_init(o1, p1[0], p1[1], p1[2], p1[3], db);
        else mma_p(o1, p1[4 * ks], p1[4 * ks + 1], p1[4 * ks + 2], p1[4 * ks + 3], db);
      }
      wg_commit();
      tok_pass<T5>();
      { WS_BEGIN; mbar_wait(bar + B_OEMPTY, ph); WS_END(2); }
      uint32_t f0[12], f1[12];
      wg_wait<1>();
      pin(o0);
      pin(p0);
      normalize<24, 0>(o0, f0);
      st_async<0>(oin_rem, bar_rem + B_OFULL, f0[0], f0[2], f0[4], f0[6]);
      st_async<1536>(oin_rem, bar_rem + B_OFULL, f0[1], f0[3], f0[5], f0[7]);
      wg_wait<0>();
      pin(o1);
      pin(p1);
      TR(9);
      normalize<0, 4>(o1, f1);
      st_async<512>(oin_rem, bar_rem + B_OFULL, f0[8], f0[10], f1[0], f1[2]);
      st_async<2048>(oin_rem, bar_rem + B_OFULL, f0[9], f0[11], f1[1], f1[3]);
      st_async<1024>(oin_rem, bar_rem + B_OFULL, f1[4], f1[6], f1[8], f1[10]);
      st_async<2560>(oin_rem, bar_rem + B_OFULL, f1[5], f1[7], f1[9], f1[11]);
      pin(f0);
      pin(f1);
      float (&oa)[48] = qa;
      if (win < 2 * ncl) mbar_wait(bars + B_WO, 0);
      if (draw) {
        ticket = __shfl_sync(0xffffffffu, ticket, 0);
        if (lane < 2)
          asm volatile("st.async.shared::cluster.mbarrier::complete_tx::bytes.b32 [%0], %1, [%2];" ::"r"(mapa(bars + W_TICK, lane)),
                       "r"(ticket), "r"(mapa(bars + B_TICK, lane))
                       : "memory");
        __syncwarp();
      }
      if (win + 2 * ncl >= base) read_ticket();
      const bool last = window(win + ncl) >= NWIN;
      TR(10);
      wg_fence();
      if (!last) tok_wait<T1>();
      TR(11);
#pragma unroll
      for (int ks = 0; ks < 3; ks++) {
        uint64_t db = mkdesc(LO_WO + ks * 64, HI_W);
        if (ks == 0) mma_o_init(oa, f0[0], f0[1], f0[2], f0[3], db);
        else mma_o(oa, f0[4 * ks], f0[4 * ks + 1], f0[4 * ks + 2], f0[4 * ks + 3], db);
      }
#pragma unroll
      for (int ks = 0; ks < 3; ks++)
        mma_o(oa, f1[4 * ks], f1[4 * ks + 1], f1[4 * ks + 2], f1[4 * ks + 3], mkdesc(LO_WO + (3 + ks) * 64, HI_W));
      { WS_BEGIN; mbar_wait(bar + B_OFULL, ph); WS_END(3); }
      asm volatile("fence.proxy.async::generic.acquire.sync_restrict::shared::cluster.cluster;" ::: "memory");
      wg_fence();
#pragma unroll
      for (int ks = 0; ks < 6; ks++)
        mma_q(oa, mkdesc(ua + LO_O + (((ks >> 1) * 512 + (ks & 1) * 32) >> 4), HI_O), mkdesc(LO_WO + (18432 >> 4) + ks * 64, HI_W));
      wg_commit();
      if (!last) tok_pass<T2>();
      load_mask(win >> 20);
      wg_wait<0>();
      pin(oa);
      pin(f0);
      pin(f1);
      TR(12);
#pragma unroll
      for (int jj = 0; jj < 6; jj++)
        stsm4((jj & 1 ? ost ^ (32 + (win >> 20)) : ost) + (jj >> 1) * 512, pack_bf16(oa[8 * jj], oa[8 * jj + 1]), pack_bf16(oa[8 * jj + 2], oa[8 * jj + 3]),
              pack_bf16(oa[8 * jj + 4], oa[8 * jj + 5]), pack_bf16(oa[8 * jj + 6], oa[8 * jj + 7]));
      if (window(win + 2 * ncl) >= NWIN) {
        if (!last) {
          tok_wait<T3>();
          tok_pass<T4>();
        }
        break;
      }
      wg_fence();
      tok_wait<T3>();
      TR(13);
      issue_q(ua);
      tok_pass<T4>();
      TR(14);
      pre_init();
    }
    store_out(window(win));
    asm volatile("cp.async.bulk.wait_group 0;" ::: "memory");
    __syncwarp();
  }
  asm volatile("barrier.cluster.arrive.relaxed.aligned;" ::: "memory");
  asm volatile("barrier.cluster.wait.aligned;" ::: "memory");
  CLKP(1);
}

typedef CUresult (*EncodeFn)(CUtensorMap*, CUtensorMapDataType, cuuint32_t, void*, const cuuint64_t*, const cuuint64_t*,
                             const cuuint32_t*, const cuuint32_t*, CUtensorMapInterleave, CUtensorMapSwizzle,
                             CUtensorMapL2promotion, CUtensorMapFloatOOBfill);

void encode_map(EncodeFn encode, CUtensorMap* m, void* p, int rank, const cuuint64_t* dim, const cuuint64_t* str,
                const cuuint32_t* box, CUtensorMapSwizzle sw) {
  const cuuint32_t es[5] = {1, 1, 1, 1, 1};
  CUresult r = encode(m, CU_TENSOR_MAP_DATA_TYPE_BFLOAT16, rank, p, dim, str, box, es, CU_TENSOR_MAP_INTERLEAVE_NONE, sw,
                      CU_TENSOR_MAP_L2_PROMOTION_L2_128B, CU_TENSOR_MAP_FLOAT_OOB_FILL_NONE);
  if (r != CUDA_SUCCESS) fprintf(stderr, "tensor map encode failed: %d\n", (int)r);
}

}

extern "C" void kernel_launch(void* const* d_in, const int* in_sizes, int n_in, void* d_out, int out_size) {
  static EncodeFn encode = nullptr;
  static int grid = 0;
  if (!encode) {
    cudaDriverEntryPointQueryResult qr;
    void* fn = nullptr;
    cudaGetDriverEntryPoint("cuTensorMapEncodeTiled", &fn, cudaEnableDefault, &qr);
    encode = (EncodeFn)fn;
    cudaFuncSetAttribute(swin_attn_kernel, cudaFuncAttributeMaxDynamicSharedMemorySize, SMEM_BYTES);
    cudaLaunchConfig_t cfg = {};
    cfg.gridDim = dim3(132);
    cfg.blockDim = dim3(384);
    cfg.dynamicSmemBytes = SMEM_BYTES;
    cudaLaunchAttribute at;
    at.id = cudaLaunchAttributeClusterDimension;
    at.val.clusterDim.x = 2;
    at.val.clusterDim.y = 1;
    at.val.clusterDim.z = 1;
    cfg.attrs = &at;
    cfg.numAttrs = 1;
    int ncl = 0;
    if (cudaOccupancyMaxActiveClusters(&ncl, swin_attn_kernel, &cfg) != cudaSuccess || ncl < 1) {
      (void)cudaGetLastError();
      ncl = 66;
    }
    if (ncl > 256) ncl = 256;
    grid = 2 * ncl;
  }
  Maps maps;
  {
    const cuuint64_t dim[5] = {64, 2, 512, 3, 256}, str[4] = {384, 512 * 384, 128, 768};
    const cuuint32_t box[5] = {64, 2, 4, 3, 2};
    encode_map(encode, &maps.x, d_in[0], 5, dim, str, box, CU_TENSOR_MAP_SWIZZLE_128B);
  }
  {
    const cuuint64_t dim[5] = {64, 4, 2, 4, 8192}, str[4] = {1024, 128, 256, 4096};
    const cuuint32_t box[5] = {64, 4, 2, 4, 1};
    encode_map(encode, &maps.mask, d_in[5], 5, dim, str, box, CU_TENSOR_MAP_SWIZZLE_128B);
  }
  {
    const cuuint64_t dim[5] = {32, 2, 512, 6, 256}, str[4] = {384, 512 * 384, 64, 768};
    const cuuint32_t box[5] = {32, 2, 4, 3, 2};
    encode_map(encode, &maps.out, d_out, 5, dim, str, box, CU_TENSOR_MAP_SWIZZLE_64B);
  }
  {
    const cuuint64_t dim[3] = {32, 192, 18}, str[2] = {576 * 2, 64};
    const cuuint32_t box[3] = {32, 192, 1};
    encode_map(encode, &maps.wqkv, d_in[1], 3, dim, str, box, CU_TENSOR_MAP_SWIZZLE_64B);
    const cuuint64_t dim2[3] = {32, 192, 6}, str2[2] = {192 * 2, 64};
    const cuuint32_t box2[3] = {32, 96, 3};
    encode_map(encode, &maps.wo, d_in[2], 3, dim2, str2, box2, CU_TENSOR_MAP_SWIZZLE_64B);
    const cuuint64_t dim3_[5] = {192, 2, 4, 4, 6}, str3[4] = {384, 8 * 384, 2 * 384, 32 * 384};
    const cuuint32_t box3[5] = {32, 2, 4, 4, 3};
    encode_map(encode, &maps.wop, d_in[2], 5, dim3_, str3, box3, CU_TENSOR_MAP_SWIZZLE_64B);
  }
  swin_attn_kernel<<<grid, 384, SMEM_BYTES>>>(maps, (const __nv_bfloat16*)d_in[3], (const int*)d_in[4], NWIN / (grid / 2) * (grid / 2), 0);
}
```

```cpp
#include <cuda_runtime.h>
#include <cuda_bf16.h>
#include <cuda.h>
#include <stdint.h>
#include <stdio.h>

namespace {

constexpr int NWIN = 4096;
#define KV_WG 0
#define L2PROMO CU_TENSOR_MAP_L2_PROMOTION_L2_128B
#define Q_SPLIT 4
#define STORE_AT 1
#define S1_LATE 0
#define PM0 0
#define PM1 0
#define SM_MODE 0
#define EXP_CH 0
#define ST_AT 3
#define PRE_T 8

constexpr uint32_t SM_BASE  = 1024;
constexpr uint32_t OFF_WQ   = 0;
constexpr uint32_t OFF_WO   = 36864;
constexpr uint32_t STAGE    = 70656;
constexpr uint32_t OFF_X    = 73728;
constexpr uint32_t X_BYTES  = 24576;
constexpr uint32_t OFF_MASK = OFF_X + X_BYTES;
constexpr uint32_t M_BYTES  = 8192;
constexpr uint32_t OFF_KV   = OFF_MASK + M_BYTES;
constexpr uint32_t OFF_OIN  = OFF_KV + 25600;
constexpr uint32_t O_BYTES  = 12288;
constexpr uint32_t OFF_BAR  = 215040;
constexpr uint32_t OFF_RPB  = OFF_BAR + 1024;
constexpr uint32_t SMEM_BYTES = OFF_RPB + 1024;
constexpr uint32_t B_XFULL = 0, B_XEMPTY = 16, B_OFULL = 32, B_OEMPTY = 48, B_WKV = 64  , B_WQ = 88, B_WO = 96,
                   B_TICK = 104, W_TICK = 112;
enum { T0 = 1, T1, T2, T3, T4, T5, T6, T7, BAR_BIAS, BAR_STAGE };

__device__ unsigned int g_ticket;

template <int V> struct IC { static constexpr int value = V; };
struct Maps { CUtensorMap x, mask, out, wqkv, wo, wop; };

__device__ __forceinline__ void mma_q_init(float (&d)[48], uint64_t descA, uint64_t descB) {
  asm volatile("wgmma.mma_async.sync.aligned.m64n96k16.f32.bf16.bf16 {%0, %1, %2, %3, %4, %5, %6, %7, %8, %9, %10, %11, %12, %13, %14, %15, %16, %17, %18, %19, %20, %21, %22, %23, %24, %25, %26, %27, %28, %29, %30, %31, %32, %33, %34, %35, %36, %37, %38, %39, %40, %41, %42, %43, %44, %45, %46, %47}, "
    "%48, %49, 0, 1, 1, 0, 1;"
    : "+f"(d[0]), "+f"(d[1]), "+f"(d[2]), "+f"(d[3]), "+f"(d[4]), "+f"(d[5]), "+f"(d[6]), "+f"(d[7]), "+f"(d[8]), "+f"(d[9]), "+f"(d[10]), "+f"(d[11]), "+f"(d[12]), "+f"(d[13]), "+f"(d[14]), "+f"(d[15]), "+f"(d[16]), "+f"(d[17]), "+f"(d[18]), "+f"(d[19]), "+f"(d[20]), "+f"(d[21]), "+f"(d[22]), "+f"(d[23]), "+f"(d[24]), "+f"(d[25]), "+f"(d[26]), "+f"(d[27]), "+f"(d[28]), "+f"(d[29]), "+f"(d[30]), "+f"(d[31]), "+f"(d[32]), "+f"(d[33]), "+f"(d[34]), "+f"(d[35]), "+f"(d[36]), "+f"(d[37]), "+f"(d[38]), "+f"(d[39]), "+f"(d[40]), "+f"(d[41]), "+f"(d[42]), "+f"(d[43]), "+f"(d[44]), "+f"(d[45]), "+f"(d[46]), "+f"(d[47])
    : "l"(descA), "l"(descB));
}
__device__ __forceinline__ void mma_q(float (&d)[48], uint64_t descA, uint64_t descB) {
  asm volatile("wgmma.mma_async.sync.aligned.m64n96k16.f32.bf16.bf16 {%0, %1, %2, %3, %4, %5, %6, %7, %8, %9, %10, %11, %12, %13, %14, %15, %16, %17, %18, %19, %20, %21, %22, %23, %24, %25, %26, %27, %28, %29, %30, %31, %32, %33, %34, %35, %36, %37, %38, %39, %40, %41, %42, %43, %44, %45, %46, %47}, "
    "%48, %49, 1, 1, 1, 0, 1;"
    : "+f"(d[0]), "+f"(d[1]), "+f"(d[2]), "+f"(d[3]), "+f"(d[4]), "+f"(d[5]), "+f"(d[6]), "+f"(d[7]), "+f"(d[8]), "+f"(d[9]), "+f"(d[10]), "+f"(d[11]), "+f"(d[12]), "+f"(d[13]), "+f"(d[14]), "+f"(d[15]), "+f"(d[16]), "+f"(d[17]), "+f"(d[18]), "+f"(d[19]), "+f"(d[20]), "+f"(d[21]), "+f"(d[22]), "+f"(d[23]), "+f"(d[24]), "+f"(d[25]), "+f"(d[26]), "+f"(d[27]), "+f"(d[28]), "+f"(d[29]), "+f"(d[30]), "+f"(d[31]), "+f"(d[32]), "+f"(d[33]), "+f"(d[34]), "+f"(d[35]), "+f"(d[36]), "+f"(d[37]), "+f"(d[38]), "+f"(d[39]), "+f"(d[40]), "+f"(d[41]), "+f"(d[42]), "+f"(d[43]), "+f"(d[44]), "+f"(d[45]), "+f"(d[46]), "+f"(d[47])
    : "l"(descA), "l"(descB));
}
__device__ __forceinline__ void mma_kv_init(float (&d)[32], uint32_t a0, uint32_t a1, uint32_t a2, uint32_t a3, uint64_t descB) {
  asm volatile("wgmma.mma_async.sync.aligned.m64n64k16.f32.bf16.bf16 {%0, %1, %2, %3, %4, %5, %6, %7, %8, %9, %10, %11, %12, %13, %14, %15, %16, %17, %18, %19, %20, %21, %22, %23, %24, %25, %26, %27, %28, %29, %30, %31}, "
    "{%32, %33, %34, %35}, %36, 0, 1, 1, 0;"
    : "+f"(d[0]), "+f"(d[1]), "+f"(d[2]), "+f"(d[3]), "+f"(d[4]), "+f"(d[5]), "+f"(d[6]), "+f"(d[7]), "+f"(d[8]), "+f"(d[9]), "+f"(d[10]), "+f"(d[11]), "+f"(d[12]), "+f"(d[13]), "+f"(d[14]), "+f"(d[15]), "+f"(d[16]), "+f"(d[17]), "+f"(d[18]), "+f"(d[19]), "+f"(d[20]), "+f"(d[21]), "+f"(d[22]), "+f"(d[23]), "+f"(d[24]), "+f"(d[25]), "+f"(d[26]), "+f"(d[27]), "+f"(d[28]), "+f"(d[29]), "+f"(d[30]), "+f"(d[31])
    : "r"(a0), "r"(a1), "r"(a2), "r"(a3), "l"(descB));
}
__device__ __forceinline__ void mma_kv(float (&d)[32], uint32_t a0, uint32_t a1, uint32_t a2, uint32_t a3, uint64_t descB) {
  asm volatile("wgmma.mma_async.sync.aligned.m64n64k16.f32.bf16.bf16 {%0, %1, %2, %3, %4, %5, %6, %7, %8, %9, %10, %11, %12, %13, %14, %15, %16, %17, %18, %19, %20, %21, %22, %23, %24, %25, %26, %27, %28, %29, %30, %31}, "
    "{%32, %33, %34, %35}, %36, 1, 1, 1, 0;"
    : "+f"(d[0]), "+f"(d[1]), "+f"(d[2]), "+f"(d[3]), "+f"(d[4]), "+f"(d[5]), "+f"(d[6]), "+f"(d[7]), "+f"(d[8]), "+f"(d[9]), "+f"(d[10]), "+f"(d[11]), "+f"(d[12]), "+f"(d[13]), "+f"(d[14]), "+f"(d[15]), "+f"(d[16]), "+f"(d[17]), "+f"(d[18]), "+f"(d[19]), "+f"(d[20]), "+f"(d[21]), "+f"(d[22]), "+f"(d[23]), "+f"(d[24]), "+f"(d[25]), "+f"(d[26]), "+f"(d[27]), "+f"(d[28]), "+f"(d[29]), "+f"(d[30]), "+f"(d[31])
    : "r"(a0), "r"(a1), "r"(a2), "r"(a3), "l"(descB));
}
__device__ __forceinline__ void mma_s(float (&d)[32], uint32_t a0, uint32_t a1, uint32_t a2, uint32_t a3, uint64_t descB) {
  asm volatile("wgmma.mma_async.sync.aligned.m64n64k16.f32.bf16.bf16 {%0, %1, %2, %3, %4, %5, %6, %7, %8, %9, %10, %11, %12, %13, %14, %15, %16, %17, %18, %19, %20, %21, %22, %23, %24, %25, %26, %27, %28, %29, %30, %31}, "
    "{%32, %33, %34, %35}, %36, 1, 1, 1, 1;"
    : "+f"(d[0]), "+f"(d[1]), "+f"(d[2]), "+f"(d[3]), "+f"(d[4]), "+f"(d[5]), "+f"(d[6]), "+f"(d[7]), "+f"(d[8]), "+f"(d[9]), "+f"(d[10]), "+f"(d[11]), "+f"(d[12]), "+f"(d[13]), "+f"(d[14]), "+f"(d[15]), "+f"(d[16]), "+f"(d[17]), "+f"(d[18]), "+f"(d[19]), "+f"(d[20]), "+f"(d[21]), "+f"(d[22]), "+f"(d[23]), "+f"(d[24]), "+f"(d[25]), "+f"(d[26]), "+f"(d[27]), "+f"(d[28]), "+f"(d[29]), "+f"(d[30]), "+f"(d[31])
    : "r"(a0), "r"(a1), "r"(a2), "r"(a3), "l"(descB));
}
__device__ __forceinline__ void mma_p_init(float (&d)[28], uint32_t a0, uint32_t a1, uint32_t a2, uint32_t a3, uint64_t descB) {
  asm volatile("wgmma.mma_async.sync.aligned.m64n56k16.f32.bf16.bf16 {%0, %1, %2, %3, %4, %5, %6, %7, %8, %9, %10, %11, %12, %13, %14, %15, %16, %17, %18, %19, %20, %21, %22, %23, %24, %25, %26, %27}, "
    "{%28, %29, %30, %31}, %32, 0, 1, 1, 0;"
    : "=f"(d[0]), "=f"(d[1]), "=f"(d[2]), "=f"(d[3]), "=f"(d[4]), "=f"(d[5]), "=f"(d[6]), "=f"(d[7]), "=f"(d[8]), "=f"(d[9]), "=f"(d[10]), "=f"(d[11]), "=f"(d[12]), "=f"(d[13]), "=f"(d[14]), "=f"(d[15]), "=f"(d[16]), "=f"(d[17]), "=f"(d[18]), "=f"(d[19]), "=f"(d[20]), "=f"(d[21]), "=f"(d[22]), "=f"(d[23]), "=f"(d[24]), "=f"(d[25]), "=f"(d[26]), "=f"(d[27])
    : "r"(a0), "r"(a1), "r"(a2), "r"(a3), "l"(descB));
}
__device__ __forceinline__ void mma_p(float (&d)[28], uint32_t a0, uint32_t a1, uint32_t a2, uint32_t a3, uint64_t descB) {
  asm volatile("wgmma.mma_async.sync.aligned.m64n56k16.f32.bf16.bf16 {%0, %1, %2, %3, %4, %5, %6, %7, %8, %9, %10, %11, %12, %13, %14, %15, %16, %17, %18, %19, %20, %21, %22, %23, %24, %25, %26, %27}, "
    "{%28, %29, %30, %31}, %32, 1, 1, 1, 0;"
    : "+f"(d[0]), "+f"(d[1]), "+f"(d[2]), "+f"(d[3]), "+f"(d[4]), "+f"(d[5]), "+f"(d[6]), "+f"(d[7]), "+f"(d[8]), "+f"(d[9]), "+f"(d[10]), "+f"(d[11]), "+f"(d[12]), "+f"(d[13]), "+f"(d[14]), "+f"(d[15]), "+f"(d[16]), "+f"(d[17]), "+f"(d[18]), "+f"(d[19]), "+f"(d[20]), "+f"(d[21]), "+f"(d[22]), "+f"(d[23]), "+f"(d[24]), "+f"(d[25]), "+f"(d[26]), "+f"(d[27])
    : "r"(a0), "r"(a1), "r"(a2), "r"(a3), "l"(descB));
}
__device__ __forceinline__ void mma_o_init(float (&d)[48], uint32_t a0, uint32_t a1, uint32_t a2, uint32_t a3, uint64_t descB) {
  asm volatile("wgmma.mma_async.sync.aligned.m64n96k16.f32.bf16.bf16 {%0, %1, %2, %3, %4, %5, %6, %7, %8, %9, %10, %11, %12, %13, %14, %15, %16, %17, %18, %19, %20, %21, %22, %23, %24, %25, %26, %27, %28, %29, %30, %31, %32, %33, %34, %35, %36, %37, %38, %39, %40, %41, %42, %43, %44, %45, %46, %47}, "
    "{%48, %49, %50, %51}, %52, 0, 1, 1, 1;"
    : "=f"(d[0]), "=f"(d[1]), "=f"(d[2]), "=f"(d[3]), "=f"(d[4]), "=f"(d[5]), "=f"(d[6]), "=f"(d[7]), "=f"(d[8]), "=f"(d[9]), "=f"(d[10]), "=f"(d[11]), "=f"(d[12]), "=f"(d[13]), "=f"(d[14]), "=f"(d[15]), "=f"(d[16]), "=f"(d[17]), "=f"(d[18]), "=f"(d[19]), "=f"(d[20]), "=f"(d[21]), "=f"(d[22]), "=f"(d[23]), "=f"(d[24]), "=f"(d[25]), "=f"(d[26]), "=f"(d[27]), "=f"(d[28]), "=f"(d[29]), "=f"(d[30]), "=f"(d[31]), "=f"(d[32]), "=f"(d[33]), "=f"(d[34]), "=f"(d[35]), "=f"(d[36]), "=f"(d[37]), "=f"(d[38]), "=f"(d[39]), "=f"(d[40]), "=f"(d[41]), "=f"(d[42]), "=f"(d[43]), "=f"(d[44]), "=f"(d[45]), "=f"(d[46]), "=f"(d[47])
    : "r"(a0), "r"(a1), "r"(a2), "r"(a3), "l"(descB));
}
__device__ __forceinline__ void mma_o(float (&d)[48], uint32_t a0, uint32_t a1, uint32_t a2, uint32_t a3, uint64_t descB) {
  asm volatile("wgmma.mma_async.sync.aligned.m64n96k16.f32.bf16.bf16 {%0, %1, %2, %3, %4, %5, %6, %7, %8, %9, %10, %11, %12, %13, %14, %15, %16, %17, %18, %19, %20, %21, %22, %23, %24, %25, %26, %27, %28, %29, %30, %31, %32, %33, %34, %35, %36, %37, %38, %39, %40, %41, %42, %43, %44, %45, %46, %47}, "
    "{%48, %49, %50, %51}, %52, 1, 1, 1, 1;"
    : "+f"(d[0]), "+f"(d[1]), "+f"(d[2]), "+f"(d[3]), "+f"(d[4]), "+f"(d[5]), "+f"(d[6]), "+f"(d[7]), "+f"(d[8]), "+f"(d[9]), "+f"(d[10]), "+f"(d[11]), "+f"(d[12]), "+f"(d[13]), "+f"(d[14]), "+f"(d[15]), "+f"(d[16]), "+f"(d[17]), "+f"(d[18]), "+f"(d[19]), "+f"(d[20]), "+f"(d[21]), "+f"(d[22]), "+f"(d[23]), "+f"(d[24]), "+f"(d[25]), "+f"(d[26]), "+f"(d[27]), "+f"(d[28]), "+f"(d[29]), "+f"(d[30]), "+f"(d[31]), "+f"(d[32]), "+f"(d[33]), "+f"(d[34]), "+f"(d[35]), "+f"(d[36]), "+f"(d[37]), "+f"(d[38]), "+f"(d[39]), "+f"(d[40]), "+f"(d[41]), "+f"(d[42]), "+f"(d[43]), "+f"(d[44]), "+f"(d[45]), "+f"(d[46]), "+f"(d[47])
    : "r"(a0), "r"(a1), "r"(a2), "r"(a3), "l"(descB));
}

__device__ __forceinline__ void wg_fence() { asm volatile("wgmma.fence.sync.aligned;" ::: "memory"); }
__device__ __forceinline__ void wg_commit() { asm volatile("wgmma.commit_group.sync.aligned;" ::: "memory"); }
template <int N> __device__ __forceinline__ void wg_wait() { asm volatile("wgmma.wait_group.sync.aligned %0;" ::"n"(N) : "memory"); }
template <int N> __device__ __forceinline__ void pin(float (&d)[N]) {
#pragma unroll
  for (int i = 0; i < N; i++) asm volatile("" : "+f"(d[i])::"memory");
}
template <int N> __device__ __forceinline__ void pin(uint32_t (&d)[N]) {
#pragma unroll
  for (int i = 0; i < N; i++) asm volatile("" : "+r"(d[i])::"memory");
}
__device__ __forceinline__ uint64_t mkdesc(uint32_t lo, uint32_t hi) { return ((uint64_t)hi << 32) | lo; }
[[maybe_unused]] constexpr uint64_t EVICT_FIRST = 0x12F0000000000000ull;
constexpr uint32_t HI_X = (3072 >> 4) | (1u << 30);
constexpr uint32_t HI_KV = (1024 >> 4) | (1u << 30);
constexpr uint32_t HI_W = (512 >> 4) | (2u << 30);
constexpr uint32_t HI_O = (1536 >> 4) | (2u << 30);
constexpr uint32_t LO_O = (1u << 16) + ((SM_BASE + OFF_OIN) >> 4);
constexpr uint32_t LO_WQ = ((12288 >> 4) << 16) + ((SM_BASE + OFF_WQ) >> 4);
constexpr uint32_t LO_WO = ((6144 >> 4) << 16) + ((SM_BASE + OFF_WO) >> 4);
constexpr uint32_t LO_X = (1u << 16) + ((SM_BASE + OFF_X) >> 4);
constexpr uint32_t LO_KV = (1u << 16) + ((SM_BASE + OFF_KV) >> 4);

__device__ __forceinline__ uint32_t pack_bf16(float lo, float hi) {
  uint32_t r;
  asm("cvt.rn.bf16x2.f32 %0, %1, %2;" : "=r"(r) : "f"(hi), "f"(lo));
  return r;
}
__device__ __forceinline__ float ex2(float x) {
  float r;
  asm("ex2.approx.ftz.f32 %0, %1;" : "=f"(r) : "f"(x));
  return r;
}
__device__ __forceinline__ float rcp(float x) {
  float r;
  asm("rcp.approx.ftz.f32 %0, %1;" : "=f"(r) : "f"(x));
  return r;
}
__device__ __forceinline__ bool elect() {
  uint32_t p;
  asm volatile("{\n.reg .pred P;\nelect.sync _|P, 0xffffffff;\nselp.u32 %0, 1, 0, P;\n}" : "=r"(p));
  return p;
}
__device__ __forceinline__ void mbar_init(uint32_t bar, uint32_t cnt) {
  asm volatile("mbarrier.init.shared::cta.b64 [%0], %1;" ::"r"(bar), "r"(cnt) : "memory");
}
__device__ __forceinline__ void mbar_wait(uint32_t bar, uint32_t parity) {
  asm volatile(
      "{\n.reg .pred p;\n.reg .u32 n;\n"
      "mbarrier.try_wait.parity.shared::cta.b64 p, [%0], %1;\n"
      "@p bra DONE;\n"
      "mov.u32 n, 0;\n"
      "LOOP:\n"
      "mbarrier.try_wait.parity.shared::cta.b64 p, [%0], %1;\n"
      "@p bra DONE;\n"
      "add.u32 n, n, 1;\n"
      "setp.lt.u32 p, n, 0x400000;\n"
      "@p bra LOOP;\n"
      "trap;\n"
      "DONE:\n}\n" ::"r"(bar), "r"(parity)
      : "memory");
}
__device__ __forceinline__ void mbar_arrive_cluster(uint32_t bar) {
  asm volatile("mbarrier.arrive.shared::cluster.b64 _, [%0];" ::"r"(bar) : "memory");
}
__device__ __forceinline__ void mbar_expect_tx(uint32_t bar, uint32_t bytes) {
  asm volatile("mbarrier.arrive.expect_tx.shared::cta.b64 _, [%0], %1;" ::"r"(bar), "r"(bytes) : "memory");
}
__device__ __forceinline__ uint32_t mapa(uint32_t addr, uint32_t rank) {
  uint32_t r;
  asm("mapa.shared::cluster.u32 %0, %1, %2;" : "=r"(r) : "r"(addr), "r"(rank));
  return r;
}
__device__ __forceinline__ void sched_fence(uint32_t& keep, int never) {
  asm volatile("{\n.reg .pred p;\nsetp.ne.s32 p, %1, 0;\n@p mov.u32 %0, %clock;\n}" : "+r"(keep) : "r"(never) : "memory");
}
#define DLY 0
#define DELAY(k, keep) do { if (DLY == (k)) { SF; float z_ = __uint_as_float(keep); for (int q_ = 0; q_ < 3; q_++) asm volatile("rcp.approx.ftz.f32 %0, %0;" : "+f"(z_)); \
  keep += __float_as_uint(z_) * never; SF; } } while (0)
template <int ID> __device__ __forceinline__ void tok_wait() { asm volatile("bar.sync %0, 256;" ::"n"(ID) : "memory"); }
template <int ID> __device__ __forceinline__ void tok_pass() { asm volatile("bar.arrive %0, 256;" ::"n"(ID) : "memory"); }
__device__ __forceinline__ void fence_async() { asm volatile("fence.proxy.async.shared::cta;" ::: "memory"); }
__device__ __forceinline__ void stsm4(uint32_t addr, uint32_t r0, uint32_t r1, uint32_t r2, uint32_t r3) {
  asm volatile("stmatrix.sync.aligned.m8n8.x4.shared.b16 [%0], {%1,%2,%3,%4};" ::"r"(addr), "r"(r0), "r"(r1), "r"(r2), "r"(r3) : "memory");
}
__device__ __forceinline__ void lds128(uint32_t addr, uint32_t& r0, uint32_t& r1, uint32_t& r2, uint32_t& r3) {
  asm volatile("ld.shared.v4.b32 {%0,%1,%2,%3}, [%4];" : "=r"(r0), "=r"(r1), "=r"(r2), "=r"(r3) : "r"(addr) : "memory");
}
template <int OFF>
__device__ __forceinline__ void st_async(uint32_t addr, uint32_t bar, uint32_t r0, uint32_t r1, uint32_t r2, uint32_t r3) {
  asm volatile("st.async.shared::cluster.mbarrier::complete_tx::bytes.v4.b32 [%0+%6], {%1,%2,%3,%4}, [%5];" ::"r"(addr), "r"(r0),
               "r"(r1), "r"(r2), "r"(r3), "r"(bar), "n"(OFF)
               : "memory");
}
__device__ __forceinline__ void tma5_mc(uint32_t dst, const CUtensorMap* tm, uint32_t bar, int c2, int c4) {
  asm volatile(
      "cp.async.bulk.tensor.5d.shared::cluster.global.mbarrier::complete_tx::bytes.multicast::cluster "
      "[%0], [%1, {0, 0, %3, 0, %4}], [%2], %5;" ::"r"(dst), "l"(tm), "r"(bar), "r"(c2), "r"(c4), "h"((uint16_t)3)
      : "memory");
}
__device__ __forceinline__ void tma5_pf(const CUtensorMap* tm, int c2, int c4) {
  asm volatile("cp.async.bulk.prefetch.tensor.5d.L2.global [%0, {0, 0, %1, 0, %2}];" ::"l"(tm), "r"(c2), "r"(c4) : "memory");
}
__device__ __forceinline__ void tma3(uint32_t dst, const CUtensorMap* tm, uint32_t bar, int c1, int c2) {
  asm volatile("cp.async.bulk.tensor.3d.shared::cluster.global.mbarrier::complete_tx::bytes [%0], [%1, {0, %3, %4}], [%2];" ::"r"(dst),
               "l"(tm), "r"(bar), "r"(c1), "r"(c2)
               : "memory");
}
#define TR_SETUP(kv)
#define TR(k)
#define TRP(k)

#define WS_BEGIN
#define WS_END(k)
#define CLKP(k)

constexpr float SQRT_HD = 6.92820323027551f;
constexpr float SM_C = 1.4426950408889634f / SQRT_HD;

template <int LO, int HI, int PM = 0>
__device__ __forceinline__ void s_init(float (&s)[32], const uint32_t (&mk)[16], const uint32_t (&b)[16]) {
#pragma unroll
  for (int i = 0; i < 16; i++) {
    if ((i & 7) < LO || (i & 7) >= HI) continue;
    const int o = 4 * (i & 7) + 2 * (i >> 3);
    uint32_t t0, t1;
    asm("{\n.reg .b16 ml, mh, bl, bh;\n.reg .b32 m2, b2;\n"
        "mov.b32 {ml, mh}, %1;\nmov.b32 {bl, bh}, %3;\nmov.b32 m2, {ml, ml};\nmov.b32 b2, {bl, bl};\n"
        "fma.rn.bf16x2 %0, m2, %2, b2;\n}"
        : "=r"(t0)
        : "r"(mk[i]), "r"(0x40DE40DEu), "r"(b[i]));
    asm("fma.rn.bf16x2 %0, %1, %2, %3;" : "=r"(t1) : "r"(mk[i]), "r"(0x40DE40DEu), "r"(b[i]));
    if ((PM >> i) & 1) asm("prmt.b32 %0, %1, 0, 0x1010;" : "=r"(t0) : "r"(t1));
    s[o] = __uint_as_float(t0);
    s[o + 1] = __uint_as_float(t1);
    asm volatile("" : "+f"(s[o]), "+f"(s[o + 1])::"memory");
  }
}
__device__ __forceinline__ uint32_t pack_bias(float lo, float hi) {
  uint32_t l = __float_as_uint(fmaf(lo, SQRT_HD, 0x1p-100f)), h = __float_as_uint(fmaf(hi, SQRT_HD, 0x1p-100f));
  l = (l - (l >> 16) + 0x8000u) >> 16;
  return ((h - l + 0x8000u) & 0xffff0000u) | l;
}
__device__ __forceinline__ void rowmax_i(const float (&s)[32], int& i0, int& i1) {
#define FI(x) __float_as_int(x)
  i0 = max(FI(s[0]), FI(s[1])), i1 = max(FI(s[2]), FI(s[3]));
  int k0 = __vimax3_s32(FI(s[4]), FI(s[5]), FI(s[8])), k1 = __vimax3_s32(FI(s[6]), FI(s[7]), FI(s[10]));
  i0 = __vimax3_s32(i0, FI(s[9]), FI(s[12]));   i1 = __vimax3_s32(i1, FI(s[11]), FI(s[14]));
  k0 = __vimax3_s32(k0, FI(s[13]), FI(s[16]));  k1 = __vimax3_s32(k1, FI(s[15]), FI(s[18]));
  i0 = __vimax3_s32(i0, FI(s[17]), FI(s[20]));  i1 = __vimax3_s32(i1, FI(s[19]), FI(s[22]));
  k0 = __vimax3_s32(k0, FI(s[21]), FI(s[24]));  k1 = __vimax3_s32(k1, FI(s[23]), FI(s[26]));
  i0 = __vimax3_s32(i0, FI(s[25]), FI(s[28]));  i1 = __vimax3_s32(i1, FI(s[27]), FI(s[30]));
  i0 = __vimax3_s32(i0, k0, FI(s[29]));         i1 = __vimax3_s32(i1, k1, FI(s[31]));
#undef FI
}
__device__ __forceinline__ void quadmax_i(int& i0, int& i1, int x) {
  i0 = max(i0, __shfl_xor_sync(0xffffffffu, i0, x));
  i1 = max(i1, __shfl_xor_sync(0xffffffffu, i1, x));
}
__device__ __forceinline__ void rowmax_f(const float (&s)[32], int& i0, int& i1) {
  float m0 = fmaxf(s[0], s[1]), m1 = fmaxf(s[2], s[3]);
#pragma unroll
  for (int j = 1; j < 8; j++) {
    m0 = fmaxf(m0, fmaxf(s[4 * j], s[4 * j + 1]));
    m1 = fmaxf(m1, fmaxf(s[4 * j + 2], s[4 * j + 3]));
  }
  m0 = fmaxf(m0, __shfl_xor_sync(0xffffffffu, m0, 1));
  m1 = fmaxf(m1, __shfl_xor_sync(0xffffffffu, m1, 1));
  m0 = fmaxf(m0, __shfl_xor_sync(0xffffffffu, m0, 2));
  m1 = fmaxf(m1, __shfl_xor_sync(0xffffffffu, m1, 2));
  i0 = __float_as_int(m0), i1 = __float_as_int(m1);
}
template <int LO, int HI>
__device__ __forceinline__ void exp_part(const float (&s)[32], uint32_t (&p)[16], float m0, float m1) {
#pragma unroll
  for (int i = LO; i < HI; i++) {
    float m = (i & 1) ? m1 : m0;
    p[i] = pack_bf16(ex2(fmaf(s[2 * i], SM_C, m)), ex2(fmaf(s[2 * i + 1], SM_C, m)));
    asm volatile("" : "+r"(p[i])::"memory");
  }
}
template <int CH>
__device__ __forceinline__ void exp_chunked(float (&s)[32], uint32_t (&p)[16], float m0, float m1, uint32_t& keep, int never) {
  float t[32];
#pragma unroll
  for (int c = 0; c <= 16 / CH; c++) {
#pragma unroll
    for (int i = 2 * CH * c; i < 2 * CH * (c + 1) && i < 32; i++) {
      t[i] = fmaf(s[i], SM_C, (i & 2) ? m1 : m0);
      asm volatile("" : "+f"(t[i]));
    }
    if (c > 0) {
#pragma unroll
      for (int i = CH * (c - 1); i < CH * c; i++) {
        t[2 * i] = ex2(t[2 * i]), t[2 * i + 1] = ex2(t[2 * i + 1]);
        asm volatile("" : "+f"(t[2 * i]), "+f"(t[2 * i + 1]));
      }
    }
    if (c > 1) {
#pragma unroll
      for (int i = CH * (c - 2); i < CH * (c - 1); i++) {
        p[i] = pack_bf16(t[2 * i], t[2 * i + 1]);
        asm volatile("" : "+r"(p[i]));
      }
    }
    if (c < 16 / CH) sched_fence(keep, never);
  }
#pragma unroll
  for (int i = 16 - CH; i < 16; i++) p[i] = pack_bf16(t[2 * i], t[2 * i + 1]);
  pin(p);
}
#define EXP(s, p, a, b) exp_part<0, 16>(s, p, __int_as_float(a) * -SM_C, __int_as_float(b) * -SM_C)
template <int SUM, int OFF>
__device__ __forceinline__ void normalize(const float (&o)[28], uint32_t (&f)[12]) {
  float r0 = rcp(o[SUM]), r1 = rcp(o[SUM + 2]);
#pragma unroll
  for (int j = 0; j < 12; j++) {
    float r = (j & 1) ? r1 : r0;
    f[j] = pack_bf16(o[OFF + 2 * j] * r, o[OFF + 2 * j + 1] * r);
  }
}

__global__ void __cluster_dims__(2, 1, 1) __launch_bounds__(384, 1)
swin_attn_kernel(const __grid_constant__ Maps maps, const __nv_bfloat16* __restrict__ rpb, const int* __restrict__ rp_idx, int base, int never) {
  extern __shared__ __align__(1024) uint8_t smem_raw[];
  const uint32_t sb = (uint32_t)__cvta_generic_to_shared(smem_raw);
  const int tid = threadIdx.x;
  const int wg = __shfl_sync(0xffffffffu, tid >> 7, 0);
  const int warp = __shfl_sync(0xffffffffu, (tid >> 5) & 3, 0);
  const int lane = tid & 31;
  const int rank = blockIdx.x & 1;
  const int cl = blockIdx.x >> 1;
  const int ncl = gridDim.x >> 1;
  const uint32_t bars = sb + OFF_BAR;
  int extra = NWIN;
  auto read_ticket = [&]() {
    mbar_wait(bars + B_TICK, 0);
    uint32_t t;
    asm volatile("ld.shared.b32 %0, [%1];" : "=r"(t) : "r"(bars + W_TICK) : "memory");
    extra = base + __shfl_sync(0xffffffffu, t, 0);
  };
  auto window = [&](int v) { return v < base ? v : (v < base + ncl ? extra : NWIN); };
  TRP(0);
  CLKP(0);

  if (wg == KV_WG) {
    auto prefetch = [&](int p, int win) {
      if (p < 2) tma5_pf(&maps.x, (((win >> 3) & ~7) + 4 + 4 * rank) & 511, (win * 4 + 2 + 2 * p) & 255);
      else tma5_pf(&maps.mask, 0, 2 * win + rank);
    };
    auto load = [&](int p, int win, int a) {
      if (p < 2)
        tma5_mc(sb + OFF_X + a * STAGE + rank * 12288 + p * 6144, &maps.x, bars + B_XFULL + 8 * a,
                (((win >> 3) & ~7) + 4 + 4 * rank) & 511, (win * 4 + 2 + 2 * p) & 255);
      else tma5_mc(sb + OFF_MASK + a * STAGE + rank * 4096, &maps.mask, bars + B_XFULL + 8 * a, 0, 2 * win + rank);
    };
    auto load_wkv = [&](int b) {
      tma3(sb + OFF_KV + (b < 3 ? b * 12288 : STAGE + (b - 3) * 12288), &maps.wqkv, bars + B_WKV + 8 * (b >> 1), 0,
           (b < 3 ? 6 : 9) + b + 3 * rank);
    };
    if (warp == 3) {
      if (elect()) {
        if ((sb & 0x3FFFF) != SM_BASE) __trap();
#pragma unroll
        for (int a = 0; a < 2; a++) {
          mbar_init(bars + B_XFULL + 8 * a, 1);
          mbar_init(bars + B_XEMPTY + 8 * a, 1);
          mbar_init(bars + B_OFULL + 8 * a, 1);
          mbar_init(bars + B_OEMPTY + 8 * a, 4);
        }
#pragma unroll
        for (int k = 0; k < 6; k++) mbar_init(bars + B_WKV + 8 * k, 1);
        asm volatile("fence.mbarrier_init.release.cluster;" ::: "memory");
        fence_async();
        mbar_expect_tx(bars + B_WKV, 24576);
        load_wkv(0);
        load_wkv(1);
        mbar_expect_tx(bars + B_TICK, 4);
      }
      __syncwarp();
    }
    asm volatile("barrier.cluster.arrive.relaxed.aligned;" ::: "memory");
    asm volatile("setmaxnreg.inc.sync.aligned.u32 216;");
    asm volatile("barrier.cluster.wait.aligned;" ::: "memory");
    TRP(1);
    if (warp == 3 && elect()) {
      mbar_expect_tx(bars + B_XFULL, X_BYTES + M_BYTES);
      for (int p = 0; p < 3; p++) load(p, cl, 0);
      mbar_expect_tx(bars + B_WKV + 8, 24576);
      load_wkv(2);
      load_wkv(3);
      mbar_expect_tx(bars + B_WQ, 36864);
      for (int nb = 0; nb < 3; nb++) tma3(sb + OFF_WQ + nb * 12288, &maps.wqkv, bars + B_WQ, 0, 3 * rank + nb);
      mbar_expect_tx(bars + B_WKV + 16, 24576);
      load_wkv(4);
      load_wkv(5);
      mbar_expect_tx(bars + B_XFULL + 8, X_BYTES + M_BYTES);
      for (int p = 0; p < 3; p++) load(p, cl + ncl, 1);
      mbar_expect_tx(bars + B_WO, 36864);
      tma3(sb + OFF_WO, &maps.wo, bars + B_WO, 96 * rank, 3 * rank);
      for (int nb = 0; nb < 3; nb++)
        asm volatile("cp.async.bulk.tensor.5d.shared::cluster.global.mbarrier::complete_tx::bytes [%0], [%1, {%3, 0, 0, 0, %4}], [%2];" ::"r"(
                         sb + OFF_WO + 18432 + nb * 6144), "l"(&maps.wop), "r"(bars + B_WO), "r"(96 * rank + 32 * nb), "r"(3 * (rank ^ 1))
                     : "memory");
    }
    __syncwarp();
    uint32_t w[3][48];
    auto load_frags = [&](int s) {
      const uint32_t la = sb + OFF_KV + (warp >> 1) * 12288 + (8 * (lane >> 4) + (lane & 7)) * 64 +
                          (((2 * (warp & 1) + ((lane >> 3) & 1)) ^ ((lane & 7) >> 1)) << 4);
      mbar_wait(bars + B_WKV + 8 * s, 0);
      TRP(6 + s);
#pragma unroll
      for (int ks = 0; ks < 12; ks++)
        asm volatile("ldmatrix.sync.aligned.m8n8.x4.trans.shared.b16 {%0,%1,%2,%3}, [%4];"
                     : "=r"(w[s][4 * ks]), "=r"(w[s][4 * ks + 1]), "=r"(w[s][4 * ks + 2]), "=r"(w[s][4 * ks + 3])
                     : "r"(la + s * 24576 + (s == 2 || (s == 1 && warp >= 2) ? STAGE - 36864 : 0) + ks * 1024)
                     : "memory");
    };
    TRP(2);
    load_frags(0);
    TRP(3);
    uint32_t sta[4];
#pragma unroll
    for (int jj = 0; jj < 4; jj++) {
      sta[jj] = sb + OFF_KV + (16 * warp + (lane & 15)) * 128 + (((2 * jj + (lane >> 4)) ^ (lane & 7)) << 4);
      asm volatile("" : "+r"(sta[jj]));
    }
    const uint32_t xe_rem = mapa(bars + B_XEMPTY, rank ^ 1);
    const uint32_t v1off = warp > 0 ? 1024 : 0;

#define SF sched_fence(sta[0], never)
    float acc[32];
    uint32_t pk[16];
    auto store = [&](uint32_t off) {
#pragma unroll
      for (int jj = 0; jj < 4; jj++) stsm4(sta[jj] + off, pk[4 * jj], pk[4 * jj + 1], pk[4 * jj + 2], pk[4 * jj + 3]);
    };
    auto issue = [&](int s, uint32_t xd, bool st, uint32_t off) {
#pragma unroll
      for (int ks = 0; ks < 12; ks++) {
        uint64_t db = mkdesc(xd + (((ks >> 2) * 1024 + (ks & 3) * 32) >> 4), HI_X);
        if (ks == 0) mma_kv_init(acc, w[s][0], w[s][1], w[s][2], w[s][3], db);
        else mma_kv(acc, w[s][4 * ks], w[s][4 * ks + 1], w[s][4 * ks + 2], w[s][4 * ks + 3], db);
        if (ks == ST_AT && st) {
          __syncwarp();
          store(off);
          __syncwarp();
        }
      }
      wg_commit();
    };
    auto convert = [&]() {
      wg_wait<0>();
      pin(acc);
#pragma unroll
      for (int j = 0; j < 16; j++) pk[j] = pack_bf16(acc[2 * j], acc[2 * j + 1]);
      pin(pk);
    };

    mbar_wait(bars + B_XFULL, 0);
    TRP(4);
    wg_fence();
    issue(0, LO_X, false, 0);
    load_frags(1);
    TRP(5);
    [[maybe_unused]] int i = 0;
    int nxt = cl + ncl;
    uint32_t ph = 0;
    uint32_t ticket = 0;
    auto step = [&](auto A) -> bool {
      constexpr int a = decltype(A)::value;
      constexpr uint32_t xd = LO_X + a * (STAGE >> 4);
      if (nxt + ncl >= base && nxt < base) read_ticket();
      const bool more = window(nxt) < NWIN;
      const int wn2 = window(nxt + ncl);
      TR_SETUP(1);
      TR(0);
      convert();
      TR(1);
      wg_fence();
      SF;
      DELAY(4, sta[0]);
      tok_wait<T2>();
      TR(2);
      issue(1, xd, true, a * STAGE);
      tok_pass<T3>();
      TR(3);
      if (warp < 3 && wn2 < NWIN && elect()) prefetch(warp, wn2);
      __syncwarp();
      TR(4);
      convert();
      store(a * STAGE + 8192);
      fence_async();
      const bool first = a == 0 && nxt == cl + ncl;
      if (first) {
        load_frags(2);
        asm volatile("bar.sync %0, 128;" ::"n"((int)BAR_STAGE) : "memory");
        asm volatile("st.shared.v4.b32 [%0], {%1,%1,%1,%1};" ::"r"(sb + OFF_KV + (warp >> 1) * STAGE + 144 * 128 + (tid & 63) * 16), "r"(0x3F803F80u) : "memory");
      }
      TR(5);
      DELAY(7, sta[0]);
      wg_fence();
      tok_wait<T5>();
      TR(6);
      issue(2, xd, false, 0);
      tok_pass<T6>();
      if (!more) {
        convert();
        store(a * STAGE + 16384 + v1off);
        fence_async();
        return false;
      }
      { WS_BEGIN; mbar_wait(bars + B_XFULL + 8 * (a ^ 1), a ? ph ^ 1 : ph); WS_END(0); WS_END(8 + i); }
      TR(7);
      convert();
      TR(8);
      wg_fence();
      SF;
      DELAY(2, sta[0]);
      tok_wait<T0>();
      TR(9);
      if (tid == KV_WG * 128) mbar_arrive_cluster(xe_rem + 8 * a);
      issue(0, LO_X + (a ^ 1) * (STAGE >> 4), true, a * STAGE + 16384 + v1off);
      tok_pass<T1>();
      TR(10);
      fence_async();
      nxt += ncl;
      if (wn2 < NWIN) {
        { WS_BEGIN; mbar_wait(bars + B_XEMPTY + 8 * a, ph); WS_END(1); }
        if (elect()) {
          if (warp < 3) {
            load(warp, wn2, a);
          } else {
            mbar_expect_tx(bars + B_XFULL + 8 * a, X_BYTES + M_BYTES);
            if (rank == 0 && nxt + 3 * ncl >= base) {
              if (nxt + 2 * ncl < base) {
                asm volatile("atom.global.inc.u32 %0, [%1], %2;" : "=r"(ticket) : "l"(&g_ticket), "r"(ncl - 1) : "memory");
              } else if (nxt + ncl < base) {
#pragma unroll
                for (int r = 0; r < 2; r++)
                  asm volatile("st.async.shared::cluster.mbarrier::complete_tx::bytes.b32 [%0], %1, [%2];" ::"r"(mapa(bars + W_TICK, r)),
                               "r"(ticket), "r"(mapa(bars + B_TICK, r))
                               : "memory");
              }
            }
          }
        }
        __syncwarp();
      }
      i++;
      return true;
    };
    while (step(IC<0>{}) && step(IC<1>{})) ph ^= 1;
    tok_wait<T0>();
    tok_pass<T1>();
    tok_wait<T2>();
    tok_pass<T3>();
    tok_wait<T5>();
  } else {
    const int a = wg - (KV_WG == 0 ? 1 : 0);
    const int g = lane >> 2, q = lane & 3;
    const uint32_t bar = bars + 8 * a;
    asm volatile("barrier.cluster.arrive.relaxed.aligned;" ::: "memory");
    if (a == 0) {
      tok_pass<T2>();
      tok_pass<T5>();
    }
    asm volatile("setmaxnreg.dec.sync.aligned.u32 144;");
    uint32_t braw[32];
    {
      const int ty = 4 * (warp >> 1) + (g >> 1), tx = 4 * (warp & 1) + (g & 1);
      const int* ip = rp_idx + (ty * 8 + tx) * 64 + 8 * q;
#pragma unroll
      for (int c = 0; c < 8; c++)
        asm volatile("ld.global.nc.v4.b32 {%0,%1,%2,%3}, [%4];"
                     : "=r"(braw[4 * c]), "=r"(braw[4 * c + 1]), "=r"(braw[4 * c + 2]), "=r"(braw[4 * c + 3])
                     : "l"(ip + (c >> 2) * 128 + ((c >> 1) & 1) * 32 + (c & 1) * 4));
      const int e = a * 128 + (tid & 127);
      if (e < 225) {
        uint32_t v = __ldg(reinterpret_cast<const uint32_t*>(rpb) + e * 2 + rank);
        asm volatile("st.shared.b32 [%0], %1;" ::"r"(sb + OFF_RPB + e * 4), "r"(v) : "memory");
      }
      tok_wait<BAR_BIAS>();
#pragma unroll
      for (int j = 0; j < 32; j++)
        asm volatile("ld.shared.b32 %0, [%1];" : "=r"(braw[j]) : "r"(sb + OFF_RPB + braw[j] * 4) : "memory");
    }
    TRP(1);
    asm volatile("barrier.cluster.wait.aligned;" ::: "memory");
    TRP(2);

    const int mrow = 16 * warp + (g >> 1) + 4 * (g & 1);
#undef SF
#define SF sched_fence(mk_addr, never)
    uint32_t mk_addr = sb + OFF_MASK + a * STAGE + mrow * 128 + ((q ^ (mrow & 7)) << 4);
    const uint32_t ostage = sb + OFF_OIN + a * STAGE + warp * 3072;
    const uint32_t ost = ostage + ((lane >> 3) & 1) * 1536 + (lane & 7) * 64 + (((lane >> 4) ^ ((lane & 7) >> 1)) << 4);
    const uint32_t oin_rem = mapa(ostage + g * 64 + ((q ^ (g >> 1)) << 4), rank ^ 1);
    const uint32_t bar_rem = mapa(bar, rank ^ 1);

    auto store_out = [&](int win) {
      fence_async();
      __syncwarp();
      if (win >= 0 && elect()) {
        int yy = (((win >> 3) & ~7) + 4 + 4 * (warp >> 1)) & 511;
        int xh = (win * 4 + 2 + 2 * (warp & 1)) & 255;
        asm volatile("cp.async.bulk.tensor.5d.global.shared::cta.bulk_group [%0, {0, 0, %2, %3, %4}], [%1];" ::"l"(&maps.out), "r"(ostage),
                     "r"(yy), "r"(3 * rank), "r"(xh)
                     : "memory");
        asm volatile("cp.async.bulk.commit_group;" ::: "memory");
      }
      __syncwarp();
    };
    auto release_oin = [&]() {
      if (elect()) {
        { WS_BEGIN; asm volatile("cp.async.bulk.wait_group.read 0;" ::: "memory"); WS_END(4); }
        if (warp == 0) mbar_expect_tx(bar + B_OFULL, O_BYTES);
        mbar_arrive_cluster(bar_rem + B_OEMPTY);
      }
      __syncwarp();
    };
    float qa[48];
    uint32_t bias0[16], bias1[16];
    uint32_t mk[16];
    auto load_mask = [&](uint32_t z) {
#pragma unroll
      for (int c = 0; c < 4; c++)
        lds128((c & 1 ? mk_addr ^ (64 + z) : mk_addr) + (c >> 1) * 1024, mk[4 * c], mk[4 * c + 1], mk[4 * c + 2], mk[4 * c + 3]);
    };
    auto pre_init = [&]() {
      SF;
#pragma unroll
      for (int j = 0; j < 16; j++) asm("max.NaN.bf16x2 %0, %0, %1;" : "+r"(mk[j]) : "r"(0xFD80FD80u));
      pin(mk);
    };
    auto issue_q = [&](uint32_t ua, bool tok, int win) {
#pragma unroll
      for (int ks = 0; ks < 12; ks++) {
        if (ks == Q_SPLIT && tok) {
          tok_pass<T4>();
          if (STORE_AT == 1) store_out(win);
          tok_wait<T7>();
          if (Q_SPLIT > 0) wg_fence();
        }
        uint64_t da = mkdesc(ua + LO_X + (((ks >> 2) * 1024 + (ks & 3) * 32) >> 4), HI_X);
        uint64_t db = mkdesc(LO_WQ + ks * 64, HI_W);
        if (ks == 0) mma_q_init(qa, da, db);
        else mma_q(qa, da, db);
      }
      wg_commit();
      if (tok) tok_pass<T5>();
    };
#pragma unroll
    for (int j = 0; j < 16; j++) {
      const uint32_t b0 = braw[2 * j], b1 = braw[2 * j + 1];
      bias0[j] = pack_bias(__uint_as_float(b0 << 16), __uint_as_float(b1 << 16));
      bias1[j] = pack_bias(__uint_as_float(b0 & 0xffff0000u), __uint_as_float(b1 & 0xffff0000u));
    }
    pin(bias0);
    pin(bias1);
    SF;
    TRP(5);
    if (a == 0) {
      mbar_wait(bars + B_XFULL, 0);
    } else {
      tok_wait<T1>();
      tok_pass<T2>();
    }
    load_mask(0);
    mbar_wait(bars + B_WQ, 0);
    TRP(3);
    wg_fence();
    if (a == 1) tok_wait<T3>();
    issue_q(a * (STAGE >> 4), false, 0);
    if (a == 0) {
      tok_wait<T3>();
    } else {
      tok_pass<T4>();
      tok_pass<T5>();
      tok_wait<T7>();
    }
    TRP(4);
    pre_init();
    uint32_t ph = 0;
    [[maybe_unused]] int i = a;
    int win = cl + a * ncl;
    for (;; win += 2 * ncl, ph ^= 1, i += 2) {
      TR_SETUP(0);
      TR(0);
      const uint32_t ua = a * (STAGE >> 4) + (win >> 20);
      const uint32_t kd = ua + LO_KV;
      float s0[32], s1[32];
      s_init<PRE_T, 8>(s0, mk, bias0);
      if (PRE_T < 8) SF;
      TR(1);
      wg_wait<0>();
      pin(qa);
      TR(2);
      uint32_t q0[12], q1[12];
#pragma unroll
      for (int j = 0; j < 12; j++) q0[j] = pack_bf16(qa[2 * j], qa[2 * j + 1]);
#pragma unroll
      for (int j = 0; j < 12; j++) q1[j] = pack_bf16(qa[24 + 2 * j], qa[25 + 2 * j]);
      pin(q0);
      pin(q1);
      s_init<0, PRE_T, PM0>(s0, mk, bias0);
      s_init<S1_LATE, 8, PM1>(s1, mk, bias1);
      pin(s0);
      if (S1_LATE > 0) SF;
      TR(3);
      DELAY(1, mk_addr);
      wg_fence();
      tok_wait<T6>();
      TR(4);
#pragma unroll
      for (int ks = 0; ks < 3; ks++)
        mma_s(s0, q0[4 * ks], q0[4 * ks + 1], q0[4 * ks + 2], q0[4 * ks + 3], mkdesc(kd + ks * 128, HI_KV));
      wg_commit();
      if (S1_LATE > 0) {
        SF;
        s_init<0, S1_LATE>(s1, mk, bias1);
        wg_fence();
      }
      pin(s1);
#pragma unroll
      for (int ks = 0; ks < 3; ks++)
        mma_s(s1, q1[4 * ks], q1[4 * ks + 1], q1[4 * ks + 2], q1[4 * ks + 3], mkdesc(kd + (3 + ks) * 128, HI_KV));
      wg_commit();
      tok_pass<T0>();
      if (STORE_AT == 0) store_out(win - 2 * ncl);
      else release_oin();
      int x0, x1, y0, y1;
      uint32_t p0[16], p1[16];
      wg_wait<1>();
      pin(s0);
      pin(q0);
      TR(5);
      rowmax_i(s0, x0, x1);
      quadmax_i(x0, x1, 1);
      wg_wait<0>();
      pin(s1);
      pin(q1);
      rowmax_i(s1, y0, y1);
      quadmax_i(x0, x1, 2);
      quadmax_i(y0, y1, 1);
      quadmax_i(y0, y1, 2);
      if (__builtin_expect(__any_sync(0xffffffffu, (x0 | x1 | y0 | y1) < 0), 0)) {
        rowmax_f(s0, x0, x1);
        rowmax_f(s1, y0, y1);
      }
      EXP(s0, p0, x0, x1);
      TR(6);
      if (STORE_AT == 0) {
        SF;
        release_oin();
        SF;
      }
      EXP(s1, p1, y0, y1);
      TR(7);
      float o0[28], o1[28];
      wg_fence();
      SF;
      DELAY(6, mk_addr);
      tok_wait<T4>();
      TR(8);
#pragma unroll
      for (int ks = 0; ks < 4; ks++) {
        uint64_t db = mkdesc(kd + ((96 * 128 + ks * 32) >> 4), HI_KV);
        if (ks == 0) mma_p_init(o0, p0[0], p0[1], p0[2], p0[3], db);
        else mma_p(o0, p0[4 * ks], p0[4 * ks + 1], p0[4 * ks + 2], p0[4 * ks + 3], db);
      }
      wg_commit();
#pragma unroll
      for (int ks = 0; ks < 4; ks++) {
        uint64_t db = mkdesc(kd + ((144 * 128 + ks * 32) >> 4), HI_KV);
        if (ks == 0) mma_p_init(o1, p1[0], p1[1], p1[2], p1[3], db);
        else mma_p(o1, p1[4 * ks], p1[4 * ks + 1], p1[4 * ks + 2], p1[4 * ks + 3], db);
      }
      wg_commit();
      tok_pass<T7>();
      { WS_BEGIN; mbar_wait(bar + B_OEMPTY, ph); WS_END(2); }
      uint32_t f0[12], f1[12];
      wg_wait<1>();
      pin(o0);
      pin(p0);
      normalize<24, 0>(o0, f0);
      st_async<0>(oin_rem, bar_rem + B_OFULL, f0[0], f0[2], f0[4], f0[6]);
      st_async<1536>(oin_rem, bar_rem + B_OFULL, f0[1], f0[3], f0[5], f0[7]);
      wg_wait<0>();
      pin(o1);
      pin(p1);
      TR(9);
      DELAY(8, mk_addr);
      normalize<0, 4>(o1, f1);
      st_async<512>(oin_rem, bar_rem + B_OFULL, f0[8], f0[10], f1[0], f1[2]);
      st_async<2048>(oin_rem, bar_rem + B_OFULL, f0[9], f0[11], f1[1], f1[3]);
      st_async<1024>(oin_rem, bar_rem + B_OFULL, f1[4], f1[6], f1[8], f1[10]);
      st_async<2560>(oin_rem, bar_rem + B_OFULL, f1[5], f1[7], f1[9], f1[11]);
      pin(f0);
      pin(f1);
      float (&oa)[48] = qa;
      bool last = false;
      bool fin = false;
      if ((unsigned)(win - 2 * ncl) >= (unsigned)(base - 4 * ncl)) {
        if (win < 2 * ncl) {
          mbar_wait(bars + B_WO, 0);
        } else {
          read_ticket();
          last = window(win + ncl) >= NWIN;
          fin = window(win + 2 * ncl) >= NWIN;
        }
      }
      TR(10);
      if (!last) tok_wait<T1>();
      SF;
#pragma unroll
      for (int j = 8; j < 12; j++) f0[j] += never;
#pragma unroll
      for (int j = 0; j < 12; j++) f1[j] += never;
      pin(f0);
      pin(f1);
      DELAY(3, mk_addr);
      wg_fence();
      TR(11);
#pragma unroll
      for (int ks = 0; ks < 3; ks++) {
        uint64_t db = mkdesc(LO_WO + ks * 64, HI_W);
        if (ks == 0) mma_o_init(oa, f0[0], f0[1], f0[2], f0[3], db);
        else mma_o(oa, f0[4 * ks], f0[4 * ks + 1], f0[4 * ks + 2], f0[4 * ks + 3], db);
      }
#pragma unroll
      for (int ks = 0; ks < 3; ks++)
        mma_o(oa, f1[4 * ks], f1[4 * ks + 1], f1[4 * ks + 2], f1[4 * ks + 3], mkdesc(LO_WO + (3 + ks) * 64, HI_W));
      { WS_BEGIN; mbar_wait(bar + B_OFULL, ph); WS_END(3); }
      asm volatile("fence.proxy.async::generic.acquire.sync_restrict::shared::cluster.cluster;" ::: "memory");
      DELAY(10, mk_addr);
      wg_fence();
#pragma unroll
      for (int ks = 0; ks < 6; ks++)
        mma_q(oa, mkdesc(ua + LO_O + (((ks >> 1) * 512 + (ks & 1) * 32) >> 4), HI_O), mkdesc(LO_WO + (18432 >> 4) + ks * 64, HI_W));
      wg_commit();
      if (!last) tok_pass<T2>();
      load_mask(win >> 20);
      wg_wait<0>();
      pin(oa);
      pin(f0);
      pin(f1);
      TR(12);
#pragma unroll
      for (int jj = 0; jj < 6; jj++)
        stsm4((jj & 1 ? ost ^ (32 + (win >> 20)) : ost) + (jj >> 1) * 512, pack_bf16(oa[8 * jj], oa[8 * jj + 1]), pack_bf16(oa[8 * jj + 2], oa[8 * jj + 3]),
              pack_bf16(oa[8 * jj + 4], oa[8 * jj + 5]), pack_bf16(oa[8 * jj + 6], oa[8 * jj + 7]));
      if (fin) {
        if (!last) {
          tok_wait<T3>();
          tok_pass<T4>();
          tok_pass<T5>();
          tok_wait<T7>();
        }
        break;
      }
      DELAY(5, mk_addr);
      wg_fence();
      tok_wait<T3>();
      TR(13);
      issue_q(ua, true, win);
      TR(14);
      pre_init();
    }
    store_out(window(win));
    asm volatile("cp.async.bulk.wait_group 0;" ::: "memory");
    __syncwarp();
  }
  asm volatile("barrier.cluster.arrive.relaxed.aligned;" ::: "memory");
  asm volatile("barrier.cluster.wait.aligned;" ::: "memory");
  CLKP(1);
}

typedef CUresult (*EncodeFn)(CUtensorMap*, CUtensorMapDataType, cuuint32_t, void*, const cuuint64_t*, const cuuint64_t*,
                             const cuuint32_t*, const cuuint32_t*, CUtensorMapInterleave, CUtensorMapSwizzle,
                             CUtensorMapL2promotion, CUtensorMapFloatOOBfill);

void encode_map(EncodeFn encode, CUtensorMap* m, void* p, int rank, const cuuint64_t* dim, const cuuint64_t* str,
                const cuuint32_t* box, CUtensorMapSwizzle sw) {
  const cuuint32_t es[5] = {1, 1, 1, 1, 1};
  CUresult r = encode(m, CU_TENSOR_MAP_DATA_TYPE_BFLOAT16, rank, p, dim, str, box, es, CU_TENSOR_MAP_INTERLEAVE_NONE, sw,
                      L2PROMO, CU_TENSOR_MAP_FLOAT_OOB_FILL_NONE);
  if (r != CUDA_SUCCESS) fprintf(stderr, "tensor map encode failed: %d\n", (int)r);
}

}

extern "C" void kernel_launch(void* const* d_in, const int* in_sizes, int n_in, void* d_out, int out_size) {
  static EncodeFn encode = nullptr;
  static int grid = 0;
  if (!encode) {
    cudaDriverEntryPointQueryResult qr;
    void* fn = nullptr;
    cudaGetDriverEntryPoint("cuTensorMapEncodeTiled", &fn, cudaEnableDefault, &qr);
    encode = (EncodeFn)fn;
    cudaFuncSetAttribute(swin_attn_kernel, cudaFuncAttributeMaxDynamicSharedMemorySize, SMEM_BYTES);
    cudaLaunchConfig_t cfg = {};
    cfg.gridDim = dim3(132);
    cfg.blockDim = dim3(384);
    cfg.dynamicSmemBytes = SMEM_BYTES;
    cudaLaunchAttribute at;
    at.id = cudaLaunchAttributeClusterDimension;
    at.val.clusterDim.x = 2;
    at.val.clusterDim.y = 1;
    at.val.clusterDim.z = 1;
    cfg.attrs = &at;
    cfg.numAttrs = 1;
    int ncl = 0;
    if (cudaOccupancyMaxActiveClusters(&ncl, swin_attn_kernel, &cfg) != cudaSuccess || ncl < 1) {
      (void)cudaGetLastError();
      ncl = 66;
    }
    if (ncl > 256) ncl = 256;
    grid = 2 * ncl;
  }
  Maps maps;
  {
    const cuuint64_t dim[5] = {64, 2, 512, 3, 256}, str[4] = {384, 512 * 384, 128, 768};
    const cuuint32_t box[5] = {64, 2, 4, 3, 2};
    encode_map(encode, &maps.x, d_in[0], 5, dim, str, box, CU_TENSOR_MAP_SWIZZLE_128B);
  }
  {
    const cuuint64_t dim[5] = {64, 4, 2, 4, 8192}, str[4] = {1024, 128, 256, 4096};
    const cuuint32_t box[5] = {64, 4, 2, 4, 1};
    encode_map(encode, &maps.mask, d_in[5], 5, dim, str, box, CU_TENSOR_MAP_SWIZZLE_128B);
  }
  {
    const cuuint64_t dim[5] = {32, 2, 512, 6, 256}, str[4] = {384, 512 * 384, 64, 768};
    const cuuint32_t box[5] = {32, 2, 4, 3, 2};
    encode_map(encode, &maps.out, d_out, 5, dim, str, box, CU_TENSOR_MAP_SWIZZLE_64B);
  }
  {
    const cuuint64_t dim[3] = {32, 192, 18}, str[2] = {576 * 2, 64};
    const cuuint32_t box[3] = {32, 192, 1};
    encode_map(encode, &maps.wqkv, d_in[1], 3, dim, str, box, CU_TENSOR_MAP_SWIZZLE_64B);
    const cuuint64_t dim2[3] = {32, 192, 6}, str2[2] = {192 * 2, 64};
    const cuuint32_t box2[3] = {32, 96, 3};
    encode_map(encode, &maps.wo, d_in[2], 3, dim2, str2, box2, CU_TENSOR_MAP_SWIZZLE_64B);
    const cuuint64_t dim3_[5] = {192, 2, 4, 4, 6}, str3[4] = {384, 8 * 384, 2 * 384, 32 * 384};
    const cuuint32_t box3[5] = {32, 2, 4, 4, 3};
    encode_map(encode, &maps.wop, d_in[2], 5, dim3_, str3, box3, CU_TENSOR_MAP_SWIZZLE_64B);
  }
  swin_attn_kernel<<<grid, 384, SMEM_BYTES>>>(maps, (const __nv_bfloat16*)d_in[3], (const int*)d_in[4], NWIN / (grid / 2) * (grid / 2), 0);
}
```

```cpp
#include <cuda_runtime.h>
#include <cuda_bf16.h>
#include <cuda.h>
#include <stdint.h>
#include <stdio.h>

namespace {

constexpr int NWIN = 4096;
#define KV_WG 0
#define L2PROMO CU_TENSOR_MAP_L2_PROMOTION_L2_128B
#define Q_SPLIT 4
#define STORE_AT 1
#define S1_LATE 0
#define PM0 0
#define PM1 0
#define SM_MODE 0
#define EXP_CH 4
#define ORDER 0x01324
#define FSUM 0
#define ST_AT 3
#define PRE_T 8

constexpr uint32_t SM_BASE  = 1024;
constexpr uint32_t OFF_WQ   = 0;
constexpr uint32_t OFF_WO   = 36864;
constexpr uint32_t STAGE    = 70656;
constexpr uint32_t OFF_X    = 73728;
constexpr uint32_t X_BYTES  = 24576;
constexpr uint32_t OFF_MASK = OFF_X + X_BYTES;
constexpr uint32_t M_BYTES  = 8192;
constexpr uint32_t OFF_KV   = OFF_MASK + M_BYTES;
constexpr uint32_t OFF_OIN  = OFF_KV + 25600;
constexpr uint32_t O_BYTES  = 12288;
constexpr uint32_t OFF_BAR  = 215040;
constexpr uint32_t OFF_RPB  = OFF_BAR + 1024;
constexpr uint32_t SMEM_BYTES = OFF_RPB + 1024;
constexpr uint32_t B_XFULL = 0, B_XEMPTY = 16, B_OFULL = 32, B_OEMPTY = 48, B_WKV = 64  , B_WQ = 88, B_WO = 96,
                   B_TICK = 104, W_TICK = 112;
enum { T0 = 1, T1, T2, T3, T4, T5, T6, T7, BAR_BIAS, BAR_STAGE };

__device__ unsigned int g_ticket;

template <int V> struct IC { static constexpr int value = V; };
struct Maps { CUtensorMap x, mask, out, wqkv, wo, wop; };

__device__ __forceinline__ void mma_q_init(float (&d)[48], uint64_t descA, uint64_t descB) {
  asm volatile("wgmma.mma_async.sync.aligned.m64n96k16.f32.bf16.bf16 {%0, %1, %2, %3, %4, %5, %6, %7, %8, %9, %10, %11, %12, %13, %14, %15, %16, %17, %18, %19, %20, %21, %22, %23, %24, %25, %26, %27, %28, %29, %30, %31, %32, %33, %34, %35, %36, %37, %38, %39, %40, %41, %42, %43, %44, %45, %46, %47}, "
    "%48, %49, 0, 1, 1, 0, 1;"
    : "+f"(d[0]), "+f"(d[1]), "+f"(d[2]), "+f"(d[3]), "+f"(d[4]), "+f"(d[5]), "+f"(d[6]), "+f"(d[7]), "+f"(d[8]), "+f"(d[9]), "+f"(d[10]), "+f"(d[11]), "+f"(d[12]), "+f"(d[13]), "+f"(d[14]), "+f"(d[15]), "+f"(d[16]), "+f"(d[17]), "+f"(d[18]), "+f"(d[19]), "+f"(d[20]), "+f"(d[21]), "+f"(d[22]), "+f"(d[23]), "+f"(d[24]), "+f"(d[25]), "+f"(d[26]), "+f"(d[27]), "+f"(d[28]), "+f"(d[29]), "+f"(d[30]), "+f"(d[31]), "+f"(d[32]), "+f"(d[33]), "+f"(d[34]), "+f"(d[35]), "+f"(d[36]), "+f"(d[37]), "+f"(d[38]), "+f"(d[39]), "+f"(d[40]), "+f"(d[41]), "+f"(d[42]), "+f"(d[43]), "+f"(d[44]), "+f"(d[45]), "+f"(d[46]), "+f"(d[47])
    : "l"(descA), "l"(descB));
}
__device__ __forceinline__ void mma_q(float (&d)[48], uint64_t descA, uint64_t descB) {
  asm volatile("wgmma.mma_async.sync.aligned.m64n96k16.f32.bf16.bf16 {%0, %1, %2, %3, %4, %5, %6, %7, %8, %9, %10, %11, %12, %13, %14, %15, %16, %17, %18, %19, %20, %21, %22, %23, %24, %25, %26, %27, %28, %29, %30, %31, %32, %33, %34, %35, %36, %37, %38, %39, %40, %41, %42, %43, %44, %45, %46, %47}, "
    "%48, %49, 1, 1, 1, 0, 1;"
    : "+f"(d[0]), "+f"(d[1]), "+f"(d[2]), "+f"(d[3]), "+f"(d[4]), "+f"(d[5]), "+f"(d[6]), "+f"(d[7]), "+f"(d[8]), "+f"(d[9]), "+f"(d[10]), "+f"(d[11]), "+f"(d[12]), "+f"(d[13]), "+f"(d[14]), "+f"(d[15]), "+f"(d[16]), "+f"(d[17]), "+f"(d[18]), "+f"(d[19]), "+f"(d[20]), "+f"(d[21]), "+f"(d[22]), "+f"(d[23]), "+f"(d[24]), "+f"(d[25]), "+f"(d[26]), "+f"(d[27]), "+f"(d[28]), "+f"(d[29]), "+f"(d[30]), "+f"(d[31]), "+f"(d[32]), "+f"(d[33]), "+f"(d[34]), "+f"(d[35]), "+f"(d[36]), "+f"(d[37]), "+f"(d[38]), "+f"(d[39]), "+f"(d[40]), "+f"(d[41]), "+f"(d[42]), "+f"(d[43]), "+f"(d[44]), "+f"(d[45]), "+f"(d[46]), "+f"(d[47])
    : "l"(descA), "l"(descB));
}
__device__ __forceinline__ void mma_kv_init(float (&d)[32], uint32_t a0, uint32_t a1, uint32_t a2, uint32_t a3, uint64_t descB) {
  asm volatile("wgmma.mma_async.sync.aligned.m64n64k16.f32.bf16.bf16 {%0, %1, %2, %3, %4, %5, %6, %7, %8, %9, %10, %11, %12, %13, %14, %15, %16, %17, %18, %19, %20, %21, %22, %23, %24, %25, %26, %27, %28, %29, %30, %31}, "
    "{%32, %33, %34, %35}, %36, 0, 1, 1, 0;"
    : "+f"(d[0]), "+f"(d[1]), "+f"(d[2]), "+f"(d[3]), "+f"(d[4]), "+f"(d[5]), "+f"(d[6]), "+f"(d[7]), "+f"(d[8]), "+f"(d[9]), "+f"(d[10]), "+f"(d[11]), "+f"(d[12]), "+f"(d[13]), "+f"(d[14]), "+f"(d[15]), "+f"(d[16]), "+f"(d[17]), "+f"(d[18]), "+f"(d[19]), "+f"(d[20]), "+f"(d[21]), "+f"(d[22]), "+f"(d[23]), "+f"(d[24]), "+f"(d[25]), "+f"(d[26]), "+f"(d[27]), "+f"(d[28]), "+f"(d[29]), "+f"(d[30]), "+f"(d[31])
    : "r"(a0), "r"(a1), "r"(a2), "r"(a3), "l"(descB));
}
__device__ __forceinline__ void mma_kv(float (&d)[32], uint32_t a0, uint32_t a1, uint32_t a2, uint32_t a3, uint64_t descB) {
  asm volatile("wgmma.mma_async.sync.aligned.m64n64k16.f32.bf16.bf16 {%0, %1, %2, %3, %4, %5, %6, %7, %8, %9, %10, %11, %12, %13, %14, %15, %16, %17, %18, %19, %20, %21, %22, %23, %24, %25, %26, %27, %28, %29, %30, %31}, "
    "{%32, %33, %34, %35}, %36, 1, 1, 1, 0;"
    : "+f"(d[0]), "+f"(d[1]), "+f"(d[2]), "+f"(d[3]), "+f"(d[4]), "+f"(d[5]), "+f"(d[6]), "+f"(d[7]), "+f"(d[8]), "+f"(d[9]), "+f"(d[10]), "+f"(d[11]), "+f"(d[12]), "+f"(d[13]), "+f"(d[14]), "+f"(d[15]), "+f"(d[16]), "+f"(d[17]), "+f"(d[18]), "+f"(d[19]), "+f"(d[20]), "+f"(d[21]), "+f"(d[22]), "+f"(d[23]), "+f"(d[24]), "+f"(d[25]), "+f"(d[26]), "+f"(d[27]), "+f"(d[28]), "+f"(d[29]), "+f"(d[30]), "+f"(d[31])
    : "r"(a0), "r"(a1), "r"(a2), "r"(a3), "l"(descB));
}
__device__ __forceinline__ void mma_s(float (&d)[32], uint32_t a0, uint32_t a1, uint32_t a2, uint32_t a3, uint64_t descB) {
  asm volatile("wgmma.mma_async.sync.aligned.m64n64k16.f32.bf16.bf16 {%0, %1, %2, %3, %4, %5, %6, %7, %8, %9, %10, %11, %12, %13, %14, %15, %16, %17, %18, %19, %20, %21, %22, %23, %24, %25, %26, %27, %28, %29, %30, %31}, "
    "{%32, %33, %34, %35}, %36, 1, 1, 1, 1;"
    : "+f"(d[0]), "+f"(d[1]), "+f"(d[2]), "+f"(d[3]), "+f"(d[4]), "+f"(d[5]), "+f"(d[6]), "+f"(d[7]), "+f"(d[8]), "+f"(d[9]), "+f"(d[10]), "+f"(d[11]), "+f"(d[12]), "+f"(d[13]), "+f"(d[14]), "+f"(d[15]), "+f"(d[16]), "+f"(d[17]), "+f"(d[18]), "+f"(d[19]), "+f"(d[20]), "+f"(d[21]), "+f"(d[22]), "+f"(d[23]), "+f"(d[24]), "+f"(d[25]), "+f"(d[26]), "+f"(d[27]), "+f"(d[28]), "+f"(d[29]), "+f"(d[30]), "+f"(d[31])
    : "r"(a0), "r"(a1), "r"(a2), "r"(a3), "l"(descB));
}
__device__ __forceinline__ void mma_p_init(float (&d)[28], uint32_t a0, uint32_t a1, uint32_t a2, uint32_t a3, uint64_t descB) {
  asm volatile("wgmma.mma_async.sync.aligned.m64n56k16.f32.bf16.bf16 {%0, %1, %2, %3, %4, %5, %6, %7, %8, %9, %10, %11, %12, %13, %14, %15, %16, %17, %18, %19, %20, %21, %22, %23, %24, %25, %26, %27}, "
    "{%28, %29, %30, %31}, %32, 0, 1, 1, 0;"
    : "=f"(d[0]), "=f"(d[1]), "=f"(d[2]), "=f"(d[3]), "=f"(d[4]), "=f"(d[5]), "=f"(d[6]), "=f"(d[7]), "=f"(d[8]), "=f"(d[9]), "=f"(d[10]), "=f"(d[11]), "=f"(d[12]), "=f"(d[13]), "=f"(d[14]), "=f"(d[15]), "=f"(d[16]), "=f"(d[17]), "=f"(d[18]), "=f"(d[19]), "=f"(d[20]), "=f"(d[21]), "=f"(d[22]), "=f"(d[23]), "=f"(d[24]), "=f"(d[25]), "=f"(d[26]), "=f"(d[27])
    : "r"(a0), "r"(a1), "r"(a2), "r"(a3), "l"(descB));
}
__device__ __forceinline__ void mma_p(float (&d)[28], uint32_t a0, uint32_t a1, uint32_t a2, uint32_t a3, uint64_t descB) {
  asm volatile("wgmma.mma_async.sync.aligned.m64n56k16.f32.bf16.bf16 {%0, %1, %2, %3, %4, %5, %6, %7, %8, %9, %10, %11, %12, %13, %14, %15, %16, %17, %18, %19, %20, %21, %22, %23, %24, %25, %26, %27}, "
    "{%28, %29, %30, %31}, %32, 1, 1, 1, 0;"
    : "+f"(d[0]), "+f"(d[1]), "+f"(d[2]), "+f"(d[3]), "+f"(d[4]), "+f"(d[5]), "+f"(d[6]), "+f"(d[7]), "+f"(d[8]), "+f"(d[9]), "+f"(d[10]), "+f"(d[11]), "+f"(d[12]), "+f"(d[13]), "+f"(d[14]), "+f"(d[15]), "+f"(d[16]), "+f"(d[17]), "+f"(d[18]), "+f"(d[19]), "+f"(d[20]), "+f"(d[21]), "+f"(d[22]), "+f"(d[23]), "+f"(d[24]), "+f"(d[25]), "+f"(d[26]), "+f"(d[27])
    : "r"(a0), "r"(a1), "r"(a2), "r"(a3), "l"(descB));
}
__device__ __forceinline__ void mma_p48_init(float (&d)[24], uint32_t a0, uint32_t a1, uint32_t a2, uint32_t a3, uint64_t descB) {
  asm volatile("wgmma.mma_async.sync.aligned.m64n48k16.f32.bf16.bf16 {%0, %1, %2, %3, %4, %5, %6, %7, %8, %9, %10, %11, %12, %13, %14, %15, %16, %17, %18, %19, %20, %21, %22, %23}, "
    "{%24, %25, %26, %27}, %28, 0, 1, 1, 0;"
    : "=f"(d[0]), "=f"(d[1]), "=f"(d[2]), "=f"(d[3]), "=f"(d[4]), "=f"(d[5]), "=f"(d[6]), "=f"(d[7]), "=f"(d[8]), "=f"(d[9]), "=f"(d[10]), "=f"(d[11]), "=f"(d[12]), "=f"(d[13]), "=f"(d[14]), "=f"(d[15]), "=f"(d[16]), "=f"(d[17]), "=f"(d[18]), "=f"(d[19]), "=f"(d[20]), "=f"(d[21]), "=f"(d[22]), "=f"(d[23])
    : "r"(a0), "r"(a1), "r"(a2), "r"(a3), "l"(descB));
}
__device__ __forceinline__ void mma_p48(float (&d)[24], uint32_t a0, uint32_t a1, uint32_t a2, uint32_t a3, uint64_t descB) {
  asm volatile("wgmma.mma_async.sync.aligned.m64n48k16.f32.bf16.bf16 {%0, %1, %2, %3, %4, %5, %6, %7, %8, %9, %10, %11, %12, %13, %14, %15, %16, %17, %18, %19, %20, %21, %22, %23}, "
    "{%24, %25, %26, %27}, %28, 1, 1, 1, 0;"
    : "+f"(d[0]), "+f"(d[1]), "+f"(d[2]), "+f"(d[3]), "+f"(d[4]), "+f"(d[5]), "+f"(d[6]), "+f"(d[7]), "+f"(d[8]), "+f"(d[9]), "+f"(d[10]), "+f"(d[11]), "+f"(d[12]), "+f"(d[13]), "+f"(d[14]), "+f"(d[15]), "+f"(d[16]), "+f"(d[17]), "+f"(d[18]), "+f"(d[19]), "+f"(d[20]), "+f"(d[21]), "+f"(d[22]), "+f"(d[23])
    : "r"(a0), "r"(a1), "r"(a2), "r"(a3), "l"(descB));
}
__device__ __forceinline__ void mma_o_init(float (&d)[48], uint32_t a0, uint32_t a1, uint32_t a2, uint32_t a3, uint64_t descB) {
  asm volatile("wgmma.mma_async.sync.aligned.m64n96k16.f32.bf16.bf16 {%0, %1, %2, %3, %4, %5, %6, %7, %8, %9, %10, %11, %12, %13, %14, %15, %16, %17, %18, %19, %20, %21, %22, %23, %24, %25, %26, %27, %28, %29, %30, %31, %32, %33, %34, %35, %36, %37, %38, %39, %40, %41, %42, %43, %44, %45, %46, %47}, "
    "{%48, %49, %50, %51}, %52, 0, 1, 1, 1;"
    : "=f"(d[0]), "=f"(d[1]), "=f"(d[2]), "=f"(d[3]), "=f"(d[4]), "=f"(d[5]), "=f"(d[6]), "=f"(d[7]), "=f"(d[8]), "=f"(d[9]), "=f"(d[10]), "=f"(d[11]), "=f"(d[12]), "=f"(d[13]), "=f"(d[14]), "=f"(d[15]), "=f"(d[16]), "=f"(d[17]), "=f"(d[18]), "=f"(d[19]), "=f"(d[20]), "=f"(d[21]), "=f"(d[22]), "=f"(d[23]), "=f"(d[24]), "=f"(d[25]), "=f"(d[26]), "=f"(d[27]), "=f"(d[28]), "=f"(d[29]), "=f"(d[30]), "=f"(d[31]), "=f"(d[32]), "=f"(d[33]), "=f"(d[34]), "=f"(d[35]), "=f"(d[36]), "=f"(d[37]), "=f"(d[38]), "=f"(d[39]), "=f"(d[40]), "=f"(d[41]), "=f"(d[42]), "=f"(d[43]), "=f"(d[44]), "=f"(d[45]), "=f"(d[46]), "=f"(d[47])
    : "r"(a0), "r"(a1), "r"(a2), "r"(a3), "l"(descB));
}
__device__ __forceinline__ void mma_o(float (&d)[48], uint32_t a0, uint32_t a1, uint32_t a2, uint32_t a3, uint64_t descB) {
  asm volatile("wgmma.mma_async.sync.aligned.m64n96k16.f32.bf16.bf16 {%0, %1, %2, %3, %4, %5, %6, %7, %8, %9, %10, %11, %12, %13, %14, %15, %16, %17, %18, %19, %20, %21, %22, %23, %24, %25, %26, %27, %28, %29, %30, %31, %32, %33, %34, %35, %36, %37, %38, %39, %40, %41, %42, %43, %44, %45, %46, %47}, "
    "{%48, %49, %50, %51}, %52, 1, 1, 1, 1;"
    : "+f"(d[0]), "+f"(d[1]), "+f"(d[2]), "+f"(d[3]), "+f"(d[4]), "+f"(d[5]), "+f"(d[6]), "+f"(d[7]), "+f"(d[8]), "+f"(d[9]), "+f"(d[10]), "+f"(d[11]), "+f"(d[12]), "+f"(d[13]), "+f"(d[14]), "+f"(d[15]), "+f"(d[16]), "+f"(d[17]), "+f"(d[18]), "+f"(d[19]), "+f"(d[20]), "+f"(d[21]), "+f"(d[22]), "+f"(d[23]), "+f"(d[24]), "+f"(d[25]), "+f"(d[26]), "+f"(d[27]), "+f"(d[28]), "+f"(d[29]), "+f"(d[30]), "+f"(d[31]), "+f"(d[32]), "+f"(d[33]), "+f"(d[34]), "+f"(d[35]), "+f"(d[36]), "+f"(d[37]), "+f"(d[38]), "+f"(d[39]), "+f"(d[40]), "+f"(d[41]), "+f"(d[42]), "+f"(d[43]), "+f"(d[44]), "+f"(d[45]), "+f"(d[46]), "+f"(d[47])
    : "r"(a0), "r"(a1), "r"(a2), "r"(a3), "l"(descB));
}

__device__ __forceinline__ void wg_fence() { asm volatile("wgmma.fence.sync.aligned;" ::: "memory"); }
__device__ __forceinline__ void wg_commit() { asm volatile("wgmma.commit_group.sync.aligned;" ::: "memory"); }
template <int N> __device__ __forceinline__ void wg_wait() { asm volatile("wgmma.wait_group.sync.aligned %0;" ::"n"(N) : "memory"); }
template <int N> __device__ __forceinline__ void pin(float (&d)[N]) {
#pragma unroll
  for (int i = 0; i < N; i++) asm volatile("" : "+f"(d[i])::"memory");
}
template <int N> __device__ __forceinline__ void pin(uint32_t (&d)[N]) {
#pragma unroll
  for (int i = 0; i < N; i++) asm volatile("" : "+r"(d[i])::"memory");
}
__device__ __forceinline__ uint64_t mkdesc(uint32_t lo, uint32_t hi) { return ((uint64_t)hi << 32) | lo; }
[[maybe_unused]] constexpr uint64_t EVICT_FIRST = 0x12F0000000000000ull;
constexpr uint32_t HI_X = (3072 >> 4) | (1u << 30);
constexpr uint32_t HI_KV = (1024 >> 4) | (1u << 30);
constexpr uint32_t HI_W = (512 >> 4) | (2u << 30);
constexpr uint32_t HI_O = (1536 >> 4) | (2u << 30);
constexpr uint32_t LO_O = (1u << 16) + ((SM_BASE + OFF_OIN) >> 4);
constexpr uint32_t LO_WQ = ((12288 >> 4) << 16) + ((SM_BASE + OFF_WQ) >> 4);
constexpr uint32_t LO_WO = ((6144 >> 4) << 16) + ((SM_BASE + OFF_WO) >> 4);
constexpr uint32_t LO_X = (1u << 16) + ((SM_BASE + OFF_X) >> 4);
constexpr uint32_t LO_KV = (1u << 16) + ((SM_BASE + OFF_KV) >> 4);

__device__ __forceinline__ uint32_t pack_bf16(float lo, float hi) {
  uint32_t r;
  asm("cvt.rn.bf16x2.f32 %0, %1, %2;" : "=r"(r) : "f"(hi), "f"(lo));
  return r;
}
__device__ __forceinline__ float ex2(float x) {
  float r;
  asm("ex2.approx.ftz.f32 %0, %1;" : "=f"(r) : "f"(x));
  return r;
}
__device__ __forceinline__ float rcp(float x) {
  float r;
  asm("rcp.approx.ftz.f32 %0, %1;" : "=f"(r) : "f"(x));
  return r;
}
__device__ __forceinline__ bool elect() {
  uint32_t p;
  asm volatile("{\n.reg .pred P;\nelect.sync _|P, 0xffffffff;\nselp.u32 %0, 1, 0, P;\n}" : "=r"(p));
  return p;
}
__device__ __forceinline__ void mbar_init(uint32_t bar, uint32_t cnt) {
  asm volatile("mbarrier.init.shared::cta.b64 [%0], %1;" ::"r"(bar), "r"(cnt) : "memory");
}
__device__ __forceinline__ void mbar_wait(uint32_t bar, uint32_t parity) {
  asm volatile(
      "{\n.reg .pred p;\n.reg .u32 n;\n"
      "mbarrier.try_wait.parity.shared::cta.b64 p, [%0], %1;\n"
      "@p bra DONE;\n"
      "mov.u32 n, 0;\n"
      "LOOP:\n"
      "mbarrier.try_wait.parity.shared::cta.b64 p, [%0], %1;\n"
      "@p bra DONE;\n"
      "add.u32 n, n, 1;\n"
      "setp.lt.u32 p, n, 0x400000;\n"
      "@p bra LOOP;\n"
      "trap;\n"
      "DONE:\n}\n" ::"r"(bar), "r"(parity)
      : "memory");
}
__device__ __forceinline__ void mbar_arrive_cluster(uint32_t bar) {
  asm volatile("mbarrier.arrive.shared::cluster.b64 _, [%0];" ::"r"(bar) : "memory");
}
__device__ __forceinline__ void mbar_expect_tx(uint32_t bar, uint32_t bytes) {
  asm volatile("mbarrier.arrive.expect_tx.shared::cta.b64 _, [%0], %1;" ::"r"(bar), "r"(bytes) : "memory");
}
__device__ __forceinline__ uint32_t mapa(uint32_t addr, uint32_t rank) {
  uint32_t r;
  asm("mapa.shared::cluster.u32 %0, %1, %2;" : "=r"(r) : "r"(addr), "r"(rank));
  return r;
}
__device__ __forceinline__ void sched_fence(uint32_t& keep, int never) {
  asm volatile("{\n.reg .pred p;\nsetp.ne.s32 p, %1, 0;\n@p mov.u32 %0, %clock;\n}" : "+r"(keep) : "r"(never) : "memory");
}
#define DLY 0
#define DELAY(k, keep) do { if (DLY == (k)) { SF; float z_ = __uint_as_float(keep); for (int q_ = 0; q_ < 3; q_++) asm volatile("rcp.approx.ftz.f32 %0, %0;" : "+f"(z_)); \
  keep += __float_as_uint(z_) * never; SF; } } while (0)
template <int ID> __device__ __forceinline__ void tok_wait() { asm volatile("bar.sync %0, 256;" ::"n"(ID) : "memory"); }
template <int ID> __device__ __forceinline__ void tok_pass() { asm volatile("bar.arrive %0, 256;" ::"n"(ID) : "memory"); }
__device__ __forceinline__ void fence_async() { asm volatile("fence.proxy.async.shared::cta;" ::: "memory"); }
__device__ __forceinline__ void stsm4(uint32_t addr, uint32_t r0, uint32_t r1, uint32_t r2, uint32_t r3) {
  asm volatile("stmatrix.sync.aligned.m8n8.x4.shared.b16 [%0], {%1,%2,%3,%4};" ::"r"(addr), "r"(r0), "r"(r1), "r"(r2), "r"(r3) : "memory");
}
__device__ __forceinline__ void lds128(uint32_t addr, uint32_t& r0, uint32_t& r1, uint32_t& r2, uint32_t& r3) {
  asm volatile("ld.shared.v4.b32 {%0,%1,%2,%3}, [%4];" : "=r"(r0), "=r"(r1), "=r"(r2), "=r"(r3) : "r"(addr) : "memory");
}
template <int OFF>
__device__ __forceinline__ void st_async(uint32_t addr, uint32_t bar, uint32_t r0, uint32_t r1, uint32_t r2, uint32_t r3) {
  asm volatile("st.async.shared::cluster.mbarrier::complete_tx::bytes.v4.b32 [%0+%6], {%1,%2,%3,%4}, [%5];" ::"r"(addr), "r"(r0),
               "r"(r1), "r"(r2), "r"(r3), "r"(bar), "n"(OFF)
               : "memory");
}
__device__ __forceinline__ void tma5_mc(uint32_t dst, const CUtensorMap* tm, uint32_t bar, int c2, int c4) {
  asm volatile(
      "cp.async.bulk.tensor.5d.shared::cluster.global.mbarrier::complete_tx::bytes.multicast::cluster.L2::cache_hint "
      "[%0], [%1, {0, 0, %3, 0, %4}], [%2], %5, %6;" ::"r"(dst), "l"(tm), "r"(bar), "r"(c2), "r"(c4), "h"((uint16_t)3), "l"(EVICT_FIRST)
      : "memory");
}
__device__ __forceinline__ void tma5_pf(const CUtensorMap* tm, int c2, int c4) {
  asm volatile("cp.async.bulk.prefetch.tensor.5d.L2.global [%0, {0, 0, %1, 0, %2}];" ::"l"(tm), "r"(c2), "r"(c4) : "memory");
}
__device__ __forceinline__ void tma3(uint32_t dst, const CUtensorMap* tm, uint32_t bar, int c1, int c2) {
  asm volatile("cp.async.bulk.tensor.3d.shared::cluster.global.mbarrier::complete_tx::bytes [%0], [%1, {0, %3, %4}], [%2];" ::"r"(dst),
               "l"(tm), "r"(bar), "r"(c1), "r"(c2)
               : "memory");
}
#define TR_SETUP(kv)
#define TR(k)
#define TRP(k)

#define WS_BEGIN
#define WS_END(k)
#define CLKP(k)

constexpr float SQRT_HD = 6.92820323027551f;
constexpr float SM_C = 1.4426950408889634f / SQRT_HD;

template <int LO, int HI, int PM = 0>
__device__ __forceinline__ void s_init(float (&s)[32], const uint32_t (&mk)[16], const uint32_t (&b)[16]) {
#pragma unroll
  for (int i = 0; i < 16; i++) {
    if ((i & 7) < LO || (i & 7) >= HI) continue;
    const int o = 4 * (i & 7) + 2 * (i >> 3);
    uint32_t t0, t1;
    asm("{\n.reg .b16 ml, mh, bl, bh;\n.reg .b32 m2, b2;\n"
        "mov.b32 {ml, mh}, %1;\nmov.b32 {bl, bh}, %3;\nmov.b32 m2, {ml, ml};\nmov.b32 b2, {bl, bl};\n"
        "fma.rn.bf16x2 %0, m2, %2, b2;\n}"
        : "=r"(t0)
        : "r"(mk[i]), "r"(0x40DE40DEu), "r"(b[i]));
    asm("fma.rn.bf16x2 %0, %1, %2, %3;" : "=r"(t1) : "r"(mk[i]), "r"(0x40DE40DEu), "r"(b[i]));
    if ((PM >> i) & 1) asm("prmt.b32 %0, %1, 0, 0x1010;" : "=r"(t0) : "r"(t1));
    s[o] = __uint_as_float(t0);
    s[o + 1] = __uint_as_float(t1);
    asm volatile("" : "+f"(s[o]), "+f"(s[o + 1])::"memory");
  }
}
__device__ __forceinline__ uint32_t pack_bias(float lo, float hi) {
  uint32_t l = __float_as_uint(fmaf(lo, SQRT_HD, 0x1p-100f)), h = __float_as_uint(fmaf(hi, SQRT_HD, 0x1p-100f));
  l = (l - (l >> 16) + 0x8000u) >> 16;
  return ((h - l + 0x8000u) & 0xffff0000u) | l;
}
__device__ __forceinline__ void rowmax_i(const float (&s)[32], int& i0, int& i1) {
#define FI(x) __float_as_int(x)
  i0 = max(FI(s[0]), FI(s[1])), i1 = max(FI(s[2]), FI(s[3]));
  int k0 = __vimax3_s32(FI(s[4]), FI(s[5]), FI(s[8])), k1 = __vimax3_s32(FI(s[6]), FI(s[7]), FI(s[10]));
  i0 = __vimax3_s32(i0, FI(s[9]), FI(s[12]));   i1 = __vimax3_s32(i1, FI(s[11]), FI(s[14]));
  k0 = __vimax3_s32(k0, FI(s[13]), FI(s[16]));  k1 = __vimax3_s32(k1, FI(s[15]), FI(s[18]));
  i0 = __vimax3_s32(i0, FI(s[17]), FI(s[20]));  i1 = __vimax3_s32(i1, FI(s[19]), FI(s[22]));
  k0 = __vimax3_s32(k0, FI(s[21]), FI(s[24]));  k1 = __vimax3_s32(k1, FI(s[23]), FI(s[26]));
  i0 = __vimax3_s32(i0, FI(s[25]), FI(s[28]));  i1 = __vimax3_s32(i1, FI(s[27]), FI(s[30]));
  i0 = __vimax3_s32(i0, k0, FI(s[29]));         i1 = __vimax3_s32(i1, k1, FI(s[31]));
#undef FI
}
__device__ __forceinline__ void quadmax_i(int& i0, int& i1, int x) {
  i0 = max(i0, __shfl_xor_sync(0xffffffffu, i0, x));
  i1 = max(i1, __shfl_xor_sync(0xffffffffu, i1, x));
}
__device__ __forceinline__ void rowmax_f(const float (&s)[32], int& i0, int& i1) {
  float m0 = fmaxf(s[0], s[1]), m1 = fmaxf(s[2], s[3]);
#pragma unroll
  for (int j = 1; j < 8; j++) {
    m0 = fmaxf(m0, fmaxf(s[4 * j], s[4 * j + 1]));
    m1 = fmaxf(m1, fmaxf(s[4 * j + 2], s[4 * j + 3]));
  }
  m0 = fmaxf(m0, __shfl_xor_sync(0xffffffffu, m0, 1));
  m1 = fmaxf(m1, __shfl_xor_sync(0xffffffffu, m1, 1));
  m0 = fmaxf(m0, __shfl_xor_sync(0xffffffffu, m0, 2));
  m1 = fmaxf(m1, __shfl_xor_sync(0xffffffffu, m1, 2));
  i0 = __float_as_int(m0), i1 = __float_as_int(m1);
}
template <int CH, bool SUM>
__device__ __forceinline__ void exp_chunked(float (&s)[32], uint32_t (&p)[16], float m0, float m1, float& l0, float& l1, uint32_t& keep,
                                            int never) {
  float t[32];
  auto acc = [&](int i) {
    if (!SUM) return;
    float& l = (i & 1) ? l1 : l0;
    l = i < 2 ? t[2 * i] + t[2 * i + 1] : (l + t[2 * i]) + t[2 * i + 1];
    asm volatile("" : "+f"(l));
  };
#pragma unroll
  for (int c = 0; c <= 16 / CH; c++) {
#pragma unroll
    for (int i = 2 * CH * c; i < 2 * CH * (c + 1) && i < 32; i++) {
      t[i] = fmaf(s[i], SM_C, (i & 2) ? m1 : m0);
      asm volatile("" : "+f"(t[i]));
    }
    if (c > 0) {
#pragma unroll
      for (int i = CH * (c - 1); i < CH * c; i++) {
        t[2 * i] = ex2(t[2 * i]), t[2 * i + 1] = ex2(t[2 * i + 1]);
        asm volatile("" : "+f"(t[2 * i]), "+f"(t[2 * i + 1]));
      }
    }
    if (c > 1) {
#pragma unroll
      for (int i = CH * (c - 2); i < CH * (c - 1); i++) {
        p[i] = pack_bf16(t[2 * i], t[2 * i + 1]);
        asm volatile("" : "+r"(p[i]));
        acc(i);
      }
    }
    if (c < 16 / CH) sched_fence(keep, never);
  }
#pragma unroll
  for (int i = 16 - CH; i < 16; i++) {
    p[i] = pack_bf16(t[2 * i], t[2 * i + 1]);
    acc(i);
  }
  pin(p);
}
#define EXP(s, p, a, b, l0, l1, SUM) exp_chunked<EXP_CH, SUM>(s, p, __int_as_float(a) * -SM_C, __int_as_float(b) * -SM_C, l0, l1, mk_addr, never)
template <int N>
__device__ __forceinline__ void issue_p(float (&o)[N], const uint32_t (&p)[16], uint32_t lo) {
#pragma unroll
  for (int ks = 0; ks < 4; ks++) {
    uint64_t db = mkdesc(lo + ks * 2, HI_KV);
    if constexpr (N == 28) {
      if (ks == 0) mma_p_init(o, p[0], p[1], p[2], p[3], db);
      else mma_p(o, p[4 * ks], p[4 * ks + 1], p[4 * ks + 2], p[4 * ks + 3], db);
    } else {
      if (ks == 0) mma_p48_init(o, p[0], p[1], p[2], p[3], db);
      else mma_p48(o, p[4 * ks], p[4 * ks + 1], p[4 * ks + 2], p[4 * ks + 3], db);
    }
  }
  wg_commit();
}
__device__ __forceinline__ void quadsum_rcp(float& l0, float& l1) {
  l0 += __shfl_xor_sync(0xffffffffu, l0, 1), l1 += __shfl_xor_sync(0xffffffffu, l1, 1);
  l0 += __shfl_xor_sync(0xffffffffu, l0, 2), l1 += __shfl_xor_sync(0xffffffffu, l1, 2);
  l0 = rcp(l0), l1 = rcp(l1);
}
template <int OFF, int N>
__device__ __forceinline__ void normalize(const float (&o)[N], uint32_t (&f)[12], float r0, float r1) {
#pragma unroll
  for (int j = 0; j < 12; j++) {
    float r = (j & 1) ? r1 : r0;
    f[j] = pack_bf16(o[OFF + 2 * j] * r, o[OFF + 2 * j + 1] * r);
  }
}

__global__ void __cluster_dims__(2, 1, 1) __launch_bounds__(384, 1)
swin_attn_kernel(const __grid_constant__ Maps maps, const __nv_bfloat16* __restrict__ rpb, const int* __restrict__ rp_idx, int base, int never) {
  extern __shared__ __align__(1024) uint8_t smem_raw[];
  const uint32_t sb = (uint32_t)__cvta_generic_to_shared(smem_raw);
  const int tid = threadIdx.x;
  const int wg = __shfl_sync(0xffffffffu, tid >> 7, 0);
  const int warp = __shfl_sync(0xffffffffu, (tid >> 5) & 3, 0);
  const int lane = tid & 31;
  const int rank = blockIdx.x & 1;
  const int cl = blockIdx.x >> 1;
  const int ncl = gridDim.x >> 1;
  const uint32_t bars = sb + OFF_BAR;
  int extra = NWIN;
  auto read_ticket = [&]() {
    mbar_wait(bars + B_TICK, 0);
    uint32_t t;
    asm volatile("ld.shared.b32 %0, [%1];" : "=r"(t) : "r"(bars + W_TICK) : "memory");
    extra = base + __shfl_sync(0xffffffffu, t, 0);
  };
  auto window = [&](int v) { return v < base ? v : (v < base + ncl ? extra : NWIN); };
  auto prefetch = [&](int p, int win) {
    if (p < 2) tma5_pf(&maps.x, (((win >> 3) & ~7) + 4 + 4 * rank) & 511, (win * 4 + 2 + 2 * p) & 255);
    else tma5_pf(&maps.mask, 0, 2 * win + rank);
  };
  auto load = [&](int p, int win, int a) {
    if (p < 2)
      tma5_mc(sb + OFF_X + a * STAGE + rank * 12288 + p * 6144, &maps.x, bars + B_XFULL + 8 * a,
              (((win >> 3) & ~7) + 4 + 4 * rank) & 511, (win * 4 + 2 + 2 * p) & 255);
    else tma5_mc(sb + OFF_MASK + a * STAGE + rank * 4096, &maps.mask, bars + B_XFULL + 8 * a, 0, 2 * win + rank);
  };
  auto load_wkv = [&](int b) {
    tma3(sb + OFF_KV + (b < 3 ? b * 12288 : STAGE + (b - 3) * 12288), &maps.wqkv, bars + B_WKV + 8 * (b >> 1), 0,
         (b < 3 ? 6 : 9) + b + 3 * rank);
  };
  auto startup_loads = [&]() {
    mbar_expect_tx(bars + B_XFULL, X_BYTES + M_BYTES);
    mbar_expect_tx(bars + B_WKV + 8, 24576);
    mbar_expect_tx(bars + B_WQ, 36864);
    mbar_expect_tx(bars + B_WKV + 16, 24576);
    mbar_expect_tx(bars + B_XFULL + 8, X_BYTES + M_BYTES);
#pragma unroll
    for (int o = 0; o < 5; o++) {
      const int what = (ORDER >> (4 * (4 - o))) & 15;
      if (what == 0) for (int p = 0; p < 3; p++) load(p, cl, 0);
      if (what == 1) { load_wkv(2); load_wkv(3); }
      if (what == 2) { load_wkv(4); load_wkv(5); }
      if (what == 3) for (int nb = 0; nb < 3; nb++) tma3(sb + OFF_WQ + nb * 12288, &maps.wqkv, bars + B_WQ, 0, 3 * rank + nb);
      if (what == 4) for (int p = 0; p < 3; p++) load(p, cl + ncl, 1);
    }
    mbar_expect_tx(bars + B_WO, 36864);
    tma3(sb + OFF_WO, &maps.wo, bars + B_WO, 96 * rank, 3 * rank);
    for (int nb = 0; nb < 3; nb++)
      asm volatile("cp.async.bulk.tensor.5d.shared::cluster.global.mbarrier::complete_tx::bytes [%0], [%1, {%3, 0, 0, 0, %4}], [%2];" ::"r"(
                       sb + OFF_WO + 18432 + nb * 6144), "l"(&maps.wop), "r"(bars + B_WO), "r"(96 * rank + 32 * nb), "r"(3 * (rank ^ 1))
                   : "memory");
  };
  TRP(0);
  CLKP(0);

  if (wg == KV_WG) {
    if (warp == 3) {
      if (elect()) {
        if ((sb & 0x3FFFF) != SM_BASE) __trap();
#pragma unroll
        for (int a = 0; a < 2; a++) {
          mbar_init(bars + B_XFULL + 8 * a, 1);
          mbar_init(bars + B_XEMPTY + 8 * a, 1);
          mbar_init(bars + B_OFULL + 8 * a, 1);
          mbar_init(bars + B_OEMPTY + 8 * a, 4);
        }
#pragma unroll
        for (int k = 0; k < 6; k++) mbar_init(bars + B_WKV + 8 * k, 1);
        asm volatile("fence.mbarrier_init.release.cluster;" ::: "memory");
        fence_async();
        mbar_expect_tx(bars + B_WKV, 24576);
        load_wkv(0);
        load_wkv(1);
        mbar_expect_tx(bars + B_TICK, 4);
      }
      __syncwarp();
    }
    asm volatile("barrier.cluster.arrive.relaxed.aligned;" ::: "memory");
    asm volatile("setmaxnreg.inc.sync.aligned.u32 216;");
    asm volatile("barrier.cluster.wait.aligned;" ::: "memory");
    TRP(1);
    if (warp == 3 && elect()) startup_loads();
    __syncwarp();
    uint32_t w[3][48];
    auto load_frags = [&](int s) {
      const uint32_t la = sb + OFF_KV + (warp >> 1) * 12288 + (8 * (lane >> 4) + (lane & 7)) * 64 +
                          (((2 * (warp & 1) + ((lane >> 3) & 1)) ^ ((lane & 7) >> 1)) << 4);
      mbar_wait(bars + B_WKV + 8 * s, 0);
      TRP(6 + s);
#pragma unroll
      for (int ks = 0; ks < 12; ks++)
        asm volatile("ldmatrix.sync.aligned.m8n8.x4.trans.shared.b16 {%0,%1,%2,%3}, [%4];"
                     : "=r"(w[s][4 * ks]), "=r"(w[s][4 * ks + 1]), "=r"(w[s][4 * ks + 2]), "=r"(w[s][4 * ks + 3])
                     : "r"(la + s * 24576 + (s == 2 || (s == 1 && warp >= 2) ? STAGE - 36864 : 0) + ks * 1024)
                     : "memory");
    };
    TRP(2);
    load_frags(0);
    TRP(3);
    uint32_t sta[4];
#pragma unroll
    for (int jj = 0; jj < 4; jj++) {
      sta[jj] = sb + OFF_KV + (16 * warp + (lane & 15)) * 128 + (((2 * jj + (lane >> 4)) ^ (lane & 7)) << 4);
      asm volatile("" : "+r"(sta[jj]));
    }
    const uint32_t xe_rem = mapa(bars + B_XEMPTY, rank ^ 1);
    const uint32_t v1off = warp > 0 ? 1024 : 0;

#define SF sched_fence(sta[0], never)
    float acc[32];
    uint32_t pk[16];
    auto store = [&](uint32_t off) {
#pragma unroll
      for (int jj = 0; jj < 4; jj++) stsm4(sta[jj] + off, pk[4 * jj], pk[4 * jj + 1], pk[4 * jj + 2], pk[4 * jj + 3]);
    };
    auto issue = [&](int s, uint32_t xd, bool st, uint32_t off) {
#pragma unroll
      for (int ks = 0; ks < 12; ks++) {
        uint64_t db = mkdesc(xd + (((ks >> 2) * 1024 + (ks & 3) * 32) >> 4), HI_X);
        if (ks == 0) mma_kv_init(acc, w[s][0], w[s][1], w[s][2], w[s][3], db);
        else mma_kv(acc, w[s][4 * ks], w[s][4 * ks + 1], w[s][4 * ks + 2], w[s][4 * ks + 3], db);
        if (ks == ST_AT && st) {
          __syncwarp();
          store(off);
          __syncwarp();
        }
      }
      wg_commit();
    };
    auto convert = [&]() {
      wg_wait<0>();
      pin(acc);
#pragma unroll
      for (int j = 0; j < 16; j++) pk[j] = pack_bf16(acc[2 * j], acc[2 * j + 1]);
      pin(pk);
    };

    mbar_wait(bars + B_XFULL, 0);
    TRP(4);
    wg_fence();
    issue(0, LO_X, false, 0);
    load_frags(1);
    TRP(5);
    [[maybe_unused]] int i = 0;
    int nxt = cl + ncl;
    uint32_t ph = 0;
    uint32_t ticket = 0;
    auto step = [&](auto A) -> bool {
      constexpr int a = decltype(A)::value;
      constexpr uint32_t xd = LO_X + a * (STAGE >> 4);
      if (nxt + ncl >= base && nxt < base) read_ticket();
      const bool more = window(nxt) < NWIN;
      const int wn2 = window(nxt + ncl);
      TR_SETUP(1);
      TR(0);
      convert();
      TR(1);
      wg_fence();
      SF;
      DELAY(4, sta[0]);
      tok_wait<T2>();
      TR(2);
      issue(1, xd, true, a * STAGE);
      tok_pass<T3>();
      TR(3);
      if (warp < 3 && wn2 < NWIN && elect()) prefetch(warp, wn2);
      __syncwarp();
      TR(4);
      convert();
      store(a * STAGE + 8192);
      fence_async();
      const bool first = a == 0 && nxt == cl + ncl;
      if (first) {
        load_frags(2);
        asm volatile("bar.sync %0, 128;" ::"n"((int)BAR_STAGE) : "memory");
        asm volatile("st.shared.v4.b32 [%0], {%1,%1,%1,%1};" ::"r"(sb + OFF_KV + (warp >> 1) * STAGE + 144 * 128 + (tid & 63) * 16), "r"(0x3F803F80u) : "memory");
      }
      TR(5);
      DELAY(7, sta[0]);
      wg_fence();
      tok_wait<T5>();
      TR(6);
      issue(2, xd, false, 0);
      tok_pass<T6>();
      if (!more) {
        convert();
        store(a * STAGE + 16384 + v1off);
        fence_async();
        return false;
      }
      { WS_BEGIN; mbar_wait(bars + B_XFULL + 8 * (a ^ 1), a ? ph ^ 1 : ph); WS_END(0); WS_END(8 + i); }
      TR(7);
      convert();
      TR(8);
      wg_fence();
      SF;
      DELAY(2, sta[0]);
      tok_wait<T0>();
      TR(9);
      if (tid == KV_WG * 128 && wn2 < NWIN) mbar_arrive_cluster(xe_rem + 8 * a);
      issue(0, LO_X + (a ^ 1) * (STAGE >> 4), true, a * STAGE + 16384 + v1off);
      tok_pass<T1>();
      TR(10);
      fence_async();
      nxt += ncl;
      if (wn2 < NWIN) {
        { WS_BEGIN; mbar_wait(bars + B_XEMPTY + 8 * a, ph); WS_END(1); }
        if (elect()) {
          if (warp < 3) {
            load(warp, wn2, a);
          } else {
            mbar_expect_tx(bars + B_XFULL + 8 * a, X_BYTES + M_BYTES);
            if (rank == 0 && nxt + 3 * ncl >= base) {
              if (nxt + 2 * ncl < base) {
                asm volatile("atom.global.inc.u32 %0, [%1], %2;" : "=r"(ticket) : "l"(&g_ticket), "r"(ncl - 1) : "memory");
              } else if (nxt + ncl < base) {
#pragma unroll
                for (int r = 0; r < 2; r++)
                  asm volatile("st.async.shared::cluster.mbarrier::complete_tx::bytes.b32 [%0], %1, [%2];" ::"r"(mapa(bars + W_TICK, r)),
                               "r"(ticket), "r"(mapa(bars + B_TICK, r))
                               : "memory");
              }
            }
          }
        }
        __syncwarp();
      }
      i++;
      return true;
    };
    while (step(IC<0>{}) && step(IC<1>{})) ph ^= 1;
    tok_wait<T0>();
    tok_pass<T1>();
    tok_wait<T2>();
    tok_pass<T3>();
    tok_wait<T5>();
  } else {
    const int a = wg - (KV_WG == 0 ? 1 : 0);
    const int g = lane >> 2, q = lane & 3;
    const uint32_t bar = bars + 8 * a;
    asm volatile("barrier.cluster.arrive.relaxed.aligned;" ::: "memory");
    if (a == 0) {
      tok_pass<T2>();
      tok_pass<T5>();
    }
    asm volatile("setmaxnreg.dec.sync.aligned.u32 144;");
    uint32_t braw[32];
    {
      const int ty = 4 * (warp >> 1) + (g >> 1), tx = 4 * (warp & 1) + (g & 1);
      const int* ip = rp_idx + (ty * 8 + tx) * 64 + 8 * q;
#pragma unroll
      for (int c = 0; c < 8; c++)
        asm volatile("ld.global.nc.v4.b32 {%0,%1,%2,%3}, [%4];"
                     : "=r"(braw[4 * c]), "=r"(braw[4 * c + 1]), "=r"(braw[4 * c + 2]), "=r"(braw[4 * c + 3])
                     : "l"(ip + (c >> 2) * 128 + ((c >> 1) & 1) * 32 + (c & 1) * 4));
      const int e = a * 128 + (tid & 127);
      uint32_t v = 0;
      if (e < 225) asm volatile("ld.global.nc.b32 %0, [%1];" : "=r"(v) : "l"(reinterpret_cast<const uint32_t*>(rpb) + e * 2 + rank));
      asm volatile("st.shared.b32 [%0], %1;" ::"r"(sb + OFF_RPB + e * 4), "r"(v) : "memory");
      tok_wait<BAR_BIAS>();
#pragma unroll
      for (int j = 0; j < 32; j++)
        asm volatile("ld.shared.b32 %0, [%1];" : "=r"(braw[j]) : "r"(sb + OFF_RPB + braw[j] * 4) : "memory");
    }
    TRP(1);
    asm volatile("barrier.cluster.wait.aligned;" ::: "memory");
    TRP(2);

    const int mrow = 16 * warp + (g >> 1) + 4 * (g & 1);
#undef SF
#define SF sched_fence(mk_addr, never)
    uint32_t mk_addr = sb + OFF_MASK + a * STAGE + mrow * 128 + ((q ^ (mrow & 7)) << 4);
    const uint32_t ostage = sb + OFF_OIN + a * STAGE + warp * 3072;
    const uint32_t ost = ostage + ((lane >> 3) & 1) * 1536 + (lane & 7) * 64 + (((lane >> 4) ^ ((lane & 7) >> 1)) << 4);
    const uint32_t oin_rem = mapa(ostage + g * 64 + ((q ^ (g >> 1)) << 4), rank ^ 1);
    const uint32_t bar_rem = mapa(bar, rank ^ 1);

    auto store_out = [&](int win) {
      fence_async();
      __syncwarp();
      if (win >= 0 && elect()) {
        int yy = (((win >> 3) & ~7) + 4 + 4 * (warp >> 1)) & 511;
        int xh = (win * 4 + 2 + 2 * (warp & 1)) & 255;
        asm volatile("cp.async.bulk.tensor.5d.global.shared::cta.bulk_group [%0, {0, 0, %2, %3, %4}], [%1];" ::"l"(&maps.out), "r"(ostage),
                     "r"(yy), "r"(3 * rank), "r"(xh)
                     : "memory");
        asm volatile("cp.async.bulk.commit_group;" ::: "memory");
      }
      __syncwarp();
    };
    auto release_oin = [&]() {
      if (elect()) {
        { WS_BEGIN; asm volatile("cp.async.bulk.wait_group.read 0;" ::: "memory"); WS_END(4); }
        if (warp == 0) mbar_expect_tx(bar + B_OFULL, O_BYTES);
        mbar_arrive_cluster(bar_rem + B_OEMPTY);
      }
      __syncwarp();
    };
    float qa[48];
    uint32_t bias0[16], bias1[16];
    uint32_t mk[16];
    auto load_mask = [&](uint32_t z) {
#pragma unroll
      for (int c = 0; c < 4; c++)
        lds128((c & 1 ? mk_addr ^ (64 + z) : mk_addr) + (c >> 1) * 1024, mk[4 * c], mk[4 * c + 1], mk[4 * c + 2], mk[4 * c + 3]);
    };
    auto pre_init = [&]() {
      SF;
#pragma unroll
      for (int j = 0; j < 16; j++) asm("max.NaN.bf16x2 %0, %0, %1;" : "+r"(mk[j]) : "r"(0xFD80FD80u));
      pin(mk);
    };
    auto issue_q = [&](uint32_t ua, bool tok, int win) {
#pragma unroll
      for (int ks = 0; ks < 12; ks++) {
        if (ks == Q_SPLIT && tok) {
          tok_pass<T4>();
          if (STORE_AT == 1) store_out(win);
          tok_wait<T7>();
          if (Q_SPLIT > 0) wg_fence();
        }
        uint64_t da = mkdesc(ua + LO_X + (((ks >> 2) * 1024 + (ks & 3) * 32) >> 4), HI_X);
        uint64_t db = mkdesc(LO_WQ + ks * 64, HI_W);
        if (ks == 0) mma_q_init(qa, da, db);
        else mma_q(qa, da, db);
      }
      wg_commit();
      if (tok) tok_pass<T5>();
    };
#pragma unroll
    for (int j = 0; j < 16; j++) {
      const uint32_t b0 = braw[2 * j], b1 = braw[2 * j + 1];
      bias0[j] = pack_bias(__uint_as_float(b0 << 16), __uint_as_float(b1 << 16));
      bias1[j] = pack_bias(__uint_as_float(b0 & 0xffff0000u), __uint_as_float(b1 & 0xffff0000u));
    }
    pin(bias0);
    pin(bias1);
    SF;
    TRP(5);
    mbar_wait(bar + B_XFULL, 0);
    load_mask(0);
    mbar_wait(bars + B_WQ, 0);
    TRP(3);
    wg_fence();
    if (a == 0) tok_wait<T3>();
    else tok_wait<T1>();
    issue_q(a * (STAGE >> 4), false, 0);
    if (a == 1) {
      tok_pass<T2>();
      tok_wait<T3>();
      tok_pass<T4>();
      tok_pass<T5>();
      tok_wait<T7>();
    }
    TRP(4);
    pre_init();
    uint32_t ph = 0;
    [[maybe_unused]] int i = a;
    int win = cl + a * ncl;
    for (;; win += 2 * ncl, ph ^= 1, i += 2) {
      TR_SETUP(0);
      TR(0);
      const uint32_t ua = a * (STAGE >> 4) + (win >> 20);
      const uint32_t kd = ua + LO_KV;
      float s0[32], s1[32];
      s_init<PRE_T, 8>(s0, mk, bias0);
      if (PRE_T < 8) SF;
      TR(1);
      wg_wait<0>();
      pin(qa);
      TR(2);
      uint32_t q0[12], q1[12];
#pragma unroll
      for (int j = 0; j < 12; j++) q0[j] = pack_bf16(qa[2 * j], qa[2 * j + 1]);
#pragma unroll
      for (int j = 0; j < 12; j++) q1[j] = pack_bf16(qa[24 + 2 * j], qa[25 + 2 * j]);
      pin(q0);
      pin(q1);
      s_init<0, PRE_T, PM0>(s0, mk, bias0);
      s_init<S1_LATE, 8, PM1>(s1, mk, bias1);
      pin(s0);
      if (S1_LATE > 0) SF;
      TR(3);
      DELAY(1, mk_addr);
      wg_fence();
      tok_wait<T6>();
      TR(4);
#pragma unroll
      for (int ks = 0; ks < 3; ks++)
        mma_s(s0, q0[4 * ks], q0[4 * ks + 1], q0[4 * ks + 2], q0[4 * ks + 3], mkdesc(kd + ks * 128, HI_KV));
      wg_commit();
      if (S1_LATE > 0) {
        SF;
        s_init<0, S1_LATE>(s1, mk, bias1);
        wg_fence();
      }
      pin(s1);
#pragma unroll
      for (int ks = 0; ks < 3; ks++)
        mma_s(s1, q1[4 * ks], q1[4 * ks + 1], q1[4 * ks + 2], q1[4 * ks + 3], mkdesc(kd + (3 + ks) * 128, HI_KV));
      wg_commit();
      tok_pass<T0>();
      if (STORE_AT == 0) store_out(win - 2 * ncl);
      else release_oin();
      int x0, x1, y0, y1;
      float l00, l01, l10, l11;
      uint32_t p0[16], p1[16];
      wg_wait<1>();
      pin(s0);
      pin(q0);
      TR(5);
      rowmax_i(s0, x0, x1);
      quadmax_i(x0, x1, 1);
      wg_wait<0>();
      pin(s1);
      pin(q1);
      rowmax_i(s1, y0, y1);
      quadmax_i(x0, x1, 2);
      quadmax_i(y0, y1, 1);
      quadmax_i(y0, y1, 2);
      if (__builtin_expect(__any_sync(0xffffffffu, (x0 | x1 | y0 | y1) < 0), 0)) {
        rowmax_f(s0, x0, x1);
        rowmax_f(s1, y0, y1);
      }
      EXP(s0, p0, x0, x1, l00, l01, (FSUM & 1) != 0);
      TR(6);
      if (STORE_AT == 0) {
        SF;
        release_oin();
        SF;
      }
      EXP(s1, p1, y0, y1, l10, l11, (FSUM & 2) != 0);
      TR(7);
      float o0[FSUM & 1 ? 24 : 28], o1[FSUM & 2 ? 24 : 28];
      wg_fence();
      SF;
      DELAY(6, mk_addr);
      tok_wait<T4>();
      TR(8);
      issue_p(o0, p0, kd + ((96 * 128) >> 4));
      issue_p(o1, p1, kd + (((FSUM & 2 ? 152 : 144) * 128) >> 4));
      tok_pass<T7>();
      if (FSUM & 1) quadsum_rcp(l00, l01);
      if (FSUM & 2) quadsum_rcp(l10, l11);
      { WS_BEGIN; mbar_wait(bar + B_OEMPTY, ph); WS_END(2); }
      uint32_t f0[12], f1[12];
      wg_wait<1>();
      pin(o0);
      pin(p0);
      if constexpr (FSUM & 1) normalize<0>(o0, f0, l00, l01);
      else normalize<0>(o0, f0, rcp(o0[FSUM & 1 ? 0 : 24]), rcp(o0[FSUM & 1 ? 0 : 26]));
      st_async<0>(oin_rem, bar_rem + B_OFULL, f0[0], f0[2], f0[4], f0[6]);
      st_async<1536>(oin_rem, bar_rem + B_OFULL, f0[1], f0[3], f0[5], f0[7]);
      wg_wait<0>();
      pin(o1);
      pin(p1);
      TR(9);
      DELAY(8, mk_addr);
      if constexpr (FSUM & 2) normalize<0>(o1, f1, l10, l11);
      else normalize<FSUM & 2 ? 0 : 4>(o1, f1, rcp(o1[0]), rcp(o1[2]));
      st_async<512>(oin_rem, bar_rem + B_OFULL, f0[8], f0[10], f1[0], f1[2]);
      st_async<2048>(oin_rem, bar_rem + B_OFULL, f0[9], f0[11], f1[1], f1[3]);
      st_async<1024>(oin_rem, bar_rem + B_OFULL, f1[4], f1[6], f1[8], f1[10]);
      st_async<2560>(oin_rem, bar_rem + B_OFULL, f1[5], f1[7], f1[9], f1[11]);
      pin(f0);
      pin(f1);
      float (&oa)[48] = qa;
      bool last = false;
      bool fin = false;
      if ((unsigned)(win - 2 * ncl) >= (unsigned)(base - 4 * ncl)) {
        if (win < 2 * ncl) {
          mbar_wait(bars + B_WO, 0);
        } else {
          read_ticket();
          last = window(win + ncl) >= NWIN;
          fin = window(win + 2 * ncl) >= NWIN;
        }
      }
      TR(10);
      if (!last) tok_wait<T1>();
      SF;
#pragma unroll
      for (int j = 8; j < 12; j++) f0[j] += never;
#pragma unroll
      for (int j = 0; j < 12; j++) f1[j] += never;
      pin(f0);
      pin(f1);
      DELAY(3, mk_addr);
      wg_fence();
      TR(11);
#pragma unroll
      for (int ks = 0; ks < 3; ks++) {
        uint64_t db = mkdesc(LO_WO + ks * 64, HI_W);
        if (ks == 0) mma_o_init(oa, f0[0], f0[1], f0[2], f0[3], db);
        else mma_o(oa, f0[4 * ks], f0[4 * ks + 1], f0[4 * ks + 2], f0[4 * ks + 3], db);
      }
#pragma unroll
      for (int ks = 0; ks < 3; ks++)
        mma_o(oa, f1[4 * ks], f1[4 * ks + 1], f1[4 * ks + 2], f1[4 * ks + 3], mkdesc(LO_WO + (3 + ks) * 64, HI_W));
      { WS_BEGIN; mbar_wait(bar + B_OFULL, ph); WS_END(3); }
      asm volatile("fence.proxy.async::generic.acquire.sync_restrict::shared::cluster.cluster;" ::: "memory");
      DELAY(10, mk_addr);
      wg_fence();
#pragma unroll
      for (int ks = 0; ks < 6; ks++)
        mma_q(oa, mkdesc(ua + LO_O + (((ks >> 1) * 512 + (ks & 1) * 32) >> 4), HI_O), mkdesc(LO_WO + (18432 >> 4) + ks * 64, HI_W));
      wg_commit();
      if (!last) tok_pass<T2>();
      load_mask(win >> 20);
      wg_wait<0>();
      pin(oa);
      pin(f0);
      pin(f1);
      TR(12);
#pragma unroll
      for (int jj = 0; jj < 6; jj++)
        stsm4((jj & 1 ? ost ^ (32 + (win >> 20)) : ost) + (jj >> 1) * 512, pack_bf16(oa[8 * jj], oa[8 * jj + 1]), pack_bf16(oa[8 * jj + 2], oa[8 * jj + 3]),
              pack_bf16(oa[8 * jj + 4], oa[8 * jj + 5]), pack_bf16(oa[8 * jj + 6], oa[8 * jj + 7]));
      if (fin) {
        if (!last) {
          tok_wait<T3>();
          tok_pass<T4>();
          tok_pass<T5>();
          tok_wait<T7>();
        }
        break;
      }
      DELAY(5, mk_addr);
      wg_fence();
      tok_wait<T3>();
      TR(13);
      issue_q(ua, true, win);
      TR(14);
      pre_init();
    }
    TRP(6);
    store_out(window(win));
    TRP(7);
    asm volatile("cp.async.bulk.wait_group.read 0;" ::: "memory");
    TRP(8);
    __syncwarp();
  }
  CLKP(1);
}

typedef CUresult (*EncodeFn)(CUtensorMap*, CUtensorMapDataType, cuuint32_t, void*, const cuuint64_t*, const cuuint64_t*,
                             const cuuint32_t*, const cuuint32_t*, CUtensorMapInterleave, CUtensorMapSwizzle,
                             CUtensorMapL2promotion, CUtensorMapFloatOOBfill);

void encode_map(EncodeFn encode, CUtensorMap* m, void* p, int rank, const cuuint64_t* dim, const cuuint64_t* str,
                const cuuint32_t* box, CUtensorMapSwizzle sw) {
  const cuuint32_t es[5] = {1, 1, 1, 1, 1};
  CUresult r = encode(m, CU_TENSOR_MAP_DATA_TYPE_BFLOAT16, rank, p, dim, str, box, es, CU_TENSOR_MAP_INTERLEAVE_NONE, sw,
                      L2PROMO, CU_TENSOR_MAP_FLOAT_OOB_FILL_NONE);
  if (r != CUDA_SUCCESS) fprintf(stderr, "tensor map encode failed: %d\n", (int)r);
}

}

extern "C" void kernel_launch(void* const* d_in, const int* in_sizes, int n_in, void* d_out, int out_size) {
  static EncodeFn encode = nullptr;
  static int grid = 0;
  if (!encode) {
    cudaDriverEntryPointQueryResult qr;
    void* fn = nullptr;
    cudaGetDriverEntryPoint("cuTensorMapEncodeTiled", &fn, cudaEnableDefault, &qr);
    encode = (EncodeFn)fn;
    cudaFuncSetAttribute(swin_attn_kernel, cudaFuncAttributeMaxDynamicSharedMemorySize, SMEM_BYTES);
    cudaLaunchConfig_t cfg = {};
    cfg.gridDim = dim3(132);
    cfg.blockDim = dim3(384);
    cfg.dynamicSmemBytes = SMEM_BYTES;
    cudaLaunchAttribute at;
    at.id = cudaLaunchAttributeClusterDimension;
    at.val.clusterDim.x = 2;
    at.val.clusterDim.y = 1;
    at.val.clusterDim.z = 1;
    cfg.attrs = &at;
    cfg.numAttrs = 1;
    int ncl = 0;
    if (cudaOccupancyMaxActiveClusters(&ncl, swin_attn_kernel, &cfg) != cudaSuccess || ncl < 1) {
      (void)cudaGetLastError();
      ncl = 66;
    }
    if (ncl > 256) ncl = 256;
    grid = 2 * ncl;
  }
  Maps maps;
  {
    const cuuint64_t dim[5] = {64, 2, 512, 3, 256}, str[4] = {384, 512 * 384, 128, 768};
    const cuuint32_t box[5] = {64, 2, 4, 3, 2};
    encode_map(encode, &maps.x, d_in[0], 5, dim, str, box, CU_TENSOR_MAP_SWIZZLE_128B);
  }
  {
    const cuuint64_t dim[5] = {64, 4, 2, 4, 8192}, str[4] = {1024, 128, 256, 4096};
    const cuuint32_t box[5] = {64, 4, 2, 4, 1};
    encode_map(encode, &maps.mask, d_in[5], 5, dim, str, box, CU_TENSOR_MAP_SWIZZLE_128B);
  }
  {
    const cuuint64_t dim[5] = {32, 2, 512, 6, 256}, str[4] = {384, 512 * 384, 64, 768};
    const cuuint32_t box[5] = {32, 2, 4, 3, 2};
    encode_map(encode, &maps.out, d_out, 5, dim, str, box, CU_TENSOR_MAP_SWIZZLE_64B);
  }
  {
    const cuuint64_t dim[3] = {32, 192, 18}, str[2] = {576 * 2, 64};
    const cuuint32_t box[3] = {32, 192, 1};
    encode_map(encode, &maps.wqkv, d_in[1], 3, dim, str, box, CU_TENSOR_MAP_SWIZZLE_64B);
    const cuuint64_t dim2[3] = {32, 192, 6}, str2[2] = {192 * 2, 64};
    const cuuint32_t box2[3] = {32, 96, 3};
    encode_map(encode, &maps.wo, d_in[2], 3, dim2, str2, box2, CU_TENSOR_MAP_SWIZZLE_64B);
    const cuuint64_t dim3_[5] = {192, 2, 4, 4, 6}, str3[4] = {384, 8 * 384, 2 * 384, 32 * 384};
    const cuuint32_t box3[5] = {32, 2, 4, 4, 3};
    encode_map(encode, &maps.wop, d_in[2], 5, dim3_, str3, box3, CU_TENSOR_MAP_SWIZZLE_64B);
  }
  swin_attn_kernel<<<grid, 384, SMEM_BYTES>>>(maps, (const __nv_bfloat16*)d_in[3], (const int*)d_in[4], NWIN / (grid / 2) * (grid / 2), 0);
}
```

```cpp
#include <cuda_runtime.h>
#include <cuda_bf16.h>
#include <cuda.h>
#include <stdint.h>
#include <stdio.h>

namespace {

constexpr int NWIN = 4096;
constexpr int KV_WG = 0;
constexpr int Q_SPLIT = 4;
constexpr int EXP_CH = 4;

constexpr uint32_t SM_BASE  = 1024;
constexpr uint32_t OFF_WQ   = 0;
constexpr uint32_t OFF_WO   = 36864;
constexpr uint32_t STAGE    = 70656;
constexpr uint32_t OFF_X    = 73728;
constexpr uint32_t X_BYTES  = 24576;
constexpr uint32_t OFF_MASK = OFF_X + X_BYTES;
constexpr uint32_t M_BYTES  = 8192;
constexpr uint32_t OFF_KV   = OFF_MASK + M_BYTES;
constexpr uint32_t OFF_OIN  = OFF_KV + 25600;
constexpr uint32_t O_BYTES  = 12288;
constexpr uint32_t OFF_BAR  = 215040;
constexpr uint32_t OFF_RPB  = OFF_BAR + 1024;
constexpr uint32_t SMEM_BYTES = OFF_RPB + 1024;
constexpr uint32_t B_XFULL = 0, B_XEMPTY = 16, B_OFULL = 32, B_OEMPTY = 48, B_WKV = 64  , B_WQ = 88, B_WO = 96,
                   B_TICK = 104, B_M0 = 112, W_TICK = 120;
enum { T0 = 1, T1, T2, T3, T4, T5, T6, T7, BAR_BIAS, BAR_STAGE };

__device__ unsigned int g_ticket;

template <int V> struct IC { static constexpr int value = V; };
struct Maps { CUtensorMap x, mask, out, wqkv, wo, wop; };

__device__ __forceinline__ void mma_q_init(float (&d)[48], uint64_t descA, uint64_t descB) {
  asm volatile("wgmma.mma_async.sync.aligned.m64n96k16.f32.bf16.bf16 {%0, %1, %2, %3, %4, %5, %6, %7, %8, %9, %10, %11, %12, %13, %14, %15, %16, %17, %18, %19, %20, %21, %22, %23, %24, %25, %26, %27, %28, %29, %30, %31, %32, %33, %34, %35, %36, %37, %38, %39, %40, %41, %42, %43, %44, %45, %46, %47}, "
    "%48, %49, 0, 1, 1, 0, 1;"
    : "+f"(d[0]), "+f"(d[1]), "+f"(d[2]), "+f"(d[3]), "+f"(d[4]), "+f"(d[5]), "+f"(d[6]), "+f"(d[7]), "+f"(d[8]), "+f"(d[9]), "+f"(d[10]), "+f"(d[11]), "+f"(d[12]), "+f"(d[13]), "+f"(d[14]), "+f"(d[15]), "+f"(d[16]), "+f"(d[17]), "+f"(d[18]), "+f"(d[19]), "+f"(d[20]), "+f"(d[21]), "+f"(d[22]), "+f"(d[23]), "+f"(d[24]), "+f"(d[25]), "+f"(d[26]), "+f"(d[27]), "+f"(d[28]), "+f"(d[29]), "+f"(d[30]), "+f"(d[31]), "+f"(d[32]), "+f"(d[33]), "+f"(d[34]), "+f"(d[35]), "+f"(d[36]), "+f"(d[37]), "+f"(d[38]), "+f"(d[39]), "+f"(d[40]), "+f"(d[41]), "+f"(d[42]), "+f"(d[43]), "+f"(d[44]), "+f"(d[45]), "+f"(d[46]), "+f"(d[47])
    : "l"(descA), "l"(descB));
}
__device__ __forceinline__ void mma_q(float (&d)[48], uint64_t descA, uint64_t descB) {
  asm volatile("wgmma.mma_async.sync.aligned.m64n96k16.f32.bf16.bf16 {%0, %1, %2, %3, %4, %5, %6, %7, %8, %9, %10, %11, %12, %13, %14, %15, %16, %17, %18, %19, %20, %21, %22, %23, %24, %25, %26, %27, %28, %29, %30, %31, %32, %33, %34, %35, %36, %37, %38, %39, %40, %41, %42, %43, %44, %45, %46, %47}, "
    "%48, %49, 1, 1, 1, 0, 1;"
    : "+f"(d[0]), "+f"(d[1]), "+f"(d[2]), "+f"(d[3]), "+f"(d[4]), "+f"(d[5]), "+f"(d[6]), "+f"(d[7]), "+f"(d[8]), "+f"(d[9]), "+f"(d[10]), "+f"(d[11]), "+f"(d[12]), "+f"(d[13]), "+f"(d[14]), "+f"(d[15]), "+f"(d[16]), "+f"(d[17]), "+f"(d[18]), "+f"(d[19]), "+f"(d[20]), "+f"(d[21]), "+f"(d[22]), "+f"(d[23]), "+f"(d[24]), "+f"(d[25]), "+f"(d[26]), "+f"(d[27]), "+f"(d[28]), "+f"(d[29]), "+f"(d[30]), "+f"(d[31]), "+f"(d[32]), "+f"(d[33]), "+f"(d[34]), "+f"(d[35]), "+f"(d[36]), "+f"(d[37]), "+f"(d[38]), "+f"(d[39]), "+f"(d[40]), "+f"(d[41]), "+f"(d[42]), "+f"(d[43]), "+f"(d[44]), "+f"(d[45]), "+f"(d[46]), "+f"(d[47])
    : "l"(descA), "l"(descB));
}
__device__ __forceinline__ void mma_kv_init(float (&d)[32], uint32_t a0, uint32_t a1, uint32_t a2, uint32_t a3, uint64_t descB) {
  asm volatile("wgmma.mma_async.sync.aligned.m64n64k16.f32.bf16.bf16 {%0, %1, %2, %3, %4, %5, %6, %7, %8, %9, %10, %11, %12, %13, %14, %15, %16, %17, %18, %19, %20, %21, %22, %23, %24, %25, %26, %27, %28, %29, %30, %31}, "
    "{%32, %33, %34, %35}, %36, 0, 1, 1, 0;"
    : "+f"(d[0]), "+f"(d[1]), "+f"(d[2]), "+f"(d[3]), "+f"(d[4]), "+f"(d[5]), "+f"(d[6]), "+f"(d[7]), "+f"(d[8]), "+f"(d[9]), "+f"(d[10]), "+f"(d[11]), "+f"(d[12]), "+f"(d[13]), "+f"(d[14]), "+f"(d[15]), "+f"(d[16]), "+f"(d[17]), "+f"(d[18]), "+f"(d[19]), "+f"(d[20]), "+f"(d[21]), "+f"(d[22]), "+f"(d[23]), "+f"(d[24]), "+f"(d[25]), "+f"(d[26]), "+f"(d[27]), "+f"(d[28]), "+f"(d[29]), "+f"(d[30]), "+f"(d[31])
    : "r"(a0), "r"(a1), "r"(a2), "r"(a3), "l"(descB));
}
__device__ __forceinline__ void mma_kv(float (&d)[32], uint32_t a0, uint32_t a1, uint32_t a2, uint32_t a3, uint64_t descB) {
  asm volatile("wgmma.mma_async.sync.aligned.m64n64k16.f32.bf16.bf16 {%0, %1, %2, %3, %4, %5, %6, %7, %8, %9, %10, %11, %12, %13, %14, %15, %16, %17, %18, %19, %20, %21, %22, %23, %24, %25, %26, %27, %28, %29, %30, %31}, "
    "{%32, %33, %34, %35}, %36, 1, 1, 1, 0;"
    : "+f"(d[0]), "+f"(d[1]), "+f"(d[2]), "+f"(d[3]), "+f"(d[4]), "+f"(d[5]), "+f"(d[6]), "+f"(d[7]), "+f"(d[8]), "+f"(d[9]), "+f"(d[10]), "+f"(d[11]), "+f"(d[12]), "+f"(d[13]), "+f"(d[14]), "+f"(d[15]), "+f"(d[16]), "+f"(d[17]), "+f"(d[18]), "+f"(d[19]), "+f"(d[20]), "+f"(d[21]), "+f"(d[22]), "+f"(d[23]), "+f"(d[24]), "+f"(d[25]), "+f"(d[26]), "+f"(d[27]), "+f"(d[28]), "+f"(d[29]), "+f"(d[30]), "+f"(d[31])
    : "r"(a0), "r"(a1), "r"(a2), "r"(a3), "l"(descB));
}
__device__ __forceinline__ void mma_s(float (&d)[32], uint32_t a0, uint32_t a1, uint32_t a2, uint32_t a3, uint64_t descB) {
  asm volatile("wgmma.mma_async.sync.aligned.m64n64k16.f32.bf16.bf16 {%0, %1, %2, %3, %4, %5, %6, %7, %8, %9, %10, %11, %12, %13, %14, %15, %16, %17, %18, %19, %20, %21, %22, %23, %24, %25, %26, %27, %28, %29, %30, %31}, "
    "{%32, %33, %34, %35}, %36, 1, 1, 1, 1;"
    : "+f"(d[0]), "+f"(d[1]), "+f"(d[2]), "+f"(d[3]), "+f"(d[4]), "+f"(d[5]), "+f"(d[6]), "+f"(d[7]), "+f"(d[8]), "+f"(d[9]), "+f"(d[10]), "+f"(d[11]), "+f"(d[12]), "+f"(d[13]), "+f"(d[14]), "+f"(d[15]), "+f"(d[16]), "+f"(d[17]), "+f"(d[18]), "+f"(d[19]), "+f"(d[20]), "+f"(d[21]), "+f"(d[22]), "+f"(d[23]), "+f"(d[24]), "+f"(d[25]), "+f"(d[26]), "+f"(d[27]), "+f"(d[28]), "+f"(d[29]), "+f"(d[30]), "+f"(d[31])
    : "r"(a0), "r"(a1), "r"(a2), "r"(a3), "l"(descB));
}
__device__ __forceinline__ void mma_p_init(float (&d)[28], uint32_t a0, uint32_t a1, uint32_t a2, uint32_t a3, uint64_t descB) {
  asm volatile("wgmma.mma_async.sync.aligned.m64n56k16.f32.bf16.bf16 {%0, %1, %2, %3, %4, %5, %6, %7, %8, %9, %10, %11, %12, %13, %14, %15, %16, %17, %18, %19, %20, %21, %22, %23, %24, %25, %26, %27}, "
    "{%28, %29, %30, %31}, %32, 0, 1, 1, 0;"
    : "=f"(d[0]), "=f"(d[1]), "=f"(d[2]), "=f"(d[3]), "=f"(d[4]), "=f"(d[5]), "=f"(d[6]), "=f"(d[7]), "=f"(d[8]), "=f"(d[9]), "=f"(d[10]), "=f"(d[11]), "=f"(d[12]), "=f"(d[13]), "=f"(d[14]), "=f"(d[15]), "=f"(d[16]), "=f"(d[17]), "=f"(d[18]), "=f"(d[19]), "=f"(d[20]), "=f"(d[21]), "=f"(d[22]), "=f"(d[23]), "=f"(d[24]), "=f"(d[25]), "=f"(d[26]), "=f"(d[27])
    : "r"(a0), "r"(a1), "r"(a2), "r"(a3), "l"(descB));
}
__device__ __forceinline__ void mma_p(float (&d)[28], uint32_t a0, uint32_t a1, uint32_t a2, uint32_t a3, uint64_t descB) {
  asm volatile("wgmma.mma_async.sync.aligned.m64n56k16.f32.bf16.bf16 {%0, %1, %2, %3, %4, %5, %6, %7, %8, %9, %10, %11, %12, %13, %14, %15, %16, %17, %18, %19, %20, %21, %22, %23, %24, %25, %26, %27}, "
    "{%28, %29, %30, %31}, %32, 1, 1, 1, 0;"
    : "+f"(d[0]), "+f"(d[1]), "+f"(d[2]), "+f"(d[3]), "+f"(d[4]), "+f"(d[5]), "+f"(d[6]), "+f"(d[7]), "+f"(d[8]), "+f"(d[9]), "+f"(d[10]), "+f"(d[11]), "+f"(d[12]), "+f"(d[13]), "+f"(d[14]), "+f"(d[15]), "+f"(d[16]), "+f"(d[17]), "+f"(d[18]), "+f"(d[19]), "+f"(d[20]), "+f"(d[21]), "+f"(d[22]), "+f"(d[23]), "+f"(d[24]), "+f"(d[25]), "+f"(d[26]), "+f"(d[27])
    : "r"(a0), "r"(a1), "r"(a2), "r"(a3), "l"(descB));
}
__device__ __forceinline__ void mma_o_init(float (&d)[48], uint32_t a0, uint32_t a1, uint32_t a2, uint32_t a3, uint64_t descB) {
  asm volatile("wgmma.mma_async.sync.aligned.m64n96k16.f32.bf16.bf16 {%0, %1, %2, %3, %4, %5, %6, %7, %8, %9, %10, %11, %12, %13, %14, %15, %16, %17, %18, %19, %20, %21, %22, %23, %24, %25, %26, %27, %28, %29, %30, %31, %32, %33, %34, %35, %36, %37, %38, %39, %40, %41, %42, %43, %44, %45, %46, %47}, "
    "{%48, %49, %50, %51}, %52, 0, 1, 1, 1;"
    : "=f"(d[0]), "=f"(d[1]), "=f"(d[2]), "=f"(d[3]), "=f"(d[4]), "=f"(d[5]), "=f"(d[6]), "=f"(d[7]), "=f"(d[8]), "=f"(d[9]), "=f"(d[10]), "=f"(d[11]), "=f"(d[12]), "=f"(d[13]), "=f"(d[14]), "=f"(d[15]), "=f"(d[16]), "=f"(d[17]), "=f"(d[18]), "=f"(d[19]), "=f"(d[20]), "=f"(d[21]), "=f"(d[22]), "=f"(d[23]), "=f"(d[24]), "=f"(d[25]), "=f"(d[26]), "=f"(d[27]), "=f"(d[28]), "=f"(d[29]), "=f"(d[30]), "=f"(d[31]), "=f"(d[32]), "=f"(d[33]), "=f"(d[34]), "=f"(d[35]), "=f"(d[36]), "=f"(d[37]), "=f"(d[38]), "=f"(d[39]), "=f"(d[40]), "=f"(d[41]), "=f"(d[42]), "=f"(d[43]), "=f"(d[44]), "=f"(d[45]), "=f"(d[46]), "=f"(d[47])
    : "r"(a0), "r"(a1), "r"(a2), "r"(a3), "l"(descB));
}
__device__ __forceinline__ void mma_o(float (&d)[48], uint32_t a0, uint32_t a1, uint32_t a2, uint32_t a3, uint64_t descB) {
  asm volatile("wgmma.mma_async.sync.aligned.m64n96k16.f32.bf16.bf16 {%0, %1, %2, %3, %4, %5, %6, %7, %8, %9, %10, %11, %12, %13, %14, %15, %16, %17, %18, %19, %20, %21, %22, %23, %24, %25, %26, %27, %28, %29, %30, %31, %32, %33, %34, %35, %36, %37, %38, %39, %40, %41, %42, %43, %44, %45, %46, %47}, "
    "{%48, %49, %50, %51}, %52, 1, 1, 1, 1;"
    : "+f"(d[0]), "+f"(d[1]), "+f"(d[2]), "+f"(d[3]), "+f"(d[4]), "+f"(d[5]), "+f"(d[6]), "+f"(d[7]), "+f"(d[8]), "+f"(d[9]), "+f"(d[10]), "+f"(d[11]), "+f"(d[12]), "+f"(d[13]), "+f"(d[14]), "+f"(d[15]), "+f"(d[16]), "+f"(d[17]), "+f"(d[18]), "+f"(d[19]), "+f"(d[20]), "+f"(d[21]), "+f"(d[22]), "+f"(d[23]), "+f"(d[24]), "+f"(d[25]), "+f"(d[26]), "+f"(d[27]), "+f"(d[28]), "+f"(d[29]), "+f"(d[30]), "+f"(d[31]), "+f"(d[32]), "+f"(d[33]), "+f"(d[34]), "+f"(d[35]), "+f"(d[36]), "+f"(d[37]), "+f"(d[38]), "+f"(d[39]), "+f"(d[40]), "+f"(d[41]), "+f"(d[42]), "+f"(d[43]), "+f"(d[44]), "+f"(d[45]), "+f"(d[46]), "+f"(d[47])
    : "r"(a0), "r"(a1), "r"(a2), "r"(a3), "l"(descB));
}

__device__ __forceinline__ void wg_fence() { asm volatile("wgmma.fence.sync.aligned;" ::: "memory"); }
__device__ __forceinline__ void wg_commit() { asm volatile("wgmma.commit_group.sync.aligned;" ::: "memory"); }
template <int N> __device__ __forceinline__ void wg_wait() { asm volatile("wgmma.wait_group.sync.aligned %0;" ::"n"(N) : "memory"); }
template <int N> __device__ __forceinline__ void pin(float (&d)[N]) {
#pragma unroll
  for (int i = 0; i < N; i++) asm volatile("" : "+f"(d[i])::"memory");
}
template <int N> __device__ __forceinline__ void pin(uint32_t (&d)[N]) {
#pragma unroll
  for (int i = 0; i < N; i++) asm volatile("" : "+r"(d[i])::"memory");
}
__device__ __forceinline__ uint64_t mkdesc(uint32_t lo, uint32_t hi) { return ((uint64_t)hi << 32) | lo; }
constexpr uint64_t EVICT_FIRST = 0x12F0000000000000ull;
constexpr uint32_t HI_X = (3072 >> 4) | (1u << 30);
constexpr uint32_t HI_KV = (1024 >> 4) | (1u << 30);
constexpr uint32_t HI_W = (512 >> 4) | (2u << 30);
constexpr uint32_t HI_O = (1536 >> 4) | (2u << 30);
constexpr uint32_t LO_O = (1u << 16) + ((SM_BASE + OFF_OIN) >> 4);
constexpr uint32_t LO_WQ = ((12288 >> 4) << 16) + ((SM_BASE + OFF_WQ) >> 4);
constexpr uint32_t LO_WO = ((6144 >> 4) << 16) + ((SM_BASE + OFF_WO) >> 4);
constexpr uint32_t LO_X = (1u << 16) + ((SM_BASE + OFF_X) >> 4);
constexpr uint32_t LO_KV = (1u << 16) + ((SM_BASE + OFF_KV) >> 4);

__device__ __forceinline__ uint32_t pack_bf16(float lo, float hi) {
  uint32_t r;
  asm("cvt.rn.bf16x2.f32 %0, %1, %2;" : "=r"(r) : "f"(hi), "f"(lo));
  return r;
}
__device__ __forceinline__ float ex2(float x) {
  float r;
  asm("ex2.approx.ftz.f32 %0, %1;" : "=f"(r) : "f"(x));
  return r;
}
__device__ __forceinline__ float rcp(float x) {
  float r;
  asm("rcp.approx.ftz.f32 %0, %1;" : "=f"(r) : "f"(x));
  return r;
}
__device__ __forceinline__ bool elect() {
  uint32_t p;
  asm volatile("{\n.reg .pred P;\nelect.sync _|P, 0xffffffff;\nselp.u32 %0, 1, 0, P;\n}" : "=r"(p));
  return p;
}
__device__ __forceinline__ void mbar_init(uint32_t bar, uint32_t cnt) {
  asm volatile("mbarrier.init.shared::cta.b64 [%0], %1;" ::"r"(bar), "r"(cnt) : "memory");
}
__device__ __forceinline__ void mbar_wait(uint32_t bar, uint32_t parity) {
  asm volatile(
      "{\n.reg .pred p;\n.reg .u32 n;\n"
      "mbarrier.try_wait.parity.shared::cta.b64 p, [%0], %1;\n"
      "@p bra DONE;\n"
      "mov.u32 n, 0;\n"
      "LOOP:\n"
      "mbarrier.try_wait.parity.shared::cta.b64 p, [%0], %1;\n"
      "@p bra DONE;\n"
      "add.u32 n, n, 1;\n"
      "setp.lt.u32 p, n, 0x400000;\n"
      "@p bra LOOP;\n"
      "trap;\n"
      "DONE:\n}\n" ::"r"(bar), "r"(parity)
      : "memory");
}
__device__ __forceinline__ void mbar_arrive_cluster(uint32_t bar) {
  asm volatile("mbarrier.arrive.shared::cluster.b64 _, [%0];" ::"r"(bar) : "memory");
}
__device__ __forceinline__ void mbar_expect_tx(uint32_t bar, uint32_t bytes) {
  asm volatile("mbarrier.arrive.expect_tx.shared::cta.b64 _, [%0], %1;" ::"r"(bar), "r"(bytes) : "memory");
}
__device__ __forceinline__ uint32_t mapa(uint32_t addr, uint32_t rank) {
  uint32_t r;
  asm("mapa.shared::cluster.u32 %0, %1, %2;" : "=r"(r) : "r"(addr), "r"(rank));
  return r;
}
__device__ __forceinline__ void sched_fence(uint32_t& keep, int never) {
  asm volatile("{\n.reg .pred p;\nsetp.ne.s32 p, %1, 0;\n@p mov.u32 %0, %clock;\n}" : "+r"(keep) : "r"(never) : "memory");
}
template <int ID> __device__ __forceinline__ void tok_wait() { asm volatile("bar.sync %0, %1;" ::"n"(ID), "n"(ID == T7 ? 384 : 256) : "memory"); }
template <int ID> __device__ __forceinline__ void tok_pass() { asm volatile("bar.arrive %0, %1;" ::"n"(ID), "n"(ID == T7 ? 384 : 256) : "memory"); }
__device__ __forceinline__ void fence_async() { asm volatile("fence.proxy.async.shared::cta;" ::: "memory"); }
__device__ __forceinline__ void stsm4(uint32_t addr, uint32_t r0, uint32_t r1, uint32_t r2, uint32_t r3) {
  asm volatile("stmatrix.sync.aligned.m8n8.x4.shared.b16 [%0], {%1,%2,%3,%4};" ::"r"(addr), "r"(r0), "r"(r1), "r"(r2), "r"(r3) : "memory");
}
__device__ __forceinline__ void lds128(uint32_t addr, uint32_t& r0, uint32_t& r1, uint32_t& r2, uint32_t& r3) {
  asm volatile("ld.shared.v4.b32 {%0,%1,%2,%3}, [%4];" : "=r"(r0), "=r"(r1), "=r"(r2), "=r"(r3) : "r"(addr) : "memory");
}
template <int OFF>
__device__ __forceinline__ void st_async(uint32_t addr, uint32_t bar, uint32_t r0, uint32_t r1, uint32_t r2, uint32_t r3) {
  asm volatile("st.async.shared::cluster.mbarrier::complete_tx::bytes.v4.b32 [%0+%6], {%1,%2,%3,%4}, [%5];" ::"r"(addr), "r"(r0),
               "r"(r1), "r"(r2), "r"(r3), "r"(bar), "n"(OFF)
               : "memory");
}
__device__ __forceinline__ void tma5_mc(uint32_t dst, const CUtensorMap* tm, uint32_t bar, int c2, int c4) {
  asm volatile(
      "cp.async.bulk.tensor.5d.shared::cluster.global.mbarrier::complete_tx::bytes.multicast::cluster.L2::cache_hint "
      "[%0], [%1, {0, 0, %3, 0, %4}], [%2], %5, %6;" ::"r"(dst), "l"(tm), "r"(bar), "r"(c2), "r"(c4), "h"((uint16_t)3), "l"(EVICT_FIRST)
      : "memory");
}
__device__ __forceinline__ void tma5_pf(const CUtensorMap* tm, int c2, int c4) {
  asm volatile("cp.async.bulk.prefetch.tensor.5d.L2.global [%0, {0, 0, %1, 0, %2}];" ::"l"(tm), "r"(c2), "r"(c4) : "memory");
}
__device__ __forceinline__ void tma3(uint32_t dst, const CUtensorMap* tm, uint32_t bar, int c1, int c2) {
  asm volatile("cp.async.bulk.tensor.3d.shared::cluster.global.mbarrier::complete_tx::bytes [%0], [%1, {0, %3, %4}], [%2];" ::"r"(dst),
               "l"(tm), "r"(bar), "r"(c1), "r"(c2)
               : "memory");
}

constexpr float SQRT_HD = 6.92820323027551f;
constexpr float SM_C = 1.4426950408889634f / SQRT_HD;

__device__ __forceinline__ void s_init(float (&s)[32], const uint32_t (&mk)[16], const uint32_t (&b)[16]) {
#pragma unroll
  for (int i = 0; i < 16; i++) {
    const int o = 4 * (i & 7) + 2 * (i >> 3);
    uint32_t t0, t1;
    asm("{\n.reg .b16 ml, mh, bl, bh;\n.reg .b32 m2, b2;\n"
        "mov.b32 {ml, mh}, %1;\nmov.b32 {bl, bh}, %3;\nmov.b32 m2, {ml, ml};\nmov.b32 b2, {bl, bl};\n"
        "fma.rn.bf16x2 %0, m2, %2, b2;\n}"
        : "=r"(t0)
        : "r"(mk[i]), "r"(0x40DE40DEu), "r"(b[i]));
    asm("fma.rn.bf16x2 %0, %1, %2, %3;" : "=r"(t1) : "r"(mk[i]), "r"(0x40DE40DEu), "r"(b[i]));
    s[o] = __uint_as_float(t0);
    s[o + 1] = __uint_as_float(t1);
    asm volatile("" : "+f"(s[o]), "+f"(s[o + 1])::"memory");
  }
}
__device__ __forceinline__ uint32_t pack_bias(float lo, float hi) {
  uint32_t l = __float_as_uint(fmaf(lo, SQRT_HD, 0x1p-100f)), h = __float_as_uint(fmaf(hi, SQRT_HD, 0x1p-100f));
  l = (l - (l >> 16) + 0x8000u) >> 16;
  return ((h - l + 0x8000u) & 0xffff0000u) | l;
}
__device__ __forceinline__ void rowmax_i(const float (&s)[32], int& i0, int& i1) {
#define FI(x) __float_as_int(x)
  i0 = max(FI(s[0]), FI(s[1])), i1 = max(FI(s[2]), FI(s[3]));
  int k0 = __vimax3_s32(FI(s[4]), FI(s[5]), FI(s[8])), k1 = __vimax3_s32(FI(s[6]), FI(s[7]), FI(s[10]));
  i0 = __vimax3_s32(i0, FI(s[9]), FI(s[12]));   i1 = __vimax3_s32(i1, FI(s[11]), FI(s[14]));
  k0 = __vimax3_s32(k0, FI(s[13]), FI(s[16]));  k1 = __vimax3_s32(k1, FI(s[15]), FI(s[18]));
  i0 = __vimax3_s32(i0, FI(s[17]), FI(s[20]));  i1 = __vimax3_s32(i1, FI(s[19]), FI(s[22]));
  k0 = __vimax3_s32(k0, FI(s[21]), FI(s[24]));  k1 = __vimax3_s32(k1, FI(s[23]), FI(s[26]));
  i0 = __vimax3_s32(i0, FI(s[25]), FI(s[28]));  i1 = __vimax3_s32(i1, FI(s[27]), FI(s[30]));
  i0 = __vimax3_s32(i0, k0, FI(s[29]));         i1 = __vimax3_s32(i1, k1, FI(s[31]));
#undef FI
}
__device__ __forceinline__ void quadmax_i(int& i0, int& i1, int x) {
  i0 = max(i0, __shfl_xor_sync(0xffffffffu, i0, x));
  i1 = max(i1, __shfl_xor_sync(0xffffffffu, i1, x));
}
__device__ __forceinline__ void rowmax_f(const float (&s)[32], int& i0, int& i1) {
  float m0 = fmaxf(s[0], s[1]), m1 = fmaxf(s[2], s[3]);
#pragma unroll
  for (int j = 1; j < 8; j++) {
    m0 = fmaxf(m0, fmaxf(s[4 * j], s[4 * j + 1]));
    m1 = fmaxf(m1, fmaxf(s[4 * j + 2], s[4 * j + 3]));
  }
  m0 = fmaxf(m0, __shfl_xor_sync(0xffffffffu, m0, 1));
  m1 = fmaxf(m1, __shfl_xor_sync(0xffffffffu, m1, 1));
  m0 = fmaxf(m0, __shfl_xor_sync(0xffffffffu, m0, 2));
  m1 = fmaxf(m1, __shfl_xor_sync(0xffffffffu, m1, 2));
  i0 = __float_as_int(m0), i1 = __float_as_int(m1);
}
template <int CH>
__device__ __forceinline__ void exp_rows(const float (&s)[32], uint32_t (&p)[16], int max0, int max1, uint32_t& keep, int never) {
  const float m0 = __int_as_float(max0) * -SM_C, m1 = __int_as_float(max1) * -SM_C;
  float t[32];
#pragma unroll
  for (int c = 0; c <= 16 / CH; c++) {
#pragma unroll
    for (int i = 2 * CH * c; i < 2 * CH * (c + 1) && i < 32; i++) {
      t[i] = fmaf(s[i], SM_C, (i & 2) ? m1 : m0);
      asm volatile("" : "+f"(t[i]));
    }
    if (c > 0) {
#pragma unroll
      for (int i = CH * (c - 1); i < CH * c; i++) {
        t[2 * i] = ex2(t[2 * i]), t[2 * i + 1] = ex2(t[2 * i + 1]);
        asm volatile("" : "+f"(t[2 * i]), "+f"(t[2 * i + 1]));
      }
    }
    if (c > 1) {
#pragma unroll
      for (int i = CH * (c - 2); i < CH * (c - 1); i++) {
        p[i] = pack_bf16(t[2 * i], t[2 * i + 1]);
        asm volatile("" : "+r"(p[i]));
      }
    }
    if (c < 16 / CH) sched_fence(keep, never);
  }
#pragma unroll
  for (int i = 16 - CH; i < 16; i++) p[i] = pack_bf16(t[2 * i], t[2 * i + 1]);
  pin(p);
}
__device__ __forceinline__ void issue_p(float (&o)[28], const uint32_t (&p)[16], uint32_t lo) {
#pragma unroll
  for (int ks = 0; ks < 4; ks++) {
    uint64_t db = mkdesc(lo + ks * 2, HI_KV);
    if (ks == 0) mma_p_init(o, p[0], p[1], p[2], p[3], db);
    else mma_p(o, p[4 * ks], p[4 * ks + 1], p[4 * ks + 2], p[4 * ks + 3], db);
  }
  wg_commit();
}
template <int SUM, int OFF>
__device__ __forceinline__ void normalize(const float (&o)[28], uint32_t (&f)[12]) {
  const float r0 = rcp(o[SUM]), r1 = rcp(o[SUM + 2]);
#pragma unroll
  for (int j = 0; j < 12; j++) {
    float r = (j & 1) ? r1 : r0;
    f[j] = pack_bf16(o[OFF + 2 * j] * r, o[OFF + 2 * j + 1] * r);
  }
}

__global__ void __cluster_dims__(2, 1, 1) __launch_bounds__(384, 1)
swin_attn_kernel(const __grid_constant__ Maps maps, const __nv_bfloat16* __restrict__ rpb, const int* __restrict__ rp_idx, int base, int never) {
  extern __shared__ __align__(1024) uint8_t smem_raw[];
  const uint32_t sb = (uint32_t)__cvta_generic_to_shared(smem_raw);
  const int tid = threadIdx.x;
  const int wg = __shfl_sync(0xffffffffu, tid >> 7, 0);
  const int warp = __shfl_sync(0xffffffffu, (tid >> 5) & 3, 0);
  const int lane = tid & 31;
  const int rank = blockIdx.x & 1;
  const int cl = blockIdx.x >> 1;
  const int ncl = gridDim.x >> 1;
  const uint32_t bars = sb + OFF_BAR;
  int extra = NWIN;
  auto read_ticket = [&]() {
    mbar_wait(bars + B_TICK, 0);
    uint32_t t;
    asm volatile("ld.shared.b32 %0, [%1];" : "=r"(t) : "r"(bars + W_TICK) : "memory");
    extra = base + __shfl_sync(0xffffffffu, t, 0);
  };
  auto window = [&](int v) { return v < base ? v : (v < base + ncl ? extra : NWIN); };
  auto prefetch = [&](int p, int win) {
    if (p < 2) tma5_pf(&maps.x, (((win >> 3) & ~7) + 4 + 4 * rank) & 511, (win * 4 + 2 + 2 * p) & 255);
    else tma5_pf(&maps.mask, 0, 2 * win + rank);
  };
  auto load = [&](int p, int win, int a) {
    if (p < 2)
      tma5_mc(sb + OFF_X + a * STAGE + rank * 12288 + p * 6144, &maps.x, bars + B_XFULL + 8 * a,
              (((win >> 3) & ~7) + 4 + 4 * rank) & 511, (win * 4 + 2 + 2 * p) & 255);
    else tma5_mc(sb + OFF_MASK + a * STAGE + rank * 4096, &maps.mask, bars + B_XFULL + 8 * a, 0, 2 * win + rank);
  };
  auto load_wkv = [&](int b) {
    tma3(sb + OFF_KV + (b < 3 ? b * 12288 : STAGE + (b - 3) * 12288), &maps.wqkv, bars + B_WKV + 8 * (b >> 1), 0,
         (b < 3 ? 6 : 9) + b + 3 * rank);
  };
  auto startup_loads = [&]() {
    if ((sb & 0x3FFFF) != SM_BASE) __trap();
    if (blockIdx.x == 0) asm volatile("st.relaxed.gpu.global.u32 [%0], 0;" ::"l"(&g_ticket) : "memory");
    mbar_expect_tx(bars + B_XFULL, X_BYTES);
    mbar_expect_tx(bars + B_M0, M_BYTES);
    mbar_expect_tx(bars + B_WKV + 8, 24576);
    load_wkv(2);
    load_wkv(3);
    tma5_mc(sb + OFF_MASK + rank * 4096, &maps.mask, bars + B_M0, 0, 2 * cl + rank);
    mbar_expect_tx(bars + B_WQ, 36864);
    for (int nb = 0; nb < 3; nb++) tma3(sb + OFF_WQ + nb * 12288, &maps.wqkv, bars + B_WQ, 0, 3 * rank + nb);
    mbar_expect_tx(bars + B_WKV + 16, 24576);
    load_wkv(4);
    load_wkv(5);
    mbar_expect_tx(bars + B_XFULL + 8, X_BYTES + M_BYTES);
    for (int p = 0; p < 3; p++) load(p, cl + ncl, 1);
    mbar_expect_tx(bars + B_TICK, 4);
    mbar_expect_tx(bars + B_WO, 36864);
    tma3(sb + OFF_WO, &maps.wo, bars + B_WO, 96 * rank, 3 * rank);
    for (int nb = 0; nb < 3; nb++)
      asm volatile("cp.async.bulk.tensor.5d.shared::cluster.global.mbarrier::complete_tx::bytes [%0], [%1, {%3, 0, 0, 0, %4}], [%2];" ::"r"(
                       sb + OFF_WO + 18432 + nb * 6144), "l"(&maps.wop), "r"(bars + B_WO), "r"(96 * rank + 32 * nb), "r"(3 * (rank ^ 1))
                   : "memory");
  };
  if (wg == KV_WG && warp == 3) {
    if (elect()) {
#pragma unroll
      for (int k = 0; k < 15; k++) mbar_init(bars + 8 * k, (k >> 1) == B_OEMPTY / 16 ? 4 : 1);
      asm volatile("fence.mbarrier_init.release.cluster;" ::: "memory");
    }
    __syncwarp();
  }
  asm volatile("barrier.cluster.arrive.relaxed.aligned;" ::: "memory");

  if (wg == KV_WG) {
    if (warp == 3 && elect()) {
      fence_async();
      mbar_expect_tx(bars + B_WKV, 24576);
      load_wkv(0);
      load_wkv(1);
    }
    __syncwarp();
    asm volatile("barrier.cluster.wait.aligned;" ::: "memory");
    if (elect()) {
      if (warp < 2) load(warp, cl, 0);
      else if (warp == 3) startup_loads();
    }
    __syncwarp();
    asm volatile("setmaxnreg.inc.sync.aligned.u32 216;");
    uint32_t w[3][48];
    auto load_frags = [&](int s) {
      const uint32_t la = sb + OFF_KV + (warp >> 1) * 12288 + (8 * (lane >> 4) + (lane & 7)) * 64 +
                          (((2 * (warp & 1) + ((lane >> 3) & 1)) ^ ((lane & 7) >> 1)) << 4);
      mbar_wait(bars + B_WKV + 8 * s, 0);
#pragma unroll
      for (int ks = 0; ks < 12; ks++)
        asm volatile("ldmatrix.sync.aligned.m8n8.x4.trans.shared.b16 {%0,%1,%2,%3}, [%4];"
                     : "=r"(w[s][4 * ks]), "=r"(w[s][4 * ks + 1]), "=r"(w[s][4 * ks + 2]), "=r"(w[s][4 * ks + 3])
                     : "r"(la + s * 24576 + (s == 2 || (s == 1 && warp >= 2) ? STAGE - 36864 : 0) + ks * 1024)
                     : "memory");
    };
    load_frags(0);
    uint32_t sta[4];
#pragma unroll
    for (int jj = 0; jj < 4; jj++) {
      sta[jj] = sb + OFF_KV + (16 * warp + (lane & 15)) * 128 + (((2 * jj + (lane >> 4)) ^ (lane & 7)) << 4);
      asm volatile("" : "+r"(sta[jj]));
    }
    const uint32_t xe_rem = mapa(bars + B_XEMPTY, rank ^ 1);
    const uint32_t v1off = warp > 0 ? 1024 : 0;

#define SF sched_fence(sta[0], never)
    float acc[32];
    uint32_t pk[16];
    auto store = [&](uint32_t off) {
#pragma unroll
      for (int jj = 0; jj < 4; jj++) stsm4(sta[jj] + off, pk[4 * jj], pk[4 * jj + 1], pk[4 * jj + 2], pk[4 * jj + 3]);
    };
    auto issue = [&](int s, uint32_t xd, bool st, uint32_t off) {
#pragma unroll
      for (int ks = 0; ks < 12; ks++) {
        uint64_t db = mkdesc(xd + (((ks >> 2) * 1024 + (ks & 3) * 32) >> 4), HI_X);
        if (ks == 0) mma_kv_init(acc, w[s][0], w[s][1], w[s][2], w[s][3], db);
        else mma_kv(acc, w[s][4 * ks], w[s][4 * ks + 1], w[s][4 * ks + 2], w[s][4 * ks + 3], db);
        if (ks == 1 && st) {
          __syncwarp();
          store(off);
          __syncwarp();
        }
      }
      wg_commit();
    };
    auto convert = [&]() {
      wg_wait<0>();
      pin(acc);
#pragma unroll
      for (int j = 0; j < 16; j++) pk[j] = pack_bf16(acc[2 * j], acc[2 * j + 1]);
      pin(pk);
    };

    mbar_wait(bars + B_XFULL, 0);
    wg_fence();
    issue(0, LO_X, false, 0);
    load_frags(1);
    int nxt = cl + ncl;
    uint32_t ph = 0;
    uint32_t ticket = 0;
    auto step = [&](auto A) -> bool {
      constexpr int a = decltype(A)::value;
      constexpr uint32_t xd = LO_X + a * (STAGE >> 4);
      if (nxt + ncl >= base && nxt < base) read_ticket();
      const bool more = window(nxt) < NWIN;
      const int wn2 = window(nxt + ncl);
      convert();
      wg_fence();
      SF;
      tok_wait<T2>();
      issue(1, xd, true, a * STAGE);
      tok_pass<T3>();
      if (warp < 3 && wn2 < NWIN && elect()) prefetch(warp, wn2);
      __syncwarp();
      const bool first = a == 0 && nxt == cl + ncl;
      convert();
      SF;
      if (!first) tok_wait<T7>();
      store(a * STAGE + 8192);
      fence_async();
      if (first) {
        load_frags(2);
        asm volatile("bar.sync %0, 128;" ::"n"((int)BAR_STAGE) : "memory");
        asm volatile("st.shared.v4.b32 [%0], {%1,%1,%1,%1};" ::"r"(sb + OFF_KV + (warp >> 1) * STAGE + 144 * 128 + (tid & 63) * 16), "r"(0x3F803F80u) : "memory");
      }
      wg_fence();
      tok_wait<T5>();
      issue(2, xd, false, 0);
      tok_pass<T6>();
      if (!more) {
        convert();
        store(a * STAGE + 16384 + v1off);
        fence_async();
        return false;
      }
      mbar_wait(bars + B_XFULL + 8 * (a ^ 1), a ? ph ^ 1 : ph);
      convert();
      wg_fence();
      SF;
      tok_wait<T0>();
      if (tid == KV_WG * 128 && wn2 < NWIN) mbar_arrive_cluster(xe_rem + 8 * a);
      issue(0, LO_X + (a ^ 1) * (STAGE >> 4), true, a * STAGE + 16384 + v1off);
      tok_pass<T1>();
      fence_async();
      nxt += ncl;
      if (wn2 < NWIN) {
        mbar_wait(bars + B_XEMPTY + 8 * a, ph);
        if (elect()) {
          if (warp < 3) {
            load(warp, wn2, a);
          } else {
            mbar_expect_tx(bars + B_XFULL + 8 * a, X_BYTES + M_BYTES);
            if (rank == 0 && nxt + 3 * ncl >= base) {
              if (nxt + 2 * ncl < base) {
                asm volatile("atom.global.inc.u32 %0, [%1], %2;" : "=r"(ticket) : "l"(&g_ticket), "r"(ncl - 1) : "memory");
              } else if (nxt + ncl < base) {
#pragma unroll
                for (int r = 0; r < 2; r++)
                  asm volatile("st.async.shared::cluster.mbarrier::complete_tx::bytes.b32 [%0], %1, [%2];" ::"r"(mapa(bars + W_TICK, r)),
                               "r"(ticket), "r"(mapa(bars + B_TICK, r))
                               : "memory");
              }
            }
          }
        }
        __syncwarp();
      }
      return true;
    };
    while (step(IC<0>{}) && step(IC<1>{})) ph ^= 1;
    tok_wait<T0>();
    tok_pass<T1>();
    tok_wait<T2>();
    tok_pass<T3>();
    tok_wait<T7>();
    tok_wait<T5>();
  } else {
    const int a = wg - (KV_WG == 0 ? 1 : 0);
    const int g = lane >> 2, q = lane & 3;
    const uint32_t bar = bars + 8 * a;
    if (a == 0) {
      tok_pass<T2>();
      tok_pass<T5>();
    }
    asm volatile("setmaxnreg.dec.sync.aligned.u32 144;");
    uint32_t braw[32];
    {
      const int ty = 4 * (warp >> 1) + (g >> 1), tx = 4 * (warp & 1) + (g & 1);
      const int* ip = rp_idx + (ty * 8 + tx) * 64 + 8 * q;
#pragma unroll
      for (int c = 0; c < 8; c++)
        asm volatile("ld.global.nc.v4.b32 {%0,%1,%2,%3}, [%4];"
                     : "=r"(braw[4 * c]), "=r"(braw[4 * c + 1]), "=r"(braw[4 * c + 2]), "=r"(braw[4 * c + 3])
                     : "l"(ip + (c >> 2) * 128 + ((c >> 1) & 1) * 32 + (c & 1) * 4));
      const int e = a * 128 + (tid & 127);
      uint32_t v = 0;
      if (e < 225) asm volatile("ld.global.nc.b32 %0, [%1];" : "=r"(v) : "l"(reinterpret_cast<const uint32_t*>(rpb) + e * 2 + rank));
      asm volatile("st.shared.b32 [%0], %1;" ::"r"(sb + OFF_RPB + e * 4), "r"(v) : "memory");
      tok_wait<BAR_BIAS>();
#pragma unroll
      for (int j = 0; j < 32; j++)
        asm volatile("ld.shared.b32 %0, [%1];" : "=r"(braw[j]) : "r"(sb + OFF_RPB + braw[j] * 4) : "memory");
    }
    asm volatile("barrier.cluster.wait.aligned;" ::: "memory");

    const int mrow = 16 * warp + (g >> 1) + 4 * (g & 1);
#undef SF
#define SF sched_fence(mk_addr, never)
    uint32_t mk_addr = sb + OFF_MASK + a * STAGE + mrow * 128 + ((q ^ (mrow & 7)) << 4);
    const uint32_t ostage = sb + OFF_OIN + a * STAGE + warp * 3072;
    const uint32_t ost = ostage + ((lane >> 3) & 1) * 1536 + (lane & 7) * 64 + (((lane >> 4) ^ ((lane & 7) >> 1)) << 4);
    const uint32_t oin_rem = mapa(ostage + g * 64 + ((q ^ (g >> 1)) << 4), rank ^ 1);
    const uint32_t bar_rem = mapa(bar, rank ^ 1);

    auto store_out = [&](int win) {
      fence_async();
      __syncwarp();
      if (elect()) {
        int yy = (((win >> 3) & ~7) + 4 + 4 * (warp >> 1)) & 511;
        int xh = (win * 4 + 2 + 2 * (warp & 1)) & 255;
        asm volatile("cp.async.bulk.tensor.5d.global.shared::cta.bulk_group [%0, {0, 0, %2, %3, %4}], [%1];" ::"l"(&maps.out), "r"(ostage),
                     "r"(yy), "r"(3 * rank), "r"(xh)
                     : "memory");
        asm volatile("cp.async.bulk.commit_group;" ::: "memory");
      }
      __syncwarp();
    };
    auto release_oin = [&]() {
      if (elect()) {
        asm volatile("cp.async.bulk.wait_group.read 0;" ::: "memory");
        if (warp == 0) mbar_expect_tx(bar + B_OFULL, O_BYTES);
        mbar_arrive_cluster(bar_rem + B_OEMPTY);
      }
      __syncwarp();
    };
    float qa[48];
    uint32_t bias0[16], bias1[16];
    uint32_t mk[16];
    auto load_mask = [&](uint32_t z) {
#pragma unroll
      for (int c = 0; c < 4; c++)
        lds128((c & 1 ? mk_addr ^ (64 + z) : mk_addr) + (c >> 1) * 1024, mk[4 * c], mk[4 * c + 1], mk[4 * c + 2], mk[4 * c + 3]);
    };
    auto clamp_mask = [&]() {
      SF;
#pragma unroll
      for (int j = 0; j < 16; j++) asm("max.NaN.bf16x2 %0, %0, %1;" : "+r"(mk[j]) : "r"(0xFD80FD80u));
      pin(mk);
    };
    auto issue_q = [&](uint32_t ua, bool tok, int win) {
#pragma unroll
      for (int ks = 0; ks < 12; ks++) {
        if (ks == Q_SPLIT && tok) {
          tok_pass<T4>();
          store_out(win);
          tok_wait<T7>();
          wg_fence();
        }
        uint64_t da = mkdesc(ua + LO_X + (((ks >> 2) * 1024 + (ks & 3) * 32) >> 4), HI_X);
        uint64_t db = mkdesc(LO_WQ + ks * 64, HI_W);
        if (ks == 0) mma_q_init(qa, da, db);
        else mma_q(qa, da, db);
      }
      wg_commit();
      if (tok) tok_pass<T5>();
    };
#pragma unroll
    for (int j = 0; j < 16; j++) {
      const uint32_t b0 = braw[2 * j], b1 = braw[2 * j + 1];
      bias0[j] = pack_bias(__uint_as_float(b0 << 16), __uint_as_float(b1 << 16));
      bias1[j] = pack_bias(__uint_as_float(b0 & 0xffff0000u), __uint_as_float(b1 & 0xffff0000u));
    }
    pin(bias0);
    pin(bias1);
    SF;
    mbar_wait(bars + B_WQ, 0);
    wg_fence();
    if (a == 0) tok_wait<T3>();
    else tok_wait<T1>();
    issue_q(a * (STAGE >> 4), false, 0);
    if (a == 0) mbar_wait(bars + B_M0, 0);
    else tok_pass<T2>();
    load_mask(0);
    if (a == 1) {
      tok_wait<T3>();
      tok_pass<T4>();
      tok_pass<T5>();
      tok_wait<T7>();
    }
    clamp_mask();
    uint32_t ph = 0;
    int win = cl + a * ncl;
    for (;; win += 2 * ncl, ph ^= 1) {
      const uint32_t ua = a * (STAGE >> 4) + (win >> 20);
      const uint32_t kd = ua + LO_KV;
      float s0[32], s1[32];
      wg_wait<0>();
      pin(qa);
      uint32_t q0[12], q1[12];
#pragma unroll
      for (int j = 0; j < 12; j++) q0[j] = pack_bf16(qa[2 * j], qa[2 * j + 1]);
#pragma unroll
      for (int j = 0; j < 12; j++) q1[j] = pack_bf16(qa[24 + 2 * j], qa[25 + 2 * j]);
      pin(q0);
      pin(q1);
      s_init(s0, mk, bias0);
      s_init(s1, mk, bias1);
      wg_fence();
      tok_wait<T6>();
#pragma unroll
      for (int ks = 0; ks < 3; ks++)
        mma_s(s0, q0[4 * ks], q0[4 * ks + 1], q0[4 * ks + 2], q0[4 * ks + 3], mkdesc(kd + ks * 128, HI_KV));
      wg_commit();
#pragma unroll
      for (int ks = 0; ks < 3; ks++)
        mma_s(s1, q1[4 * ks], q1[4 * ks + 1], q1[4 * ks + 2], q1[4 * ks + 3], mkdesc(kd + (3 + ks) * 128, HI_KV));
      wg_commit();
      tok_pass<T0>();
      release_oin();
      int x0, x1, y0, y1;
      uint32_t p0[16], p1[16];
      wg_wait<1>();
      pin(s0);
      pin(q0);
      rowmax_i(s0, x0, x1);
      quadmax_i(x0, x1, 1);
      wg_wait<0>();
      pin(s1);
      pin(q1);
      rowmax_i(s1, y0, y1);
      quadmax_i(x0, x1, 2);
      quadmax_i(y0, y1, 1);
      quadmax_i(y0, y1, 2);
      if (__builtin_expect(__any_sync(0xffffffffu, (x0 | x1 | y0 | y1) < 0), 0)) {
        rowmax_f(s0, x0, x1);
        rowmax_f(s1, y0, y1);
      }
      exp_rows<EXP_CH>(s0, p0, x0, x1, mk_addr, never);
      exp_rows<EXP_CH>(s1, p1, y0, y1, mk_addr, never);
      float o0[28], o1[28];
      wg_fence();
      SF;
      tok_wait<T4>();
      issue_p(o0, p0, kd + ((96 * 128) >> 4));
      issue_p(o1, p1, kd + ((144 * 128) >> 4));
      tok_pass<T7>();
      mbar_wait(bar + B_OEMPTY, ph);
      uint32_t f0[12], f1[12];
      wg_wait<1>();
      pin(o0);
      pin(p0);
      normalize<24, 0>(o0, f0);
      st_async<0>(oin_rem, bar_rem + B_OFULL, f0[0], f0[2], f0[4], f0[6]);
      st_async<1536>(oin_rem, bar_rem + B_OFULL, f0[1], f0[3], f0[5], f0[7]);
      wg_wait<0>();
      pin(o1);
      pin(p1);
      normalize<0, 4>(o1, f1);
      st_async<512>(oin_rem, bar_rem + B_OFULL, f0[8], f0[10], f1[0], f1[2]);
      st_async<2048>(oin_rem, bar_rem + B_OFULL, f0[9], f0[11], f1[1], f1[3]);
      st_async<1024>(oin_rem, bar_rem + B_OFULL, f1[4], f1[6], f1[8], f1[10]);
      st_async<2560>(oin_rem, bar_rem + B_OFULL, f1[5], f1[7], f1[9], f1[11]);
      pin(f0);
      pin(f1);
      float (&oa)[48] = qa;
      bool last = false;
      bool fin = false;
      if ((unsigned)(win - 2 * ncl) >= (unsigned)(base - 4 * ncl)) {
        if (win < 2 * ncl) {
          mbar_wait(bars + B_WO, 0);
        } else {
          read_ticket();
          last = window(win + ncl) >= NWIN;
          fin = window(win + 2 * ncl) >= NWIN;
        }
      }
      if (!last) tok_wait<T1>();
      SF;
#pragma unroll
      for (int j = 8; j < 12; j++) f0[j] += never;
#pragma unroll
      for (int j = 0; j < 12; j++) f1[j] += never;
      pin(f0);
      pin(f1);
      wg_fence();
#pragma unroll
      for (int ks = 0; ks < 3; ks++) {
        uint64_t db = mkdesc(LO_WO + ks * 64, HI_W);
        if (ks == 0) mma_o_init(oa, f0[0], f0[1], f0[2], f0[3], db);
        else mma_o(oa, f0[4 * ks], f0[4 * ks + 1], f0[4 * ks + 2], f0[4 * ks + 3], db);
      }
#pragma unroll
      for (int ks = 0; ks < 3; ks++)
        mma_o(oa, f1[4 * ks], f1[4 * ks + 1], f1[4 * ks + 2], f1[4 * ks + 3], mkdesc(LO_WO + (3 + ks) * 64, HI_W));
      mbar_wait(bar + B_OFULL, ph);
      asm volatile("fence.proxy.async::generic.acquire.sync_restrict::shared::cluster.cluster;" ::: "memory");
      wg_fence();
#pragma unroll
      for (int ks = 0; ks < 6; ks++)
        mma_q(oa, mkdesc(ua + LO_O + (((ks >> 1) * 512 + (ks & 1) * 32) >> 4), HI_O), mkdesc(LO_WO + (18432 >> 4) + ks * 64, HI_W));
      wg_commit();
      if (!last) tok_pass<T2>();
      load_mask(win >> 20);
      wg_wait<0>();
      pin(oa);
      pin(f0);
      pin(f1);
#pragma unroll
      for (int jj = 0; jj < 6; jj++)
        stsm4((jj & 1 ? ost ^ (32 + (win >> 20)) : ost) + (jj >> 1) * 512, pack_bf16(oa[8 * jj], oa[8 * jj + 1]), pack_bf16(oa[8 * jj + 2], oa[8 * jj + 3]),
              pack_bf16(oa[8 * jj + 4], oa[8 * jj + 5]), pack_bf16(oa[8 * jj + 6], oa[8 * jj + 7]));
      if (fin) {
        if (!last) {
          tok_wait<T3>();
          tok_pass<T4>();
          tok_pass<T5>();
          tok_wait<T7>();
        }
        break;
      }
      wg_fence();
      tok_wait<T3>();
      issue_q(ua, true, win);
      clamp_mask();
    }
    store_out(window(win));
    asm volatile("cp.async.bulk.wait_group.read 0;" ::: "memory");
    __syncwarp();
  }
}

typedef CUresult (*EncodeFn)(CUtensorMap*, CUtensorMapDataType, cuuint32_t, void*, const cuuint64_t*, const cuuint64_t*,
                             const cuuint32_t*, const cuuint32_t*, CUtensorMapInterleave, CUtensorMapSwizzle,
                             CUtensorMapL2promotion, CUtensorMapFloatOOBfill);

void encode_map(EncodeFn encode, CUtensorMap* m, void* p, int rank, const cuuint64_t* dim, const cuuint64_t* str,
                const cuuint32_t* box, CUtensorMapSwizzle sw) {
  const cuuint32_t es[5] = {1, 1, 1, 1, 1};
  CUresult r = encode(m, CU_TENSOR_MAP_DATA_TYPE_BFLOAT16, rank, p, dim, str, box, es, CU_TENSOR_MAP_INTERLEAVE_NONE, sw,
                      CU_TENSOR_MAP_L2_PROMOTION_L2_128B, CU_TENSOR_MAP_FLOAT_OOB_FILL_NONE);
  if (r != CUDA_SUCCESS) fprintf(stderr, "tensor map encode failed: %d\n", (int)r);
}

}

extern "C" void kernel_launch(void* const* d_in, const int* in_sizes, int n_in, void* d_out, int out_size) {
  static EncodeFn encode = nullptr;
  static int grid = 0;
  if (!encode) {
    cudaDriverEntryPointQueryResult qr;
    void* fn = nullptr;
    cudaGetDriverEntryPoint("cuTensorMapEncodeTiled", &fn, cudaEnableDefault, &qr);
    encode = (EncodeFn)fn;
    cudaFuncSetAttribute(swin_attn_kernel, cudaFuncAttributeMaxDynamicSharedMemorySize, SMEM_BYTES);
    cudaLaunchConfig_t cfg = {};
    cfg.gridDim = dim3(132);
    cfg.blockDim = dim3(384);
    cfg.dynamicSmemBytes = SMEM_BYTES;
    cudaLaunchAttribute at;
    at.id = cudaLaunchAttributeClusterDimension;
    at.val.clusterDim.x = 2;
    at.val.clusterDim.y = 1;
    at.val.clusterDim.z = 1;
    cfg.attrs = &at;
    cfg.numAttrs = 1;
    int ncl = 0;
    if (cudaOccupancyMaxActiveClusters(&ncl, swin_attn_kernel, &cfg) != cudaSuccess || ncl < 1) {
      (void)cudaGetLastError();
      ncl = 66;
    }
    if (ncl > 256) ncl = 256;
    grid = 2 * ncl;
  }
  Maps maps;
  {
    const cuuint64_t dim[5] = {64, 2, 512, 3, 256}, str[4] = {384, 512 * 384, 128, 768};
    const cuuint32_t box[5] = {64, 2, 4, 3, 2};
    encode_map(encode, &maps.x, d_in[0], 5, dim, str, box, CU_TENSOR_MAP_SWIZZLE_128B);
  }
  {
    const cuuint64_t dim[5] = {64, 4, 2, 4, 8192}, str[4] = {1024, 128, 256, 4096};
    const cuuint32_t box[5] = {64, 4, 2, 4, 1};
    encode_map(encode, &maps.mask, d_in[5], 5, dim, str, box, CU_TENSOR_MAP_SWIZZLE_128B);
  }
  {
    const cuuint64_t dim[5] = {32, 2, 512, 6, 256}, str[4] = {384, 512 * 384, 64, 768};
    const cuuint32_t box[5] = {32, 2, 4, 3, 2};
    encode_map(encode, &maps.out, d_out, 5, dim, str, box, CU_TENSOR_MAP_SWIZZLE_64B);
  }
  {
    const cuuint64_t dim[3] = {32, 192, 18}, str[2] = {576 * 2, 64};
    const cuuint32_t box[3] = {32, 192, 1};
    encode_map(encode, &maps.wqkv, d_in[1], 3, dim, str, box, CU_TENSOR_MAP_SWIZZLE_64B);
    const cuuint64_t dim2[3] = {32, 192, 6}, str2[2] = {192 * 2, 64};
    const cuuint32_t box2[3] = {32, 96, 3};
    encode_map(encode, &maps.wo, d_in[2], 3, dim2, str2, box2, CU_TENSOR_MAP_SWIZZLE_64B);
    const cuuint64_t dim3_[5] = {192, 2, 4, 4, 6}, str3[4] = {384, 8 * 384, 2 * 384, 32 * 384};
    const cuuint32_t box3[5] = {32, 2, 4, 4, 3};
    encode_map(encode, &maps.wop, d_in[2], 5, dim3_, str3, box3, CU_TENSOR_MAP_SWIZZLE_64B);
  }
  swin_attn_kernel<<<grid, 384, SMEM_BYTES>>>(maps, (const __nv_bfloat16*)d_in[3], (const int*)d_in[4], NWIN / (grid / 2) * (grid / 2), 0);
}
```

```cpp
#include <cuda_runtime.h>
#include <cuda_bf16.h>
#include <cuda.h>
#include <stdint.h>
#include <stdio.h>

namespace {

constexpr int NWIN = 4096;
constexpr int KV_WG = 0;
#define QS 4
constexpr int Q_SPLIT = QS;
#define STA 1
#define ECH 4
constexpr int EXP_CH = ECH;

constexpr uint32_t SM_BASE  = 1024;
constexpr uint32_t OFF_WQ   = 0;
constexpr uint32_t OFF_WO   = 36864;
constexpr uint32_t STAGE    = 70656;
constexpr uint32_t OFF_X    = 73728;
constexpr uint32_t X_BYTES  = 24576;
constexpr uint32_t OFF_MASK = OFF_X + X_BYTES;
constexpr uint32_t M_BYTES  = 8192;
constexpr uint32_t OFF_KV   = OFF_MASK + M_BYTES;
constexpr uint32_t OFF_OIN  = OFF_KV + 25600;
constexpr uint32_t O_BYTES  = 12288;
constexpr uint32_t OFF_BAR  = 215040;
constexpr uint32_t OFF_RPB  = OFF_BAR + 1024;
constexpr uint32_t SMEM_BYTES = OFF_RPB + 1024;
constexpr uint32_t B_XFULL = 0, B_XEMPTY = 16, B_OFULL = 32, B_OEMPTY = 48, B_WKV = 64  , B_WQ = 88, B_WO = 96,
                   B_TICK = 104, B_M0 = 112, W_TICK = 120;
enum { T0 = 1, T1, T2, T3, T4, T5, T6, T7, BAR_BIAS, BAR_STAGE };

__device__ unsigned int g_ticket;

template <int V> struct IC { static constexpr int value = V; };
struct Maps { CUtensorMap x, mask, out, wqkv, wo, wop; };

__device__ __forceinline__ void mma_q_init(float (&d)[48], uint64_t descA, uint64_t descB) {
  asm volatile("wgmma.mma_async.sync.aligned.m64n96k16.f32.bf16.bf16 {%0, %1, %2, %3, %4, %5, %6, %7, %8, %9, %10, %11, %12, %13, %14, %15, %16, %17, %18, %19, %20, %21, %22, %23, %24, %25, %26, %27, %28, %29, %30, %31, %32, %33, %34, %35, %36, %37, %38, %39, %40, %41, %42, %43, %44, %45, %46, %47}, "
    "%48, %49, 0, 1, 1, 0, 1;"
    : "+f"(d[0]), "+f"(d[1]), "+f"(d[2]), "+f"(d[3]), "+f"(d[4]), "+f"(d[5]), "+f"(d[6]), "+f"(d[7]), "+f"(d[8]), "+f"(d[9]), "+f"(d[10]), "+f"(d[11]), "+f"(d[12]), "+f"(d[13]), "+f"(d[14]), "+f"(d[15]), "+f"(d[16]), "+f"(d[17]), "+f"(d[18]), "+f"(d[19]), "+f"(d[20]), "+f"(d[21]), "+f"(d[22]), "+f"(d[23]), "+f"(d[24]), "+f"(d[25]), "+f"(d[26]), "+f"(d[27]), "+f"(d[28]), "+f"(d[29]), "+f"(d[30]), "+f"(d[31]), "+f"(d[32]), "+f"(d[33]), "+f"(d[34]), "+f"(d[35]), "+f"(d[36]), "+f"(d[37]), "+f"(d[38]), "+f"(d[39]), "+f"(d[40]), "+f"(d[41]), "+f"(d[42]), "+f"(d[43]), "+f"(d[44]), "+f"(d[45]), "+f"(d[46]), "+f"(d[47])
    : "l"(descA), "l"(descB));
}
__device__ __forceinline__ void mma_q(float (&d)[48], uint64_t descA, uint64_t descB) {
  asm volatile("wgmma.mma_async.sync.aligned.m64n96k16.f32.bf16.bf16 {%0, %1, %2, %3, %4, %5, %6, %7, %8, %9, %10, %11, %12, %13, %14, %15, %16, %17, %18, %19, %20, %21, %22, %23, %24, %25, %26, %27, %28, %29, %30, %31, %32, %33, %34, %35, %36, %37, %38, %39, %40, %41, %42, %43, %44, %45, %46, %47}, "
    "%48, %49, 1, 1, 1, 0, 1;"
    : "+f"(d[0]), "+f"(d[1]), "+f"(d[2]), "+f"(d[3]), "+f"(d[4]), "+f"(d[5]), "+f"(d[6]), "+f"(d[7]), "+f"(d[8]), "+f"(d[9]), "+f"(d[10]), "+f"(d[11]), "+f"(d[12]), "+f"(d[13]), "+f"(d[14]), "+f"(d[15]), "+f"(d[16]), "+f"(d[17]), "+f"(d[18]), "+f"(d[19]), "+f"(d[20]), "+f"(d[21]), "+f"(d[22]), "+f"(d[23]), "+f"(d[24]), "+f"(d[25]), "+f"(d[26]), "+f"(d[27]), "+f"(d[28]), "+f"(d[29]), "+f"(d[30]), "+f"(d[31]), "+f"(d[32]), "+f"(d[33]), "+f"(d[34]), "+f"(d[35]), "+f"(d[36]), "+f"(d[37]), "+f"(d[38]), "+f"(d[39]), "+f"(d[40]), "+f"(d[41]), "+f"(d[42]), "+f"(d[43]), "+f"(d[44]), "+f"(d[45]), "+f"(d[46]), "+f"(d[47])
    : "l"(descA), "l"(descB));
}
__device__ __forceinline__ void mma_kv_init(float (&d)[32], uint32_t a0, uint32_t a1, uint32_t a2, uint32_t a3, uint64_t descB) {
  asm volatile("wgmma.mma_async.sync.aligned.m64n64k16.f32.bf16.bf16 {%0, %1, %2, %3, %4, %5, %6, %7, %8, %9, %10, %11, %12, %13, %14, %15, %16, %17, %18, %19, %20, %21, %22, %23, %24, %25, %26, %27, %28, %29, %30, %31}, "
    "{%32, %33, %34, %35}, %36, 0, 1, 1, 0;"
    : "+f"(d[0]), "+f"(d[1]), "+f"(d[2]), "+f"(d[3]), "+f"(d[4]), "+f"(d[5]), "+f"(d[6]), "+f"(d[7]), "+f"(d[8]), "+f"(d[9]), "+f"(d[10]), "+f"(d[11]), "+f"(d[12]), "+f"(d[13]), "+f"(d[14]), "+f"(d[15]), "+f"(d[16]), "+f"(d[17]), "+f"(d[18]), "+f"(d[19]), "+f"(d[20]), "+f"(d[21]), "+f"(d[22]), "+f"(d[23]), "+f"(d[24]), "+f"(d[25]), "+f"(d[26]), "+f"(d[27]), "+f"(d[28]), "+f"(d[29]), "+f"(d[30]), "+f"(d[31])
    : "r"(a0), "r"(a1), "r"(a2), "r"(a3), "l"(descB));
}
__device__ __forceinline__ void mma_kv(float (&d)[32], uint32_t a0, uint32_t a1, uint32_t a2, uint32_t a3, uint64_t descB) {
  asm volatile("wgmma.mma_async.sync.aligned.m64n64k16.f32.bf16.bf16 {%0, %1, %2, %3, %4, %5, %6, %7, %8, %9, %10, %11, %12, %13, %14, %15, %16, %17, %18, %19, %20, %21, %22, %23, %24, %25, %26, %27, %28, %29, %30, %31}, "
    "{%32, %33, %34, %35}, %36, 1, 1, 1, 0;"
    : "+f"(d[0]), "+f"(d[1]), "+f"(d[2]), "+f"(d[3]), "+f"(d[4]), "+f"(d[5]), "+f"(d[6]), "+f"(d[7]), "+f"(d[8]), "+f"(d[9]), "+f"(d[10]), "+f"(d[11]), "+f"(d[12]), "+f"(d[13]), "+f"(d[14]), "+f"(d[15]), "+f"(d[16]), "+f"(d[17]), "+f"(d[18]), "+f"(d[19]), "+f"(d[20]), "+f"(d[21]), "+f"(d[22]), "+f"(d[23]), "+f"(d[24]), "+f"(d[25]), "+f"(d[26]), "+f"(d[27]), "+f"(d[28]), "+f"(d[29]), "+f"(d[30]), "+f"(d[31])
    : "r"(a0), "r"(a1), "r"(a2), "r"(a3), "l"(descB));
}
__device__ __forceinline__ void mma_s(float (&d)[32], uint32_t a0, uint32_t a1, uint32_t a2, uint32_t a3, uint64_t descB) {
  asm volatile("wgmma.mma_async.sync.aligned.m64n64k16.f32.bf16.bf16 {%0, %1, %2, %3, %4, %5, %6, %7, %8, %9, %10, %11, %12, %13, %14, %15, %16, %17, %18, %19, %20, %21, %22, %23, %24, %25, %26, %27, %28, %29, %30, %31}, "
    "{%32, %33, %34, %35}, %36, 1, 1, 1, 1;"
    : "+f"(d[0]), "+f"(d[1]), "+f"(d[2]), "+f"(d[3]), "+f"(d[4]), "+f"(d[5]), "+f"(d[6]), "+f"(d[7]), "+f"(d[8]), "+f"(d[9]), "+f"(d[10]), "+f"(d[11]), "+f"(d[12]), "+f"(d[13]), "+f"(d[14]), "+f"(d[15]), "+f"(d[16]), "+f"(d[17]), "+f"(d[18]), "+f"(d[19]), "+f"(d[20]), "+f"(d[21]), "+f"(d[22]), "+f"(d[23]), "+f"(d[24]), "+f"(d[25]), "+f"(d[26]), "+f"(d[27]), "+f"(d[28]), "+f"(d[29]), "+f"(d[30]), "+f"(d[31])
    : "r"(a0), "r"(a1), "r"(a2), "r"(a3), "l"(descB));
}
__device__ __forceinline__ void mma_p_init(float (&d)[28], uint32_t a0, uint32_t a1, uint32_t a2, uint32_t a3, uint64_t descB) {
  asm volatile("wgmma.mma_async.sync.aligned.m64n56k16.f32.bf16.bf16 {%0, %1, %2, %3, %4, %5, %6, %7, %8, %9, %10, %11, %12, %13, %14, %15, %16, %17, %18, %19, %20, %21, %22, %23, %24, %25, %26, %27}, "
    "{%28, %29, %30, %31}, %32, 0, 1, 1, 0;"
    : "=f"(d[0]), "=f"(d[1]), "=f"(d[2]), "=f"(d[3]), "=f"(d[4]), "=f"(d[5]), "=f"(d[6]), "=f"(d[7]), "=f"(d[8]), "=f"(d[9]), "=f"(d[10]), "=f"(d[11]), "=f"(d[12]), "=f"(d[13]), "=f"(d[14]), "=f"(d[15]), "=f"(d[16]), "=f"(d[17]), "=f"(d[18]), "=f"(d[19]), "=f"(d[20]), "=f"(d[21]), "=f"(d[22]), "=f"(d[23]), "=f"(d[24]), "=f"(d[25]), "=f"(d[26]), "=f"(d[27])
    : "r"(a0), "r"(a1), "r"(a2), "r"(a3), "l"(descB));
}
__device__ __forceinline__ void mma_p(float (&d)[28], uint32_t a0, uint32_t a1, uint32_t a2, uint32_t a3, uint64_t descB) {
  asm volatile("wgmma.mma_async.sync.aligned.m64n56k16.f32.bf16.bf16 {%0, %1, %2, %3, %4, %5, %6, %7, %8, %9, %10, %11, %12, %13, %14, %15, %16, %17, %18, %19, %20, %21, %22, %23, %24, %25, %26, %27}, "
    "{%28, %29, %30, %31}, %32, 1, 1, 1, 0;"
    : "+f"(d[0]), "+f"(d[1]), "+f"(d[2]), "+f"(d[3]), "+f"(d[4]), "+f"(d[5]), "+f"(d[6]), "+f"(d[7]), "+f"(d[8]), "+f"(d[9]), "+f"(d[10]), "+f"(d[11]), "+f"(d[12]), "+f"(d[13]), "+f"(d[14]), "+f"(d[15]), "+f"(d[16]), "+f"(d[17]), "+f"(d[18]), "+f"(d[19]), "+f"(d[20]), "+f"(d[21]), "+f"(d[22]), "+f"(d[23]), "+f"(d[24]), "+f"(d[25]), "+f"(d[26]), "+f"(d[27])
    : "r"(a0), "r"(a1), "r"(a2), "r"(a3), "l"(descB));
}
__device__ __forceinline__ void mma_o_init(float (&d)[48], uint32_t a0, uint32_t a1, uint32_t a2, uint32_t a3, uint64_t descB) {
  asm volatile("wgmma.mma_async.sync.aligned.m64n96k16.f32.bf16.bf16 {%0, %1, %2, %3, %4, %5, %6, %7, %8, %9, %10, %11, %12, %13, %14, %15, %16, %17, %18, %19, %20, %21, %22, %23, %24, %25, %26, %27, %28, %29, %30, %31, %32, %33, %34, %35, %36, %37, %38, %39, %40, %41, %42, %43, %44, %45, %46, %47}, "
    "{%48, %49, %50, %51}, %52, 0, 1, 1, 1;"
    : "=f"(d[0]), "=f"(d[1]), "=f"(d[2]), "=f"(d[3]), "=f"(d[4]), "=f"(d[5]), "=f"(d[6]), "=f"(d[7]), "=f"(d[8]), "=f"(d[9]), "=f"(d[10]), "=f"(d[11]), "=f"(d[12]), "=f"(d[13]), "=f"(d[14]), "=f"(d[15]), "=f"(d[16]), "=f"(d[17]), "=f"(d[18]), "=f"(d[19]), "=f"(d[20]), "=f"(d[21]), "=f"(d[22]), "=f"(d[23]), "=f"(d[24]), "=f"(d[25]), "=f"(d[26]), "=f"(d[27]), "=f"(d[28]), "=f"(d[29]), "=f"(d[30]), "=f"(d[31]), "=f"(d[32]), "=f"(d[33]), "=f"(d[34]), "=f"(d[35]), "=f"(d[36]), "=f"(d[37]), "=f"(d[38]), "=f"(d[39]), "=f"(d[40]), "=f"(d[41]), "=f"(d[42]), "=f"(d[43]), "=f"(d[44]), "=f"(d[45]), "=f"(d[46]), "=f"(d[47])
    : "r"(a0), "r"(a1), "r"(a2), "r"(a3), "l"(descB));
}
__device__ __forceinline__ void mma_o(float (&d)[48], uint32_t a0, uint32_t a1, uint32_t a2, uint32_t a3, uint64_t descB) {
  asm volatile("wgmma.mma_async.sync.aligned.m64n96k16.f32.bf16.bf16 {%0, %1, %2, %3, %4, %5, %6, %7, %8, %9, %10, %11, %12, %13, %14, %15, %16, %17, %18, %19, %20, %21, %22, %23, %24, %25, %26, %27, %28, %29, %30, %31, %32, %33, %34, %35, %36, %37, %38, %39, %40, %41, %42, %43, %44, %45, %46, %47}, "
    "{%48, %49, %50, %51}, %52, 1, 1, 1, 1;"
    : "+f"(d[0]), "+f"(d[1]), "+f"(d[2]), "+f"(d[3]), "+f"(d[4]), "+f"(d[5]), "+f"(d[6]), "+f"(d[7]), "+f"(d[8]), "+f"(d[9]), "+f"(d[10]), "+f"(d[11]), "+f"(d[12]), "+f"(d[13]), "+f"(d[14]), "+f"(d[15]), "+f"(d[16]), "+f"(d[17]), "+f"(d[18]), "+f"(d[19]), "+f"(d[20]), "+f"(d[21]), "+f"(d[22]), "+f"(d[23]), "+f"(d[24]), "+f"(d[25]), "+f"(d[26]), "+f"(d[27]), "+f"(d[28]), "+f"(d[29]), "+f"(d[30]), "+f"(d[31]), "+f"(d[32]), "+f"(d[33]), "+f"(d[34]), "+f"(d[35]), "+f"(d[36]), "+f"(d[37]), "+f"(d[38]), "+f"(d[39]), "+f"(d[40]), "+f"(d[41]), "+f"(d[42]), "+f"(d[43]), "+f"(d[44]), "+f"(d[45]), "+f"(d[46]), "+f"(d[47])
    : "r"(a0), "r"(a1), "r"(a2), "r"(a3), "l"(descB));
}

__device__ __forceinline__ void wg_fence() { asm volatile("wgmma.fence.sync.aligned;" ::: "memory"); }
__device__ __forceinline__ void wg_commit() { asm volatile("wgmma.commit_group.sync.aligned;" ::: "memory"); }
template <int N> __device__ __forceinline__ void wg_wait() { asm volatile("wgmma.wait_group.sync.aligned %0;" ::"n"(N) : "memory"); }
template <int N> __device__ __forceinline__ void pin(float (&d)[N]) {
#pragma unroll
  for (int i = 0; i < N; i++) asm volatile("" : "+f"(d[i])::"memory");
}
template <int N> __device__ __forceinline__ void pin(uint32_t (&d)[N]) {
#pragma unroll
  for (int i = 0; i < N; i++) asm volatile("" : "+r"(d[i])::"memory");
}
__device__ __forceinline__ uint64_t mkdesc(uint32_t lo, uint32_t hi) { return ((uint64_t)hi << 32) | lo; }
constexpr uint64_t EVICT_FIRST = 0x12F0000000000000ull;
constexpr uint32_t HI_X = (3072 >> 4) | (1u << 30);
constexpr uint32_t HI_KV = (1024 >> 4) | (1u << 30);
constexpr uint32_t HI_W = (512 >> 4) | (2u << 30);
constexpr uint32_t HI_O = (1536 >> 4) | (2u << 30);
constexpr uint32_t LO_O = (1u << 16) + ((SM_BASE + OFF_OIN) >> 4);
constexpr uint32_t LO_WQ = ((12288 >> 4) << 16) + ((SM_BASE + OFF_WQ) >> 4);
constexpr uint32_t LO_WO = ((6144 >> 4) << 16) + ((SM_BASE + OFF_WO) >> 4);
constexpr uint32_t LO_X = (1u << 16) + ((SM_BASE + OFF_X) >> 4);
constexpr uint32_t LO_KV = (1u << 16) + ((SM_BASE + OFF_KV) >> 4);

__device__ __forceinline__ uint32_t pack_bf16(float lo, float hi) {
  uint32_t r;
  asm("cvt.rn.bf16x2.f32 %0, %1, %2;" : "=r"(r) : "f"(hi), "f"(lo));
  return r;
}
__device__ __forceinline__ float ex2(float x) {
  float r;
  asm("ex2.approx.ftz.f32 %0, %1;" : "=f"(r) : "f"(x));
  return r;
}
__device__ __forceinline__ float rcp(float x) {
  float r;
  asm("rcp.approx.ftz.f32 %0, %1;" : "=f"(r) : "f"(x));
  return r;
}
__device__ __forceinline__ bool elect() {
  uint32_t p;
  asm volatile("{\n.reg .pred P;\nelect.sync _|P, 0xffffffff;\nselp.u32 %0, 1, 0, P;\n}" : "=r"(p));
  return p;
}
__device__ __forceinline__ void mbar_init(uint32_t bar, uint32_t cnt) {
  asm volatile("mbarrier.init.shared::cta.b64 [%0], %1;" ::"r"(bar), "r"(cnt) : "memory");
}
__device__ __forceinline__ void mbar_wait(uint32_t bar, uint32_t parity) {
  asm volatile(
      "{\n.reg .pred p;\n.reg .u32 n;\n"
      "mbarrier.try_wait.parity.shared::cta.b64 p, [%0], %1;\n"
      "@p bra DONE;\n"
      "mov.u32 n, 0;\n"
      "LOOP:\n"
      "mbarrier.try_wait.parity.shared::cta.b64 p, [%0], %1;\n"
      "@p bra DONE;\n"
      "add.u32 n, n, 1;\n"
      "setp.lt.u32 p, n, 0x400000;\n"
      "@p bra LOOP;\n"
      "trap;\n"
      "DONE:\n}\n" ::"r"(bar), "r"(parity)
      : "memory");
}
__device__ __forceinline__ void mbar_arrive_cluster(uint32_t bar) {
  asm volatile("mbarrier.arrive.shared::cluster.b64 _, [%0];" ::"r"(bar) : "memory");
}
__device__ __forceinline__ void mbar_expect_tx(uint32_t bar, uint32_t bytes) {
  asm volatile("mbarrier.arrive.expect_tx.shared::cta.b64 _, [%0], %1;" ::"r"(bar), "r"(bytes) : "memory");
}
__device__ __forceinline__ uint32_t mapa(uint32_t addr, uint32_t rank) {
  uint32_t r;
  asm("mapa.shared::cluster.u32 %0, %1, %2;" : "=r"(r) : "r"(addr), "r"(rank));
  return r;
}
__device__ __forceinline__ void sched_fence(uint32_t& keep, int never) {
  asm volatile("{\n.reg .pred p;\nsetp.ne.s32 p, %1, 0;\n@p mov.u32 %0, %clock;\n}" : "+r"(keep) : "r"(never) : "memory");
}
template <int ID> __device__ __forceinline__ void tok_wait() { asm volatile("bar.sync %0, %1;" ::"n"(ID), "n"(ID == T7 ? 384 : 256) : "memory"); }
template <int ID> __device__ __forceinline__ void tok_pass() { asm volatile("bar.arrive %0, %1;" ::"n"(ID), "n"(ID == T7 ? 384 : 256) : "memory"); }
__device__ __forceinline__ void fence_async() { asm volatile("fence.proxy.async.shared::cta;" ::: "memory"); }
__device__ __forceinline__ void stsm4(uint32_t addr, uint32_t r0, uint32_t r1, uint32_t r2, uint32_t r3) {
  asm volatile("stmatrix.sync.aligned.m8n8.x4.shared.b16 [%0], {%1,%2,%3,%4};" ::"r"(addr), "r"(r0), "r"(r1), "r"(r2), "r"(r3) : "memory");
}
__device__ __forceinline__ void lds128(uint32_t addr, uint32_t& r0, uint32_t& r1, uint32_t& r2, uint32_t& r3) {
  asm volatile("ld.shared.v4.b32 {%0,%1,%2,%3}, [%4];" : "=r"(r0), "=r"(r1), "=r"(r2), "=r"(r3) : "r"(addr) : "memory");
}
template <int OFF>
__device__ __forceinline__ void st_async(uint32_t addr, uint32_t bar, uint32_t r0, uint32_t r1, uint32_t r2, uint32_t r3) {
  asm volatile("st.async.shared::cluster.mbarrier::complete_tx::bytes.v4.b32 [%0+%6], {%1,%2,%3,%4}, [%5];" ::"r"(addr), "r"(r0),
               "r"(r1), "r"(r2), "r"(r3), "r"(bar), "n"(OFF)
               : "memory");
}
__device__ __forceinline__ void tma5_mc(uint32_t dst, const CUtensorMap* tm, uint32_t bar, int c2, int c4) {
  asm volatile(
      "cp.async.bulk.tensor.5d.shared::cluster.global.mbarrier::complete_tx::bytes.multicast::cluster.L2::cache_hint "
      "[%0], [%1, {0, 0, %3, 0, %4}], [%2], %5, %6;" ::"r"(dst), "l"(tm), "r"(bar), "r"(c2), "r"(c4), "h"((uint16_t)3), "l"(EVICT_FIRST)
      : "memory");
}
__device__ __forceinline__ void tma5_pf(const CUtensorMap* tm, int c2, int c4) {
  asm volatile("cp.async.bulk.prefetch.tensor.5d.L2.global [%0, {0, 0, %1, 0, %2}];" ::"l"(tm), "r"(c2), "r"(c4) : "memory");
}
__device__ __forceinline__ void tma3(uint32_t dst, const CUtensorMap* tm, uint32_t bar, int c1, int c2) {
  asm volatile("cp.async.bulk.tensor.3d.shared::cluster.global.mbarrier::complete_tx::bytes [%0], [%1, {0, %3, %4}], [%2];" ::"r"(dst),
               "l"(tm), "r"(bar), "r"(c1), "r"(c2)
               : "memory");
}

constexpr float SQRT_HD = 6.92820323027551f;
constexpr float SM_C = 1.4426950408889634f / SQRT_HD;

__device__ __forceinline__ void s_init(float (&s)[32], const uint32_t (&mk)[16], const uint32_t (&b)[16]) {
#pragma unroll
  for (int i = 0; i < 16; i++) {
    const int o = 4 * (i & 7) + 2 * (i >> 3);
    uint32_t t0, t1;
    asm("{\n.reg .b16 ml, mh, bl, bh;\n.reg .b32 m2, b2;\n"
        "mov.b32 {ml, mh}, %1;\nmov.b32 {bl, bh}, %3;\nmov.b32 m2, {ml, ml};\nmov.b32 b2, {bl, bl};\n"
        "fma.rn.bf16x2 %0, m2, %2, b2;\n}"
        : "=r"(t0)
        : "r"(mk[i]), "r"(0x40DE40DEu), "r"(b[i]));
    asm("fma.rn.bf16x2 %0, %1, %2, %3;" : "=r"(t1) : "r"(mk[i]), "r"(0x40DE40DEu), "r"(b[i]));
    s[o] = __uint_as_float(t0);
    s[o + 1] = __uint_as_float(t1);
    asm volatile("" : "+f"(s[o]), "+f"(s[o + 1])::"memory");
  }
}
__device__ __forceinline__ uint32_t pack_bias(float lo, float hi) {
  uint32_t l = __float_as_uint(fmaf(lo, SQRT_HD, 0x1p-100f)), h = __float_as_uint(fmaf(hi, SQRT_HD, 0x1p-100f));
  l = (l - (l >> 16) + 0x8000u) >> 16;
  return ((h - l + 0x8000u) & 0xffff0000u) | l;
}
__device__ __forceinline__ void rowmax_i(const float (&s)[32], int& i0, int& i1) {
#define FI(x) __float_as_int(x)
  i0 = max(FI(s[0]), FI(s[1])), i1 = max(FI(s[2]), FI(s[3]));
  int k0 = __vimax3_s32(FI(s[4]), FI(s[5]), FI(s[8])), k1 = __vimax3_s32(FI(s[6]), FI(s[7]), FI(s[10]));
  i0 = __vimax3_s32(i0, FI(s[9]), FI(s[12]));   i1 = __vimax3_s32(i1, FI(s[11]), FI(s[14]));
  k0 = __vimax3_s32(k0, FI(s[13]), FI(s[16]));  k1 = __vimax3_s32(k1, FI(s[15]), FI(s[18]));
  i0 = __vimax3_s32(i0, FI(s[17]), FI(s[20]));  i1 = __vimax3_s32(i1, FI(s[19]), FI(s[22]));
  k0 = __vimax3_s32(k0, FI(s[21]), FI(s[24]));  k1 = __vimax3_s32(k1, FI(s[23]), FI(s[26]));
  i0 = __vimax3_s32(i0, FI(s[25]), FI(s[28]));  i1 = __vimax3_s32(i1, FI(s[27]), FI(s[30]));
  i0 = __vimax3_s32(i0, k0, FI(s[29]));         i1 = __vimax3_s32(i1, k1, FI(s[31]));
#undef FI
}
__device__ __forceinline__ void quadmax_i(int& i0, int& i1, int x) {
  i0 = max(i0, __shfl_xor_sync(0xffffffffu, i0, x));
  i1 = max(i1, __shfl_xor_sync(0xffffffffu, i1, x));
}
__device__ __forceinline__ void rowmax_f(const float (&s)[32], int& i0, int& i1) {
  float m0 = fmaxf(s[0], s[1]), m1 = fmaxf(s[2], s[3]);
#pragma unroll
  for (int j = 1; j < 8; j++) {
    m0 = fmaxf(m0, fmaxf(s[4 * j], s[4 * j + 1]));
    m1 = fmaxf(m1, fmaxf(s[4 * j + 2], s[4 * j + 3]));
  }
  m0 = fmaxf(m0, __shfl_xor_sync(0xffffffffu, m0, 1));
  m1 = fmaxf(m1, __shfl_xor_sync(0xffffffffu, m1, 1));
  m0 = fmaxf(m0, __shfl_xor_sync(0xffffffffu, m0, 2));
  m1 = fmaxf(m1, __shfl_xor_sync(0xffffffffu, m1, 2));
  i0 = __float_as_int(m0), i1 = __float_as_int(m1);
}
template <int CH>
__device__ __forceinline__ void exp_rows(const float (&s)[32], uint32_t (&p)[16], int max0, int max1, uint32_t& keep, int never) {
  const float m0 = __int_as_float(max0) * -SM_C, m1 = __int_as_float(max1) * -SM_C;
  float t[32];
#pragma unroll
  for (int c = 0; c <= 16 / CH; c++) {
#pragma unroll
    for (int i = 2 * CH * c; i < 2 * CH * (c + 1) && i < 32; i++) {
      t[i] = fmaf(s[i], SM_C, (i & 2) ? m1 : m0);
      asm volatile("" : "+f"(t[i]));
    }
    if (c > 0) {
#pragma unroll
      for (int i = CH * (c - 1); i < CH * c; i++) {
        t[2 * i] = ex2(t[2 * i]), t[2 * i + 1] = ex2(t[2 * i + 1]);
        asm volatile("" : "+f"(t[2 * i]), "+f"(t[2 * i + 1]));
      }
    }
    if (c > 1) {
#pragma unroll
      for (int i = CH * (c - 2); i < CH * (c - 1); i++) {
        p[i] = pack_bf16(t[2 * i], t[2 * i + 1]);
        asm volatile("" : "+r"(p[i]));
      }
    }
    if (c < 16 / CH) sched_fence(keep, never);
  }
#pragma unroll
  for (int i = 16 - CH; i < 16; i++) p[i] = pack_bf16(t[2 * i], t[2 * i + 1]);
  pin(p);
}
__device__ __forceinline__ void issue_p(float (&o)[28], const uint32_t (&p)[16], uint32_t lo) {
#pragma unroll
  for (int ks = 0; ks < 4; ks++) {
    uint64_t db = mkdesc(lo + ks * 2, HI_KV);
    if (ks == 0) mma_p_init(o, p[0], p[1], p[2], p[3], db);
    else mma_p(o, p[4 * ks], p[4 * ks + 1], p[4 * ks + 2], p[4 * ks + 3], db);
  }
  wg_commit();
}
template <int SUM, int OFF>
__device__ __forceinline__ void normalize(const float (&o)[28], uint32_t (&f)[12]) {
  const float r0 = rcp(o[SUM]), r1 = rcp(o[SUM + 2]);
  uint32_t h0 = pack_bf16(r0, r0), h1 = pack_bf16(r1, r1);
#pragma unroll
  for (int j = 0; j < 12; j++)
    asm("mul.rn.bf16x2 %0, %1, %2;" : "=r"(f[j]) : "r"(pack_bf16(o[OFF + 2 * j], o[OFF + 2 * j + 1])), "r"((j & 1) ? h1 : h0));
}

__global__ void __cluster_dims__(2, 1, 1) __launch_bounds__(384, 1)
swin_attn_kernel(const __grid_constant__ Maps maps, const __nv_bfloat16* __restrict__ rpb, const int* __restrict__ rp_idx, int base, int never) {
  extern __shared__ __align__(1024) uint8_t smem_raw[];
  const uint32_t sb = (uint32_t)__cvta_generic_to_shared(smem_raw);
  const int tid = threadIdx.x;
  const int wg = __shfl_sync(0xffffffffu, tid >> 7, 0);
  const int warp = __shfl_sync(0xffffffffu, (tid >> 5) & 3, 0);
  const int lane = tid & 31;
  const int rank = blockIdx.x & 1;
  const int cl = blockIdx.x >> 1;
  const int ncl = gridDim.x >> 1;
  const uint32_t bars = sb + OFF_BAR;
  int extra = NWIN;
  auto read_ticket = [&]() {
    mbar_wait(bars + B_TICK, 0);
    uint32_t t;
    asm volatile("ld.shared.b32 %0, [%1];" : "=r"(t) : "r"(bars + W_TICK) : "memory");
    extra = base + __shfl_sync(0xffffffffu, t, 0);
  };
  auto window = [&](int v) { return v < base ? v : (v < base + ncl ? extra : NWIN); };
  auto prefetch = [&](int p, int win) {
    if (p < 2) tma5_pf(&maps.x, (((win >> 3) & ~7) + 4 + 4 * rank) & 511, (win * 4 + 2 + 2 * p) & 255);
    else tma5_pf(&maps.mask, 0, 2 * win + rank);
  };
  auto load = [&](int p, int win, int a) {
    if (p < 2)
      tma5_mc(sb + OFF_X + a * STAGE + rank * 12288 + p * 6144, &maps.x, bars + B_XFULL + 8 * a,
              (((win >> 3) & ~7) + 4 + 4 * rank) & 511, (win * 4 + 2 + 2 * p) & 255);
    else tma5_mc(sb + OFF_MASK + a * STAGE + rank * 4096, &maps.mask, bars + B_XFULL + 8 * a, 0, 2 * win + rank);
  };
  auto load_wkv = [&](int b) {
    tma3(sb + OFF_KV + (b < 3 ? b * 12288 : STAGE + (b - 3) * 12288), &maps.wqkv, bars + B_WKV + 8 * (b >> 1), 0,
         (b < 3 ? 6 : 9) + b + 3 * rank);
  };
  auto startup_loads = [&]() {
    if ((sb & 0x3FFFF) != SM_BASE) __trap();
    if (blockIdx.x == 0) asm volatile("st.relaxed.gpu.global.u32 [%0], 0;" ::"l"(&g_ticket) : "memory");
    mbar_expect_tx(bars + B_XFULL, X_BYTES);
    mbar_expect_tx(bars + B_M0, M_BYTES);
    mbar_expect_tx(bars + B_WKV + 8, 24576);
    load_wkv(2);
    load_wkv(3);
    tma5_mc(sb + OFF_MASK + rank * 4096, &maps.mask, bars + B_M0, 0, 2 * cl + rank);
    mbar_expect_tx(bars + B_WQ, 36864);
    for (int nb = 0; nb < 3; nb++) tma3(sb + OFF_WQ + nb * 12288, &maps.wqkv, bars + B_WQ, 0, 3 * rank + nb);
    mbar_expect_tx(bars + B_WKV + 16, 24576);
    load_wkv(4);
    load_wkv(5);
    mbar_expect_tx(bars + B_XFULL + 8, X_BYTES + M_BYTES);
    for (int p = 0; p < 3; p++) load(p, cl + ncl, 1);
    mbar_expect_tx(bars + B_TICK, 4);
    mbar_expect_tx(bars + B_WO, 36864);
    tma3(sb + OFF_WO, &maps.wo, bars + B_WO, 96 * rank, 3 * rank);
    for (int nb = 0; nb < 3; nb++)
      asm volatile("cp.async.bulk.tensor.5d.shared::cluster.global.mbarrier::complete_tx::bytes [%0], [%1, {%3, 0, 0, 0, %4}], [%2];" ::"r"(
                       sb + OFF_WO + 18432 + nb * 6144), "l"(&maps.wop), "r"(bars + B_WO), "r"(96 * rank + 32 * nb), "r"(3 * (rank ^ 1))
                   : "memory");
  };
  if (wg == KV_WG && warp == 3) {
    if (elect()) {
#pragma unroll
      for (int k = 0; k < 15; k++) mbar_init(bars + 8 * k, (k >> 1) == B_OEMPTY / 16 ? 4 : 1);
      asm volatile("fence.mbarrier_init.release.cluster;" ::: "memory");
    }
    __syncwarp();
  }
  asm volatile("barrier.cluster.arrive.relaxed.aligned;" ::: "memory");

  if (wg == KV_WG) {
    if (warp == 3 && elect()) {
      fence_async();
      mbar_expect_tx(bars + B_WKV, 24576);
      load_wkv(0);
      load_wkv(1);
    }
    __syncwarp();
    asm volatile("barrier.cluster.wait.aligned;" ::: "memory");
    if (elect()) {
      if (warp < 2) load(warp, cl, 0);
      else if (warp == 3) startup_loads();
    }
    __syncwarp();
    asm volatile("setmaxnreg.inc.sync.aligned.u32 216;");
    uint32_t w[3][48];
    auto load_frags = [&](int s) {
      const uint32_t la = sb + OFF_KV + (warp >> 1) * 12288 + (8 * (lane >> 4) + (lane & 7)) * 64 +
                          (((2 * (warp & 1) + ((lane >> 3) & 1)) ^ ((lane & 7) >> 1)) << 4);
      mbar_wait(bars + B_WKV + 8 * s, 0);
#pragma unroll
      for (int ks = 0; ks < 12; ks++)
        asm volatile("ldmatrix.sync.aligned.m8n8.x4.trans.shared.b16 {%0,%1,%2,%3}, [%4];"
                     : "=r"(w[s][4 * ks]), "=r"(w[s][4 * ks + 1]), "=r"(w[s][4 * ks + 2]), "=r"(w[s][4 * ks + 3])
                     : "r"(la + s * 24576 + (s == 2 || (s == 1 && warp >= 2) ? STAGE - 36864 : 0) + ks * 1024)
                     : "memory");
    };
    load_frags(0);
    uint32_t sta[4];
#pragma unroll
    for (int jj = 0; jj < 4; jj++) {
      sta[jj] = sb + OFF_KV + (16 * warp + (lane & 15)) * 128 + (((2 * jj + (lane >> 4)) ^ (lane & 7)) << 4);
      asm volatile("" : "+r"(sta[jj]));
    }
    const uint32_t xe_rem = mapa(bars + B_XEMPTY, rank ^ 1);
    const uint32_t v1off = warp > 0 ? 1024 : 0;

#define SF sched_fence(sta[0], never)
    float acc[32];
    uint32_t pk[16];
    auto store = [&](uint32_t off) {
#pragma unroll
      for (int jj = 0; jj < 4; jj++) stsm4(sta[jj] + off, pk[4 * jj], pk[4 * jj + 1], pk[4 * jj + 2], pk[4 * jj + 3]);
    };
    auto issue = [&](int s, uint32_t xd, bool st, uint32_t off) {
#pragma unroll
      for (int ks = 0; ks < 12; ks++) {
        uint64_t db = mkdesc(xd + (((ks >> 2) * 1024 + (ks & 3) * 32) >> 4), HI_X);
        if (ks == 0) mma_kv_init(acc, w[s][0], w[s][1], w[s][2], w[s][3], db);
        else mma_kv(acc, w[s][4 * ks], w[s][4 * ks + 1], w[s][4 * ks + 2], w[s][4 * ks + 3], db);
        if (ks == STA && st) {
          __syncwarp();
          store(off);
          __syncwarp();
        }
      }
      wg_commit();
    };
    auto convert = [&]() {
      wg_wait<0>();
      pin(acc);
#pragma unroll
      for (int j = 0; j < 16; j++) pk[j] = pack_bf16(acc[2 * j], acc[2 * j + 1]);
      pin(pk);
    };

    mbar_wait(bars + B_XFULL, 0);
    wg_fence();
    issue(0, LO_X, false, 0);
    load_frags(1);
    int nxt = cl + ncl;
    uint32_t ph = 0;
    uint32_t ticket = 0;
    auto step = [&](auto A) -> bool {
      constexpr int a = decltype(A)::value;
      constexpr uint32_t xd = LO_X + a * (STAGE >> 4);
      if (nxt + ncl >= base && nxt < base) read_ticket();
      const bool more = window(nxt) < NWIN;
      const int wn2 = window(nxt + ncl);
      convert();
      wg_fence();
      SF;
      tok_wait<T2>();
      issue(1, xd, true, a * STAGE);
      tok_pass<T3>();
      if (warp < 3 && wn2 < NWIN && elect()) prefetch(warp, wn2);
      __syncwarp();
      const bool first = a == 0 && nxt == cl + ncl;
      convert();
      SF;
      if (!first) tok_wait<T7>();
      store(a * STAGE + 8192);
      fence_async();
      if (first) {
        load_frags(2);
        asm volatile("bar.sync %0, 128;" ::"n"((int)BAR_STAGE) : "memory");
        asm volatile("st.shared.v4.b32 [%0], {%1,%1,%1,%1};" ::"r"(sb + OFF_KV + (warp >> 1) * STAGE + 144 * 128 + (tid & 63) * 16), "r"(0x3F803F80u) : "memory");
      }
      wg_fence();
      tok_wait<T5>();
      issue(2, xd, false, 0);
      tok_pass<T6>();
      if (!more) {
        convert();
        store(a * STAGE + 16384 + v1off);
        fence_async();
        return false;
      }
      mbar_wait(bars + B_XFULL + 8 * (a ^ 1), a ? ph ^ 1 : ph);
      convert();
      wg_fence();
      SF;
      tok_wait<T0>();
      if (tid == KV_WG * 128 && wn2 < NWIN) mbar_arrive_cluster(xe_rem + 8 * a);
      issue(0, LO_X + (a ^ 1) * (STAGE >> 4), true, a * STAGE + 16384 + v1off);
      tok_pass<T1>();
      fence_async();
      nxt += ncl;
      if (wn2 < NWIN) {
        mbar_wait(bars + B_XEMPTY + 8 * a, ph);
        if (elect()) {
          if (warp < 3) {
            load(warp, wn2, a);
          } else {
            mbar_expect_tx(bars + B_XFULL + 8 * a, X_BYTES + M_BYTES);
            if (rank == 0 && nxt + 3 * ncl >= base) {
              if (nxt + 2 * ncl < base) {
                asm volatile("atom.global.inc.u32 %0, [%1], %2;" : "=r"(ticket) : "l"(&g_ticket), "r"(ncl - 1) : "memory");
              } else if (nxt + ncl < base) {
#pragma unroll
                for (int r = 0; r < 2; r++)
                  asm volatile("st.async.shared::cluster.mbarrier::complete_tx::bytes.b32 [%0], %1, [%2];" ::"r"(mapa(bars + W_TICK, r)),
                               "r"(ticket), "r"(mapa(bars + B_TICK, r))
                               : "memory");
              }
            }
          }
        }
        __syncwarp();
      }
      return true;
    };
    while (step(IC<0>{}) && step(IC<1>{})) ph ^= 1;
    tok_wait<T0>();
    tok_pass<T1>();
    tok_wait<T2>();
    tok_pass<T3>();
    tok_wait<T7>();
    tok_wait<T5>();
  } else {
    const int a = wg - (KV_WG == 0 ? 1 : 0);
    const int g = lane >> 2, q = lane & 3;
    const uint32_t bar = bars + 8 * a;
    if (a == 0) {
      tok_pass<T2>();
      tok_pass<T5>();
    }
    asm volatile("setmaxnreg.dec.sync.aligned.u32 144;");
    uint32_t braw[32];
    {
      const int ty = 4 * (warp >> 1) + (g >> 1), tx = 4 * (warp & 1) + (g & 1);
      const int* ip = rp_idx + (ty * 8 + tx) * 64 + 8 * q;
#pragma unroll
      for (int c = 0; c < 8; c++)
        asm volatile("ld.global.nc.v4.b32 {%0,%1,%2,%3}, [%4];"
                     : "=r"(braw[4 * c]), "=r"(braw[4 * c + 1]), "=r"(braw[4 * c + 2]), "=r"(braw[4 * c + 3])
                     : "l"(ip + (c >> 2) * 128 + ((c >> 1) & 1) * 32 + (c & 1) * 4));
      const int e = a * 128 + (tid & 127);
      uint32_t v = 0;
      if (e < 225) asm volatile("ld.global.nc.b32 %0, [%1];" : "=r"(v) : "l"(reinterpret_cast<const uint32_t*>(rpb) + e * 2 + rank));
      asm volatile("st.shared.b32 [%0], %1;" ::"r"(sb + OFF_RPB + e * 4), "r"(v) : "memory");
      tok_wait<BAR_BIAS>();
#pragma unroll
      for (int j = 0; j < 32; j++)
        asm volatile("ld.shared.b32 %0, [%1];" : "=r"(braw[j]) : "r"(sb + OFF_RPB + braw[j] * 4) : "memory");
    }
    asm volatile("barrier.cluster.wait.aligned;" ::: "memory");

    const int mrow = 16 * warp + (g >> 1) + 4 * (g & 1);
#undef SF
#define SF sched_fence(mk_addr, never)
    uint32_t mk_addr = sb + OFF_MASK + a * STAGE + mrow * 128 + ((q ^ (mrow & 7)) << 4);
    const uint32_t ostage = sb + OFF_OIN + a * STAGE + warp * 3072;
    const uint32_t ost = ostage + ((lane >> 3) & 1) * 1536 + (lane & 7) * 64 + (((lane >> 4) ^ ((lane & 7) >> 1)) << 4);
    const uint32_t oin_rem = mapa(ostage + g * 64 + ((q ^ (g >> 1)) << 4), rank ^ 1);
    const uint32_t bar_rem = mapa(bar, rank ^ 1);

    auto store_out = [&](int win) {
      fence_async();
      __syncwarp();
      if (elect()) {
        int yy = (((win >> 3) & ~7) + 4 + 4 * (warp >> 1)) & 511;
        int xh = (win * 4 + 2 + 2 * (warp & 1)) & 255;
        asm volatile("cp.async.bulk.tensor.5d.global.shared::cta.bulk_group [%0, {0, 0, %2, %3, %4}], [%1];" ::"l"(&maps.out), "r"(ostage),
                     "r"(yy), "r"(3 * rank), "r"(xh)
                     : "memory");
        asm volatile("cp.async.bulk.commit_group;" ::: "memory");
      }
      __syncwarp();
    };
    auto release_oin = [&]() {
      if (elect()) {
        asm volatile("cp.async.bulk.wait_group.read 0;" ::: "memory");
        if (warp == 0) mbar_expect_tx(bar + B_OFULL, O_BYTES);
        mbar_arrive_cluster(bar_rem + B_OEMPTY);
      }
      __syncwarp();
    };
    float qa[48];
    uint32_t bias0[16], bias1[16];
    uint32_t mk[16];
    auto load_mask = [&](uint32_t z) {
#pragma unroll
      for (int c = 0; c < 4; c++)
        lds128((c & 1 ? mk_addr ^ (64 + z) : mk_addr) + (c >> 1) * 1024, mk[4 * c], mk[4 * c + 1], mk[4 * c + 2], mk[4 * c + 3]);
    };
    auto clamp_mask = [&]() {
      SF;
#pragma unroll
      for (int j = 0; j < 16; j++) asm("max.NaN.bf16x2 %0, %0, %1;" : "+r"(mk[j]) : "r"(0xFD80FD80u));
      pin(mk);
    };
    auto issue_q = [&](uint32_t ua, bool tok, int win) {
#pragma unroll
      for (int ks = 0; ks < 12; ks++) {
        if (ks == Q_SPLIT && tok) {
          tok_pass<T4>();
          store_out(win);
          tok_wait<T7>();
          wg_fence();
        }
        uint64_t da = mkdesc(ua + LO_X + (((ks >> 2) * 1024 + (ks & 3) * 32) >> 4), HI_X);
        uint64_t db = mkdesc(LO_WQ + ks * 64, HI_W);
        if (ks == 0) mma_q_init(qa, da, db);
        else mma_q(qa, da, db);
      }
      wg_commit();
      if (tok) tok_pass<T5>();
    };
#pragma unroll
    for (int j = 0; j < 16; j++) {
      const uint32_t b0 = braw[2 * j], b1 = braw[2 * j + 1];
      bias0[j] = pack_bias(__uint_as_float(b0 << 16), __uint_as_float(b1 << 16));
      bias1[j] = pack_bias(__uint_as_float(b0 & 0xffff0000u), __uint_as_float(b1 & 0xffff0000u));
    }
    pin(bias0);
    pin(bias1);
    SF;
    mbar_wait(bars + B_WQ, 0);
    wg_fence();
    if (a == 0) tok_wait<T3>();
    else tok_wait<T1>();
    issue_q(a * (STAGE >> 4), false, 0);
    if (a == 0) mbar_wait(bars + B_M0, 0);
    else tok_pass<T2>();
    load_mask(0);
    if (a == 1) {
      tok_wait<T3>();
      tok_pass<T4>();
      tok_pass<T5>();
      tok_wait<T7>();
    }
    clamp_mask();
    uint32_t ph = 0;
    int win = cl + a * ncl;
    for (;; win += 2 * ncl, ph ^= 1) {
      const uint32_t ua = a * (STAGE >> 4) + (win >> 20);
      const uint32_t kd = ua + LO_KV;
      float s0[32], s1[32];
      wg_wait<0>();
      pin(qa);
      uint32_t q0[12], q1[12];
#pragma unroll
      for (int j = 0; j < 12; j++) q0[j] = pack_bf16(qa[2 * j], qa[2 * j + 1]);
#pragma unroll
      for (int j = 0; j < 12; j++) q1[j] = pack_bf16(qa[24 + 2 * j], qa[25 + 2 * j]);
      pin(q0);
      pin(q1);
      s_init(s0, mk, bias0);
      s_init(s1, mk, bias1);
      wg_fence();
      tok_wait<T6>();
#pragma unroll
      for (int ks = 0; ks < 3; ks++)
        mma_s(s0, q0[4 * ks], q0[4 * ks + 1], q0[4 * ks + 2], q0[4 * ks + 3], mkdesc(kd + ks * 128, HI_KV));
      wg_commit();
#pragma unroll
      for (int ks = 0; ks < 3; ks++)
        mma_s(s1, q1[4 * ks], q1[4 * ks + 1], q1[4 * ks + 2], q1[4 * ks + 3], mkdesc(kd + (3 + ks) * 128, HI_KV));
      wg_commit();
      tok_pass<T0>();
      release_oin();
      int x0, x1, y0, y1;
      uint32_t p0[16], p1[16];
      wg_wait<1>();
      pin(s0);
      pin(q0);
      rowmax_i(s0, x0, x1);
      quadmax_i(x0, x1, 1);
      wg_wait<0>();
      pin(s1);
      pin(q1);
      rowmax_i(s1, y0, y1);
      quadmax_i(x0, x1, 2);
      quadmax_i(y0, y1, 1);
      quadmax_i(y0, y1, 2);
      if (__builtin_expect(__any_sync(0xffffffffu, (x0 | x1 | y0 | y1) < 0), 0)) {
        rowmax_f(s0, x0, x1);
        rowmax_f(s1, y0, y1);
      }
      exp_rows<EXP_CH>(s0, p0, x0, x1, mk_addr, never);
      exp_rows<EXP_CH>(s1, p1, y0, y1, mk_addr, never);
      float o0[28], o1[28];
      wg_fence();
      SF;
      tok_wait<T4>();
      issue_p(o0, p0, kd + ((96 * 128) >> 4));
      issue_p(o1, p1, kd + ((144 * 128) >> 4));
      tok_pass<T7>();
      mbar_wait(bar + B_OEMPTY, ph);
      uint32_t f0[12], f1[12];
      wg_wait<1>();
      pin(o0);
      pin(p0);
      normalize<24, 0>(o0, f0);
      st_async<0>(oin_rem, bar_rem + B_OFULL, f0[0], f0[2], f0[4], f0[6]);
      st_async<1536>(oin_rem, bar_rem + B_OFULL, f0[1], f0[3], f0[5], f0[7]);
      wg_wait<0>();
      pin(o1);
      pin(p1);
      normalize<0, 4>(o1, f1);
      st_async<512>(oin_rem, bar_rem + B_OFULL, f0[8], f0[10], f1[0], f1[2]);
      st_async<2048>(oin_rem, bar_rem + B_OFULL, f0[9], f0[11], f1[1], f1[3]);
      st_async<1024>(oin_rem, bar_rem + B_OFULL, f1[4], f1[6], f1[8], f1[10]);
      st_async<2560>(oin_rem, bar_rem + B_OFULL, f1[5], f1[7], f1[9], f1[11]);
      pin(f0);
      pin(f1);
      float (&oa)[48] = qa;
      int wn1 = 0, wn2 = 0;
      if ((unsigned)(win - 2 * ncl) >= (unsigned)(base - 4 * ncl)) {
        if (win < 2 * ncl) {
          mbar_wait(bars + B_WO, 0);
        } else {
          read_ticket();
          wn1 = window(win + ncl), wn2 = window(win + 2 * ncl);
        }
      }
      const bool last = wn1 >= NWIN;
      if (!last) tok_wait<T1>();
      wg_fence();
#pragma unroll
      for (int ks = 0; ks < 3; ks++) {
        uint64_t db = mkdesc(LO_WO + ks * 64, HI_W);
        if (ks == 0) mma_o_init(oa, f0[0], f0[1], f0[2], f0[3], db);
        else mma_o(oa, f0[4 * ks], f0[4 * ks + 1], f0[4 * ks + 2], f0[4 * ks + 3], db);
      }
#pragma unroll
      for (int ks = 0; ks < 3; ks++)
        mma_o(oa, f1[4 * ks], f1[4 * ks + 1], f1[4 * ks + 2], f1[4 * ks + 3], mkdesc(LO_WO + (3 + ks) * 64, HI_W));
      mbar_wait(bar + B_OFULL, ph);
      asm volatile("fence.proxy.async::generic.acquire.sync_restrict::shared::cluster.cluster;" ::: "memory");
      wg_fence();
#pragma unroll
      for (int ks = 0; ks < 6; ks++)
        mma_q(oa, mkdesc(ua + LO_O + (((ks >> 1) * 512 + (ks & 1) * 32) >> 4), HI_O), mkdesc(LO_WO + (18432 >> 4) + ks * 64, HI_W));
      wg_commit();
      if (!last) tok_pass<T2>();
      load_mask(win >> 20);
      wg_wait<0>();
      pin(oa);
      pin(f0);
      pin(f1);
#pragma unroll
      for (int jj = 0; jj < 6; jj++)
        stsm4((jj & 1 ? ost ^ (32 + (win >> 20)) : ost) + (jj >> 1) * 512, pack_bf16(oa[8 * jj], oa[8 * jj + 1]), pack_bf16(oa[8 * jj + 2], oa[8 * jj + 3]),
              pack_bf16(oa[8 * jj + 4], oa[8 * jj + 5]), pack_bf16(oa[8 * jj + 6], oa[8 * jj + 7]));
      if (wn2 >= NWIN) {
        if (!last) {
          tok_wait<T3>();
          tok_pass<T4>();
          tok_pass<T5>();
          tok_wait<T7>();
        }
        break;
      }
      wg_fence();
      tok_wait<T3>();
      issue_q(ua, true, win);
      clamp_mask();
    }
    store_out(window(win));
    asm volatile("cp.async.bulk.wait_group.read 0;" ::: "memory");
    __syncwarp();
  }
}

typedef CUresult (*EncodeFn)(CUtensorMap*, CUtensorMapDataType, cuuint32_t, void*, const cuuint64_t*, const cuuint64_t*,
                             const cuuint32_t*, const cuuint32_t*, CUtensorMapInterleave, CUtensorMapSwizzle,
                             CUtensorMapL2promotion, CUtensorMapFloatOOBfill);

void encode_map(EncodeFn encode, CUtensorMap* m, void* p, int rank, const cuuint64_t* dim, const cuuint64_t* str,
                const cuuint32_t* box, CUtensorMapSwizzle sw) {
  const cuuint32_t es[5] = {1, 1, 1, 1, 1};
  CUresult r = encode(m, CU_TENSOR_MAP_DATA_TYPE_BFLOAT16, rank, p, dim, str, box, es, CU_TENSOR_MAP_INTERLEAVE_NONE, sw,
                      CU_TENSOR_MAP_L2_PROMOTION_L2_128B, CU_TENSOR_MAP_FLOAT_OOB_FILL_NONE);
  if (r != CUDA_SUCCESS) fprintf(stderr, "tensor map encode failed: %d\n", (int)r);
}

}

extern "C" void kernel_launch(void* const* d_in, const int* in_sizes, int n_in, void* d_out, int out_size) {
  static EncodeFn encode = nullptr;
  static int grid = 0;
  if (!encode) {
    cudaDriverEntryPointQueryResult qr;
    void* fn = nullptr;
    cudaGetDriverEntryPoint("cuTensorMapEncodeTiled", &fn, cudaEnableDefault, &qr);
    encode = (EncodeFn)fn;
    cudaFuncSetAttribute(swin_attn_kernel, cudaFuncAttributeMaxDynamicSharedMemorySize, SMEM_BYTES);
    cudaLaunchConfig_t cfg = {};
    cfg.gridDim = dim3(132);
    cfg.blockDim = dim3(384);
    cfg.dynamicSmemBytes = SMEM_BYTES;
    cudaLaunchAttribute at;
    at.id = cudaLaunchAttributeClusterDimension;
    at.val.clusterDim.x = 2;
    at.val.clusterDim.y = 1;
    at.val.clusterDim.z = 1;
    cfg.attrs = &at;
    cfg.numAttrs = 1;
    int ncl = 0;
    if (cudaOccupancyMaxActiveClusters(&ncl, swin_attn_kernel, &cfg) != cudaSuccess || ncl < 1) {
      (void)cudaGetLastError();
      ncl = 66;
    }
    if (ncl > 256) ncl = 256;
    grid = 2 * ncl;
  }
  Maps maps;
  {
    const cuuint64_t dim[5] = {64, 2, 512, 3, 256}, str[4] = {384, 512 * 384, 128, 768};
    const cuuint32_t box[5] = {64, 2, 4, 3, 2};
    encode_map(encode, &maps.x, d_in[0], 5, dim, str, box, CU_TENSOR_MAP_SWIZZLE_128B);
  }
  {
    const cuuint64_t dim[5] = {64, 4, 2, 4, 8192}, str[4] = {1024, 128, 256, 4096};
    const cuuint32_t box[5] = {64, 4, 2, 4, 1};
    encode_map(encode, &maps.mask, d_in[5], 5, dim, str, box, CU_TENSOR_MAP_SWIZZLE_128B);
  }
  {
    const cuuint64_t dim[5] = {32, 2, 512, 6, 256}, str[4] = {384, 512 * 384, 64, 768};
    const cuuint32_t box[5] = {32, 2, 4, 3, 2};
    encode_map(encode, &maps.out, d_out, 5, dim, str, box, CU_TENSOR_MAP_SWIZZLE_64B);
  }
  {
    const cuuint64_t dim[3] = {32, 192, 18}, str[2] = {576 * 2, 64};
    const cuuint32_t box[3] = {32, 192, 1};
    encode_map(encode, &maps.wqkv, d_in[1], 3, dim, str, box, CU_TENSOR_MAP_SWIZZLE_64B);
    const cuuint64_t dim2[3] = {32, 192, 6}, str2[2] = {192 * 2, 64};
    const cuuint32_t box2[3] = {32, 96, 3};
    encode_map(encode, &maps.wo, d_in[2], 3, dim2, str2, box2, CU_TENSOR_MAP_SWIZZLE_64B);
    const cuuint64_t dim3_[5] = {192, 2, 4, 4, 6}, str3[4] = {384, 8 * 384, 2 * 384, 32 * 384};
    const cuuint32_t box3[5] = {32, 2, 4, 4, 3};
    encode_map(encode, &maps.wop, d_in[2], 5, dim3_, str3, box3, CU_TENSOR_MAP_SWIZZLE_64B);
  }
  swin_attn_kernel<<<grid, 384, SMEM_BYTES>>>(maps, (const __nv_bfloat16*)d_in[3], (const int*)d_in[4], NWIN / (grid / 2) * (grid / 2), 0);
}
```

```cpp
#include <cuda_runtime.h>
#include <cuda_bf16.h>
#include <cuda.h>
#include <stdint.h>
#include <stdio.h>

namespace {

constexpr int NWIN = 4096;
constexpr int KV_WG = 0;
constexpr int Q_SPLIT = 4;
constexpr int EXP_CH = 4;

constexpr uint32_t SM_BASE  = 1024;
constexpr uint32_t OFF_WQ   = 0;
constexpr uint32_t OFF_WO   = 36864;
constexpr uint32_t STAGE    = 70656;
constexpr uint32_t OFF_X    = 73728;
constexpr uint32_t X_BYTES  = 24576;
constexpr uint32_t OFF_MASK = OFF_X + X_BYTES;
constexpr uint32_t M_BYTES  = 8192;
constexpr uint32_t OFF_KV   = OFF_MASK + M_BYTES;
constexpr uint32_t OFF_OIN  = OFF_KV + 25600;
constexpr uint32_t O_BYTES  = 12288;
constexpr uint32_t OFF_BAR  = 215040;
constexpr uint32_t OFF_RPB  = OFF_BAR + 1024;
constexpr uint32_t SMEM_BYTES = OFF_RPB + 1024;
constexpr uint32_t B_XFULL = 0, B_XEMPTY = 16, B_OFULL = 32, B_OEMPTY = 48, B_WKV = 64  , B_WQ = 88, B_WO = 96,
                   B_TICK = 104, B_M0 = 112, W_TICK = 120;
enum { T0 = 1, T1, T2, T3, T4, T5, T6, T7, BAR_BIAS, BAR_STAGE };

__device__ unsigned int g_ticket;

template <int V> struct IC { static constexpr int value = V; };
struct Maps { CUtensorMap x, mask, out, wqkv, wo, wop; };

__device__ __forceinline__ void mma_q_init(float (&d)[48], uint64_t descA, uint64_t descB) {
  asm volatile("wgmma.mma_async.sync.aligned.m64n96k16.f32.bf16.bf16 {%0, %1, %2, %3, %4, %5, %6, %7, %8, %9, %10, %11, %12, %13, %14, %15, %16, %17, %18, %19, %20, %21, %22, %23, %24, %25, %26, %27, %28, %29, %30, %31, %32, %33, %34, %35, %36, %37, %38, %39, %40, %41, %42, %43, %44, %45, %46, %47}, "
    "%48, %49, 0, 1, 1, 0, 1;"
    : "+f"(d[0]), "+f"(d[1]), "+f"(d[2]), "+f"(d[3]), "+f"(d[4]), "+f"(d[5]), "+f"(d[6]), "+f"(d[7]), "+f"(d[8]), "+f"(d[9]), "+f"(d[10]), "+f"(d[11]), "+f"(d[12]), "+f"(d[13]), "+f"(d[14]), "+f"(d[15]), "+f"(d[16]), "+f"(d[17]), "+f"(d[18]), "+f"(d[19]), "+f"(d[20]), "+f"(d[21]), "+f"(d[22]), "+f"(d[23]), "+f"(d[24]), "+f"(d[25]), "+f"(d[26]), "+f"(d[27]), "+f"(d[28]), "+f"(d[29]), "+f"(d[30]), "+f"(d[31]), "+f"(d[32]), "+f"(d[33]), "+f"(d[34]), "+f"(d[35]), "+f"(d[36]), "+f"(d[37]), "+f"(d[38]), "+f"(d[39]), "+f"(d[40]), "+f"(d[41]), "+f"(d[42]), "+f"(d[43]), "+f"(d[44]), "+f"(d[45]), "+f"(d[46]), "+f"(d[47])
    : "l"(descA), "l"(descB));
}
__device__ __forceinline__ void mma_q(float (&d)[48], uint64_t descA, uint64_t descB) {
  asm volatile("wgmma.mma_async.sync.aligned.m64n96k16.f32.bf16.bf16 {%0, %1, %2, %3, %4, %5, %6, %7, %8, %9, %10, %11, %12, %13, %14, %15, %16, %17, %18, %19, %20, %21, %22, %23, %24, %25, %26, %27, %28, %29, %30, %31, %32, %33, %34, %35, %36, %37, %38, %39, %40, %41, %42, %43, %44, %45, %46, %47}, "
    "%48, %49, 1, 1, 1, 0, 1;"
    : "+f"(d[0]), "+f"(d[1]), "+f"(d[2]), "+f"(d[3]), "+f"(d[4]), "+f"(d[5]), "+f"(d[6]), "+f"(d[7]), "+f"(d[8]), "+f"(d[9]), "+f"(d[10]), "+f"(d[11]), "+f"(d[12]), "+f"(d[13]), "+f"(d[14]), "+f"(d[15]), "+f"(d[16]), "+f"(d[17]), "+f"(d[18]), "+f"(d[19]), "+f"(d[20]), "+f"(d[21]), "+f"(d[22]), "+f"(d[23]), "+f"(d[24]), "+f"(d[25]), "+f"(d[26]), "+f"(d[27]), "+f"(d[28]), "+f"(d[29]), "+f"(d[30]), "+f"(d[31]), "+f"(d[32]), "+f"(d[33]), "+f"(d[34]), "+f"(d[35]), "+f"(d[36]), "+f"(d[37]), "+f"(d[38]), "+f"(d[39]), "+f"(d[40]), "+f"(d[41]), "+f"(d[42]), "+f"(d[43]), "+f"(d[44]), "+f"(d[45]), "+f"(d[46]), "+f"(d[47])
    : "l"(descA), "l"(descB));
}
__device__ __forceinline__ void mma_kv_init(float (&d)[32], uint32_t a0, uint32_t a1, uint32_t a2, uint32_t a3, uint64_t descB) {
  asm volatile("wgmma.mma_async.sync.aligned.m64n64k16.f32.bf16.bf16 {%0, %1, %2, %3, %4, %5, %6, %7, %8, %9, %10, %11, %12, %13, %14, %15, %16, %17, %18, %19, %20, %21, %22, %23, %24, %25, %26, %27, %28, %29, %30, %31}, "
    "{%32, %33, %34, %35}, %36, 0, 1, 1, 0;"
    : "+f"(d[0]), "+f"(d[1]), "+f"(d[2]), "+f"(d[3]), "+f"(d[4]), "+f"(d[5]), "+f"(d[6]), "+f"(d[7]), "+f"(d[8]), "+f"(d[9]), "+f"(d[10]), "+f"(d[11]), "+f"(d[12]), "+f"(d[13]), "+f"(d[14]), "+f"(d[15]), "+f"(d[16]), "+f"(d[17]), "+f"(d[18]), "+f"(d[19]), "+f"(d[20]), "+f"(d[21]), "+f"(d[22]), "+f"(d[23]), "+f"(d[24]), "+f"(d[25]), "+f"(d[26]), "+f"(d[27]), "+f"(d[28]), "+f"(d[29]), "+f"(d[30]), "+f"(d[31])
    : "r"(a0), "r"(a1), "r"(a2), "r"(a3), "l"(descB));
}
__device__ __forceinline__ void mma_kv(float (&d)[32], uint32_t a0, uint32_t a1, uint32_t a2, uint32_t a3, uint64_t descB) {
  asm volatile("wgmma.mma_async.sync.aligned.m64n64k16.f32.bf16.bf16 {%0, %1, %2, %3, %4, %5, %6, %7, %8, %9, %10, %11, %12, %13, %14, %15, %16, %17, %18, %19, %20, %21, %22, %23, %24, %25, %26, %27, %28, %29, %30, %31}, "
    "{%32, %33, %34, %35}, %36, 1, 1, 1, 0;"
    : "+f"(d[0]), "+f"(d[1]), "+f"(d[2]), "+f"(d[3]), "+f"(d[4]), "+f"(d[5]), "+f"(d[6]), "+f"(d[7]), "+f"(d[8]), "+f"(d[9]), "+f"(d[10]), "+f"(d[11]), "+f"(d[12]), "+f"(d[13]), "+f"(d[14]), "+f"(d[15]), "+f"(d[16]), "+f"(d[17]), "+f"(d[18]), "+f"(d[19]), "+f"(d[20]), "+f"(d[21]), "+f"(d[22]), "+f"(d[23]), "+f"(d[24]), "+f"(d[25]), "+f"(d[26]), "+f"(d[27]), "+f"(d[28]), "+f"(d[29]), "+f"(d[30]), "+f"(d[31])
    : "r"(a0), "r"(a1), "r"(a2), "r"(a3), "l"(descB));
}
__device__ __forceinline__ void mma_s(float (&d)[32], uint32_t a0, uint32_t a1, uint32_t a2, uint32_t a3, uint64_t descB) {
  asm volatile("wgmma.mma_async.sync.aligned.m64n64k16.f32.bf16.bf16 {%0, %1, %2, %3, %4, %5, %6, %7, %8, %9, %10, %11, %12, %13, %14, %15, %16, %17, %18, %19, %20, %21, %22, %23, %24, %25, %26, %27, %28, %29, %30, %31}, "
    "{%32, %33, %34, %35}, %36, 1, 1, 1, 1;"
    : "+f"(d[0]), "+f"(d[1]), "+f"(d[2]), "+f"(d[3]), "+f"(d[4]), "+f"(d[5]), "+f"(d[6]), "+f"(d[7]), "+f"(d[8]), "+f"(d[9]), "+f"(d[10]), "+f"(d[11]), "+f"(d[12]), "+f"(d[13]), "+f"(d[14]), "+f"(d[15]), "+f"(d[16]), "+f"(d[17]), "+f"(d[18]), "+f"(d[19]), "+f"(d[20]), "+f"(d[21]), "+f"(d[22]), "+f"(d[23]), "+f"(d[24]), "+f"(d[25]), "+f"(d[26]), "+f"(d[27]), "+f"(d[28]), "+f"(d[29]), "+f"(d[30]), "+f"(d[31])
    : "r"(a0), "r"(a1), "r"(a2), "r"(a3), "l"(descB));
}
__device__ __forceinline__ void mma_p_init(float (&d)[28], uint32_t a0, uint32_t a1, uint32_t a2, uint32_t a3, uint64_t descB) {
  asm volatile("wgmma.mma_async.sync.aligned.m64n56k16.f32.bf16.bf16 {%0, %1, %2, %3, %4, %5, %6, %7, %8, %9, %10, %11, %12, %13, %14, %15, %16, %17, %18, %19, %20, %21, %22, %23, %24, %25, %26, %27}, "
    "{%28, %29, %30, %31}, %32, 0, 1, 1, 0;"
    : "=f"(d[0]), "=f"(d[1]), "=f"(d[2]), "=f"(d[3]), "=f"(d[4]), "=f"(d[5]), "=f"(d[6]), "=f"(d[7]), "=f"(d[8]), "=f"(d[9]), "=f"(d[10]), "=f"(d[11]), "=f"(d[12]), "=f"(d[13]), "=f"(d[14]), "=f"(d[15]), "=f"(d[16]), "=f"(d[17]), "=f"(d[18]), "=f"(d[19]), "=f"(d[20]), "=f"(d[21]), "=f"(d[22]), "=f"(d[23]), "=f"(d[24]), "=f"(d[25]), "=f"(d[26]), "=f"(d[27])
    : "r"(a0), "r"(a1), "r"(a2), "r"(a3), "l"(descB));
}
__device__ __forceinline__ void mma_p(float (&d)[28], uint32_t a0, uint32_t a1, uint32_t a2, uint32_t a3, uint64_t descB) {
  asm volatile("wgmma.mma_async.sync.aligned.m64n56k16.f32.bf16.bf16 {%0, %1, %2, %3, %4, %5, %6, %7, %8, %9, %10, %11, %12, %13, %14, %15, %16, %17, %18, %19, %20, %21, %22, %23, %24, %25, %26, %27}, "
    "{%28, %29, %30, %31}, %32, 1, 1, 1, 0;"
    : "+f"(d[0]), "+f"(d[1]), "+f"(d[2]), "+f"(d[3]), "+f"(d[4]), "+f"(d[5]), "+f"(d[6]), "+f"(d[7]), "+f"(d[8]), "+f"(d[9]), "+f"(d[10]), "+f"(d[11]), "+f"(d[12]), "+f"(d[13]), "+f"(d[14]), "+f"(d[15]), "+f"(d[16]), "+f"(d[17]), "+f"(d[18]), "+f"(d[19]), "+f"(d[20]), "+f"(d[21]), "+f"(d[22]), "+f"(d[23]), "+f"(d[24]), "+f"(d[25]), "+f"(d[26]), "+f"(d[27])
    : "r"(a0), "r"(a1), "r"(a2), "r"(a3), "l"(descB));
}
__device__ __forceinline__ void mma_o_init(float (&d)[48], uint32_t a0, uint32_t a1, uint32_t a2, uint32_t a3, uint64_t descB) {
  asm volatile("wgmma.mma_async.sync.aligned.m64n96k16.f32.bf16.bf16 {%0, %1, %2, %3, %4, %5, %6, %7, %8, %9, %10, %11, %12, %13, %14, %15, %16, %17, %18, %19, %20, %21, %22, %23, %24, %25, %26, %27, %28, %29, %30, %31, %32, %33, %34, %35, %36, %37, %38, %39, %40, %41, %42, %43, %44, %45, %46, %47}, "
    "{%48, %49, %50, %51}, %52, 0, 1, 1, 1;"
    : "=f"(d[0]), "=f"(d[1]), "=f"(d[2]), "=f"(d[3]), "=f"(d[4]), "=f"(d[5]), "=f"(d[6]), "=f"(d[7]), "=f"(d[8]), "=f"(d[9]), "=f"(d[10]), "=f"(d[11]), "=f"(d[12]), "=f"(d[13]), "=f"(d[14]), "=f"(d[15]), "=f"(d[16]), "=f"(d[17]), "=f"(d[18]), "=f"(d[19]), "=f"(d[20]), "=f"(d[21]), "=f"(d[22]), "=f"(d[23]), "=f"(d[24]), "=f"(d[25]), "=f"(d[26]), "=f"(d[27]), "=f"(d[28]), "=f"(d[29]), "=f"(d[30]), "=f"(d[31]), "=f"(d[32]), "=f"(d[33]), "=f"(d[34]), "=f"(d[35]), "=f"(d[36]), "=f"(d[37]), "=f"(d[38]), "=f"(d[39]), "=f"(d[40]), "=f"(d[41]), "=f"(d[42]), "=f"(d[43]), "=f"(d[44]), "=f"(d[45]), "=f"(d[46]), "=f"(d[47])
    : "r"(a0), "r"(a1), "r"(a2), "r"(a3), "l"(descB));
}
__device__ __forceinline__ void mma_o(float (&d)[48], uint32_t a0, uint32_t a1, uint32_t a2, uint32_t a3, uint64_t descB) {
  asm volatile("wgmma.mma_async.sync.aligned.m64n96k16.f32.bf16.bf16 {%0, %1, %2, %3, %4, %5, %6, %7, %8, %9, %10, %11, %12, %13, %14, %15, %16, %17, %18, %19, %20, %21, %22, %23, %24, %25, %26, %27, %28, %29, %30, %31, %32, %33, %34, %35, %36, %37, %38, %39, %40, %41, %42, %43, %44, %45, %46, %47}, "
    "{%48, %49, %50, %51}, %52, 1, 1, 1, 1;"
    : "+f"(d[0]), "+f"(d[1]), "+f"(d[2]), "+f"(d[3]), "+f"(d[4]), "+f"(d[5]), "+f"(d[6]), "+f"(d[7]), "+f"(d[8]), "+f"(d[9]), "+f"(d[10]), "+f"(d[11]), "+f"(d[12]), "+f"(d[13]), "+f"(d[14]), "+f"(d[15]), "+f"(d[16]), "+f"(d[17]), "+f"(d[18]), "+f"(d[19]), "+f"(d[20]), "+f"(d[21]), "+f"(d[22]), "+f"(d[23]), "+f"(d[24]), "+f"(d[25]), "+f"(d[26]), "+f"(d[27]), "+f"(d[28]), "+f"(d[29]), "+f"(d[30]), "+f"(d[31]), "+f"(d[32]), "+f"(d[33]), "+f"(d[34]), "+f"(d[35]), "+f"(d[36]), "+f"(d[37]), "+f"(d[38]), "+f"(d[39]), "+f"(d[40]), "+f"(d[41]), "+f"(d[42]), "+f"(d[43]), "+f"(d[44]), "+f"(d[45]), "+f"(d[46]), "+f"(d[47])
    : "r"(a0), "r"(a1), "r"(a2), "r"(a3), "l"(descB));
}

__device__ __forceinline__ void wg_fence() { asm volatile("wgmma.fence.sync.aligned;" ::: "memory"); }
__device__ __forceinline__ void wg_commit() { asm volatile("wgmma.commit_group.sync.aligned;" ::: "memory"); }
template <int N> __device__ __forceinline__ void wg_wait() { asm volatile("wgmma.wait_group.sync.aligned %0;" ::"n"(N) : "memory"); }
template <int N> __device__ __forceinline__ void pin(float (&d)[N]) {
#pragma unroll
  for (int i = 0; i < N; i++) asm volatile("" : "+f"(d[i])::"memory");
}
template <int N> __device__ __forceinline__ void pin(uint32_t (&d)[N]) {
#pragma unroll
  for (int i = 0; i < N; i++) asm volatile("" : "+r"(d[i])::"memory");
}
__device__ __forceinline__ uint64_t mkdesc(uint32_t lo, uint32_t hi) { return ((uint64_t)hi << 32) | lo; }
constexpr uint64_t EVICT_FIRST = 0x12F0000000000000ull;
constexpr uint32_t HI_X = (3072 >> 4) | (1u << 30);
constexpr uint32_t HI_KV = (1024 >> 4) | (1u << 30);
constexpr uint32_t HI_W = (512 >> 4) | (2u << 30);
constexpr uint32_t HI_O = (1536 >> 4) | (2u << 30);
constexpr uint32_t LO_O = (1u << 16) + ((SM_BASE + OFF_OIN) >> 4);
constexpr uint32_t LO_WQ = ((12288 >> 4) << 16) + ((SM_BASE + OFF_WQ) >> 4);
constexpr uint32_t LO_WO = ((6144 >> 4) << 16) + ((SM_BASE + OFF_WO) >> 4);
constexpr uint32_t LO_X = (1u << 16) + ((SM_BASE + OFF_X) >> 4);
constexpr uint32_t LO_KV = (1u << 16) + ((SM_BASE + OFF_KV) >> 4);

__device__ __forceinline__ uint32_t pack_bf16(float lo, float hi) {
  uint32_t r;
  asm("cvt.rn.bf16x2.f32 %0, %1, %2;" : "=r"(r) : "f"(hi), "f"(lo));
  return r;
}
__device__ __forceinline__ float ex2(float x) {
  float r;
  asm("ex2.approx.ftz.f32 %0, %1;" : "=f"(r) : "f"(x));
  return r;
}
__device__ __forceinline__ float rcp(float x) {
  float r;
  asm("rcp.approx.ftz.f32 %0, %1;" : "=f"(r) : "f"(x));
  return r;
}
__device__ __forceinline__ bool elect() {
  uint32_t p;
  asm volatile("{\n.reg .pred P;\nelect.sync _|P, 0xffffffff;\nselp.u32 %0, 1, 0, P;\n}" : "=r"(p));
  return p;
}
__device__ __forceinline__ void mbar_init(uint32_t bar, uint32_t cnt) {
  asm volatile("mbarrier.init.shared::cta.b64 [%0], %1;" ::"r"(bar), "r"(cnt) : "memory");
}
__device__ __forceinline__ void mbar_wait(uint32_t bar, uint32_t parity) {
  asm volatile(
      "{\n.reg .pred p;\n.reg .u32 n;\n"
      "mbarrier.try_wait.parity.shared::cta.b64 p, [%0], %1;\n"
      "@p bra DONE;\n"
      "mov.u32 n, 0;\n"
      "LOOP:\n"
      "mbarrier.try_wait.parity.shared::cta.b64 p, [%0], %1;\n"
      "@p bra DONE;\n"
      "add.u32 n, n, 1;\n"
      "setp.lt.u32 p, n, 0x400000;\n"
      "@p bra LOOP;\n"
      "trap;\n"
      "DONE:\n}\n" ::"r"(bar), "r"(parity)
      : "memory");
}
__device__ __forceinline__ void mbar_arrive_cluster(uint32_t bar) {
  asm volatile("mbarrier.arrive.shared::cluster.b64 _, [%0];" ::"r"(bar) : "memory");
}
__device__ __forceinline__ void mbar_expect_tx(uint32_t bar, uint32_t bytes) {
  asm volatile("mbarrier.arrive.expect_tx.shared::cta.b64 _, [%0], %1;" ::"r"(bar), "r"(bytes) : "memory");
}
__device__ __forceinline__ uint32_t mapa(uint32_t addr, uint32_t rank) {
  uint32_t r;
  asm("mapa.shared::cluster.u32 %0, %1, %2;" : "=r"(r) : "r"(addr), "r"(rank));
  return r;
}
__device__ __forceinline__ void sched_fence(uint32_t& keep, int never) {
  asm volatile("{\n.reg .pred p;\nsetp.ne.s32 p, %1, 0;\n@p mov.u32 %0, %clock;\n}" : "+r"(keep) : "r"(never) : "memory");
}
template <int ID> __device__ __forceinline__ void tok_wait() { asm volatile("bar.sync %0, %1;" ::"n"(ID), "n"(ID == T7 ? 384 : 256) : "memory"); }
template <int ID> __device__ __forceinline__ void tok_pass() { asm volatile("bar.arrive %0, %1;" ::"n"(ID), "n"(ID == T7 ? 384 : 256) : "memory"); }
__device__ __forceinline__ void fence_async() { asm volatile("fence.proxy.async.shared::cta;" ::: "memory"); }
__device__ __forceinline__ void stsm4(uint32_t addr, uint32_t r0, uint32_t r1, uint32_t r2, uint32_t r3) {
  asm volatile("stmatrix.sync.aligned.m8n8.x4.shared.b16 [%0], {%1,%2,%3,%4};" ::"r"(addr), "r"(r0), "r"(r1), "r"(r2), "r"(r3) : "memory");
}
__device__ __forceinline__ void lds128(uint32_t addr, uint32_t& r0, uint32_t& r1, uint32_t& r2, uint32_t& r3) {
  asm volatile("ld.shared.v4.b32 {%0,%1,%2,%3}, [%4];" : "=r"(r0), "=r"(r1), "=r"(r2), "=r"(r3) : "r"(addr) : "memory");
}
template <int OFF>
__device__ __forceinline__ void st_async(uint32_t addr, uint32_t bar, uint32_t r0, uint32_t r1, uint32_t r2, uint32_t r3) {
  asm volatile("st.async.shared::cluster.mbarrier::complete_tx::bytes.v4.b32 [%0+%6], {%1,%2,%3,%4}, [%5];" ::"r"(addr), "r"(r0),
               "r"(r1), "r"(r2), "r"(r3), "r"(bar), "n"(OFF)
               : "memory");
}
__device__ __forceinline__ void tma5_mc(uint32_t dst, const CUtensorMap* tm, uint32_t bar, int c2, int c4) {
  asm volatile(
      "cp.async.bulk.tensor.5d.shared::cluster.global.mbarrier::complete_tx::bytes.multicast::cluster.L2::cache_hint "
      "[%0], [%1, {0, 0, %3, 0, %4}], [%2], %5, %6;" ::"r"(dst), "l"(tm), "r"(bar), "r"(c2), "r"(c4), "h"((uint16_t)3), "l"(EVICT_FIRST)
      : "memory");
}
__device__ __forceinline__ void tma5_pf(const CUtensorMap* tm, int c2, int c4) {
  asm volatile("cp.async.bulk.prefetch.tensor.5d.L2.global [%0, {0, 0, %1, 0, %2}];" ::"l"(tm), "r"(c2), "r"(c4) : "memory");
}
__device__ __forceinline__ void tma3(uint32_t dst, const CUtensorMap* tm, uint32_t bar, int c1, int c2) {
  asm volatile("cp.async.bulk.tensor.3d.shared::cluster.global.mbarrier::complete_tx::bytes [%0], [%1, {0, %3, %4}], [%2];" ::"r"(dst),
               "l"(tm), "r"(bar), "r"(c1), "r"(c2)
               : "memory");
}

constexpr float SQRT_HD = 6.92820323027551f;
constexpr float SM_C = 1.4426950408889634f / SQRT_HD;

__device__ __forceinline__ void s_init(float (&s)[32], const uint32_t (&mk)[16], const uint32_t (&b)[16]) {
#pragma unroll
  for (int i = 0; i < 16; i++) {
    const int o = 4 * (i & 7) + 2 * (i >> 3);
    uint32_t t0, t1;
    asm("{\n.reg .b16 ml, mh, bl, bh;\n.reg .b32 m2, b2;\n"
        "mov.b32 {ml, mh}, %1;\nmov.b32 {bl, bh}, %3;\nmov.b32 m2, {ml, ml};\nmov.b32 b2, {bl, bl};\n"
        "fma.rn.bf16x2 %0, m2, %2, b2;\n}"
        : "=r"(t0)
        : "r"(mk[i]), "r"(0x40DE40DEu), "r"(b[i]));
    asm("fma.rn.bf16x2 %0, %1, %2, %3;" : "=r"(t1) : "r"(mk[i]), "r"(0x40DE40DEu), "r"(b[i]));
    s[o] = __uint_as_float(t0);
    s[o + 1] = __uint_as_float(t1);
    asm volatile("" : "+f"(s[o]), "+f"(s[o + 1])::"memory");
  }
}
__device__ __forceinline__ uint32_t pack_bias(float lo, float hi) {
  uint32_t l = __float_as_uint(fmaf(lo, SQRT_HD, 0x1p-100f)), h = __float_as_uint(fmaf(hi, SQRT_HD, 0x1p-100f));
  l = (l - (l >> 16) + 0x8000u) >> 16;
  return ((h - l + 0x8000u) & 0xffff0000u) | l;
}
__device__ __forceinline__ void rowmax_i(const float (&s)[32], int& i0, int& i1) {
#define FI(x) __float_as_int(x)
  i0 = max(FI(s[0]), FI(s[1])), i1 = max(FI(s[2]), FI(s[3]));
  int k0 = __vimax3_s32(FI(s[4]), FI(s[5]), FI(s[8])), k1 = __vimax3_s32(FI(s[6]), FI(s[7]), FI(s[10]));
  i0 = __vimax3_s32(i0, FI(s[9]), FI(s[12]));   i1 = __vimax3_s32(i1, FI(s[11]), FI(s[14]));
  k0 = __vimax3_s32(k0, FI(s[13]), FI(s[16]));  k1 = __vimax3_s32(k1, FI(s[15]), FI(s[18]));
  i0 = __vimax3_s32(i0, FI(s[17]), FI(s[20]));  i1 = __vimax3_s32(i1, FI(s[19]), FI(s[22]));
  k0 = __vimax3_s32(k0, FI(s[21]), FI(s[24]));  k1 = __vimax3_s32(k1, FI(s[23]), FI(s[26]));
  i0 = __vimax3_s32(i0, FI(s[25]), FI(s[28]));  i1 = __vimax3_s32(i1, FI(s[27]), FI(s[30]));
  i0 = __vimax3_s32(i0, k0, FI(s[29]));         i1 = __vimax3_s32(i1, k1, FI(s[31]));
#undef FI
}
__device__ __forceinline__ void quadmax_i(int& i0, int& i1, int x) {
  i0 = max(i0, __shfl_xor_sync(0xffffffffu, i0, x));
  i1 = max(i1, __shfl_xor_sync(0xffffffffu, i1, x));
}
__device__ __forceinline__ void rowmax_f(const float (&s)[32], int& i0, int& i1) {
  float m0 = fmaxf(s[0], s[1]), m1 = fmaxf(s[2], s[3]);
#pragma unroll
  for (int j = 1; j < 8; j++) {
    m0 = fmaxf(m0, fmaxf(s[4 * j], s[4 * j + 1]));
    m1 = fmaxf(m1, fmaxf(s[4 * j + 2], s[4 * j + 3]));
  }
  m0 = fmaxf(m0, __shfl_xor_sync(0xffffffffu, m0, 1));
  m1 = fmaxf(m1, __shfl_xor_sync(0xffffffffu, m1, 1));
  m0 = fmaxf(m0, __shfl_xor_sync(0xffffffffu, m0, 2));
  m1 = fmaxf(m1, __shfl_xor_sync(0xffffffffu, m1, 2));
  i0 = __float_as_int(m0), i1 = __float_as_int(m1);
}
template <int CH>
__device__ __forceinline__ void exp_rows(const float (&s)[32], uint32_t (&p)[16], int max0, int max1, uint32_t& keep, int never) {
  const float m0 = __int_as_float(max0) * -SM_C, m1 = __int_as_float(max1) * -SM_C;
  float t[32];
#pragma unroll
  for (int c = 0; c <= 16 / CH; c++) {
#pragma unroll
    for (int i = 2 * CH * c; i < 2 * CH * (c + 1) && i < 32; i++) {
      t[i] = fmaf(s[i], SM_C, (i & 2) ? m1 : m0);
      asm volatile("" : "+f"(t[i]));
    }
    if (c > 0) {
#pragma unroll
      for (int i = CH * (c - 1); i < CH * c; i++) {
        t[2 * i] = ex2(t[2 * i]), t[2 * i + 1] = ex2(t[2 * i + 1]);
        asm volatile("" : "+f"(t[2 * i]), "+f"(t[2 * i + 1]));
      }
    }
    if (c > 1) {
#pragma unroll
      for (int i = CH * (c - 2); i < CH * (c - 1); i++) {
        p[i] = pack_bf16(t[2 * i], t[2 * i + 1]);
        asm volatile("" : "+r"(p[i]));
      }
    }
    if (c < 16 / CH) sched_fence(keep, never);
  }
#pragma unroll
  for (int i = 16 - CH; i < 16; i++) p[i] = pack_bf16(t[2 * i], t[2 * i + 1]);
  pin(p);
}
__device__ __forceinline__ void issue_p(float (&o)[28], const uint32_t (&p)[16], uint32_t lo) {
#pragma unroll
  for (int ks = 0; ks < 4; ks++) {
    uint64_t db = mkdesc(lo + ks * 2, HI_KV);
    if (ks == 0) mma_p_init(o, p[0], p[1], p[2], p[3], db);
    else mma_p(o, p[4 * ks], p[4 * ks + 1], p[4 * ks + 2], p[4 * ks + 3], db);
  }
  wg_commit();
}
template <int SUM, int OFF>
__device__ __forceinline__ void normalize(const float (&o)[28], uint32_t (&f)[12]) {
  const float r0 = rcp(o[SUM]), r1 = rcp(o[SUM + 2]);
  uint32_t h0 = pack_bf16(r0, r0), h1 = pack_bf16(r1, r1);
#pragma unroll
  for (int j = 0; j < 12; j++)
    asm("mul.rn.bf16x2 %0, %1, %2;" : "=r"(f[j]) : "r"(pack_bf16(o[OFF + 2 * j], o[OFF + 2 * j + 1])), "r"((j & 1) ? h1 : h0));
}

__global__ void __cluster_dims__(2, 1, 1) __launch_bounds__(384, 1)
swin_attn_kernel(const __grid_constant__ Maps maps, const __nv_bfloat16* __restrict__ rpb, const int* __restrict__ rp_idx, int base, int never) {
  extern __shared__ __align__(1024) uint8_t smem_raw[];
  const uint32_t sb = (uint32_t)__cvta_generic_to_shared(smem_raw);
  const int tid = threadIdx.x;
  const int wg = __shfl_sync(0xffffffffu, tid >> 7, 0);
  const int warp = __shfl_sync(0xffffffffu, (tid >> 5) & 3, 0);
  const int lane = tid & 31;
  const int rank = blockIdx.x & 1;
  const int cl = blockIdx.x >> 1;
  const int ncl = gridDim.x >> 1;
  const uint32_t bars = sb + OFF_BAR;
  int extra = NWIN;
  auto read_ticket = [&]() {
    mbar_wait(bars + B_TICK, 0);
    uint32_t t;
    asm volatile("ld.shared.b32 %0, [%1];" : "=r"(t) : "r"(bars + W_TICK) : "memory");
    extra = base + __shfl_sync(0xffffffffu, t, 0);
  };
  auto window = [&](int v) { return v < base ? v : (v < base + ncl ? extra : NWIN); };
  auto prefetch = [&](int p, int win) {
    if (p < 2) tma5_pf(&maps.x, (((win >> 3) & ~7) + 4 + 4 * rank) & 511, (win * 4 + 2 + 2 * p) & 255);
    else tma5_pf(&maps.mask, 0, 2 * win + rank);
  };
  auto load = [&](int p, int win, int a) {
    if (p < 2)
      tma5_mc(sb + OFF_X + a * STAGE + rank * 12288 + p * 6144, &maps.x, bars + B_XFULL + 8 * a,
              (((win >> 3) & ~7) + 4 + 4 * rank) & 511, (win * 4 + 2 + 2 * p) & 255);
    else tma5_mc(sb + OFF_MASK + a * STAGE + rank * 4096, &maps.mask, bars + B_XFULL + 8 * a, 0, 2 * win + rank);
  };
  auto load_wkv = [&](int b) {
    tma3(sb + OFF_KV + (b < 3 ? b * 12288 : STAGE + (b - 3) * 12288), &maps.wqkv, bars + B_WKV + 8 * (b >> 1), 0,
         (b < 3 ? 6 : 9) + b + 3 * rank);
  };
  auto startup_loads = [&]() {
    if ((sb & 0x3FFFF) != SM_BASE) __trap();
    if (blockIdx.x == 0) asm volatile("st.relaxed.gpu.global.u32 [%0], 0;" ::"l"(&g_ticket) : "memory");
    mbar_expect_tx(bars + B_XFULL, X_BYTES);
    mbar_expect_tx(bars + B_M0, M_BYTES);
    mbar_expect_tx(bars + B_WKV + 8, 24576);
    load_wkv(2);
    load_wkv(3);
    tma5_mc(sb + OFF_MASK + rank * 4096, &maps.mask, bars + B_M0, 0, 2 * cl + rank);
    mbar_expect_tx(bars + B_WQ, 36864);
    for (int nb = 0; nb < 3; nb++) tma3(sb + OFF_WQ + nb * 12288, &maps.wqkv, bars + B_WQ, 0, 3 * rank + nb);
    mbar_expect_tx(bars + B_WKV + 16, 24576);
    load_wkv(4);
    load_wkv(5);
    mbar_expect_tx(bars + B_XFULL + 8, X_BYTES + M_BYTES);
    for (int p = 0; p < 3; p++) load(p, cl + ncl, 1);
    mbar_expect_tx(bars + B_TICK, 4);
    mbar_expect_tx(bars + B_WO, 36864);
    tma3(sb + OFF_WO, &maps.wo, bars + B_WO, 96 * rank, 3 * rank);
    for (int nb = 0; nb < 3; nb++)
      asm volatile("cp.async.bulk.tensor.5d.shared::cluster.global.mbarrier::complete_tx::bytes [%0], [%1, {%3, 0, 0, 0, %4}], [%2];" ::"r"(
                       sb + OFF_WO + 18432 + nb * 6144), "l"(&maps.wop), "r"(bars + B_WO), "r"(96 * rank + 32 * nb), "r"(3 * (rank ^ 1))
                   : "memory");
  };
  if (wg == KV_WG && warp == 3) {
    if (elect()) {
#pragma unroll
      for (int k = 0; k < 15; k++) mbar_init(bars + 8 * k, (k >> 1) == B_OEMPTY / 16 ? 4 : 1);
      asm volatile("fence.mbarrier_init.release.cluster;" ::: "memory");
    }
    __syncwarp();
  }
  asm volatile("barrier.cluster.arrive.relaxed.aligned;" ::: "memory");

  if (wg == KV_WG) {
    if (warp == 3 && elect()) {
      fence_async();
      mbar_expect_tx(bars + B_WKV, 24576);
      load_wkv(0);
      load_wkv(1);
    }
    __syncwarp();
    asm volatile("barrier.cluster.wait.aligned;" ::: "memory");
    if (elect()) {
      if (warp < 2) load(warp, cl, 0);
      else if (warp == 3) startup_loads();
    }
    __syncwarp();
    asm volatile("setmaxnreg.inc.sync.aligned.u32 216;");
    uint32_t w[3][48];
    auto load_frags = [&](int s) {
      const uint32_t la = sb + OFF_KV + (warp >> 1) * 12288 + (8 * (lane >> 4) + (lane & 7)) * 64 +
                          (((2 * (warp & 1) + ((lane >> 3) & 1)) ^ ((lane & 7) >> 1)) << 4);
      mbar_wait(bars + B_WKV + 8 * s, 0);
#pragma unroll
      for (int ks = 0; ks < 12; ks++)
        asm volatile("ldmatrix.sync.aligned.m8n8.x4.trans.shared.b16 {%0,%1,%2,%3}, [%4];"
                     : "=r"(w[s][4 * ks]), "=r"(w[s][4 * ks + 1]), "=r"(w[s][4 * ks + 2]), "=r"(w[s][4 * ks + 3])
                     : "r"(la + s * 24576 + (s == 2 || (s == 1 && warp >= 2) ? STAGE - 36864 : 0) + ks * 1024)
                     : "memory");
    };
    load_frags(0);
    uint32_t sta[4];
#pragma unroll
    for (int jj = 0; jj < 4; jj++) {
      sta[jj] = sb + OFF_KV + (16 * warp + (lane & 15)) * 128 + (((2 * jj + (lane >> 4)) ^ (lane & 7)) << 4);
      asm volatile("" : "+r"(sta[jj]));
    }
    const uint32_t xe_rem = mapa(bars + B_XEMPTY, rank ^ 1);
    const uint32_t v1off = warp > 0 ? 1024 : 0;

#define SF sched_fence(sta[0], never)
    float acc[32];
    uint32_t pk[16];
    auto store = [&](uint32_t off) {
#pragma unroll
      for (int jj = 0; jj < 4; jj++) stsm4(sta[jj] + off, pk[4 * jj], pk[4 * jj + 1], pk[4 * jj + 2], pk[4 * jj + 3]);
    };
    auto issue = [&](int s, uint32_t xd, bool st, uint32_t off) {
#pragma unroll
      for (int ks = 0; ks < 12; ks++) {
        uint64_t db = mkdesc(xd + (((ks >> 2) * 1024 + (ks & 3) * 32) >> 4), HI_X);
        if (ks == 0) mma_kv_init(acc, w[s][0], w[s][1], w[s][2], w[s][3], db);
        else mma_kv(acc, w[s][4 * ks], w[s][4 * ks + 1], w[s][4 * ks + 2], w[s][4 * ks + 3], db);
        if (ks == 1 && st) {
          __syncwarp();
          store(off);
          __syncwarp();
        }
      }
      wg_commit();
    };
    auto convert = [&]() {
      wg_wait<0>();
      pin(acc);
#pragma unroll
      for (int j = 0; j < 16; j++) pk[j] = pack_bf16(acc[2 * j], acc[2 * j + 1]);
      pin(pk);
    };

    mbar_wait(bars + B_XFULL, 0);
    wg_fence();
    issue(0, LO_X, false, 0);
    load_frags(1);
    int nxt = cl + ncl;
    uint32_t ph = 0;
    uint32_t ticket = 0;
    auto step = [&](auto A) -> bool {
      constexpr int a = decltype(A)::value;
      constexpr uint32_t xd = LO_X + a * (STAGE >> 4);
      if (nxt + ncl >= base && nxt < base) read_ticket();
      const bool more = window(nxt) < NWIN;
      const int wn2 = window(nxt + ncl);
      convert();
      wg_fence();
      SF;
      tok_wait<T2>();
      issue(1, xd, true, a * STAGE);
      tok_pass<T3>();
      if (warp < 3 && wn2 < NWIN && elect()) prefetch(warp, wn2);
      __syncwarp();
      const bool first = a == 0 && nxt == cl + ncl;
      convert();
      SF;
      if (!first) tok_wait<T7>();
      store(a * STAGE + 8192);
      fence_async();
      if (first) {
        load_frags(2);
        asm volatile("bar.sync %0, 128;" ::"n"((int)BAR_STAGE) : "memory");
        asm volatile("st.shared.v4.b32 [%0], {%1,%1,%1,%1};" ::"r"(sb + OFF_KV + (warp >> 1) * STAGE + 144 * 128 + (tid & 63) * 16), "r"(0x3F803F80u) : "memory");
      }
      wg_fence();
      tok_wait<T5>();
      issue(2, xd, false, 0);
      tok_pass<T6>();
      if (!more) {
        convert();
        store(a * STAGE + 16384 + v1off);
        fence_async();
        return false;
      }
      mbar_wait(bars + B_XFULL + 8 * (a ^ 1), a ? ph ^ 1 : ph);
      convert();
      wg_fence();
      SF;
      tok_wait<T0>();
      if (tid == KV_WG * 128 && wn2 < NWIN) mbar_arrive_cluster(xe_rem + 8 * a);
      issue(0, LO_X + (a ^ 1) * (STAGE >> 4), true, a * STAGE + 16384 + v1off);
      tok_pass<T1>();
      fence_async();
      nxt += ncl;
      if (wn2 < NWIN) {
        mbar_wait(bars + B_XEMPTY + 8 * a, ph);
        if (elect()) {
          if (warp < 3) {
            load(warp, wn2, a);
          } else {
            mbar_expect_tx(bars + B_XFULL + 8 * a, X_BYTES + M_BYTES);
            if (rank == 0 && nxt + 3 * ncl >= base) {
              if (nxt + 2 * ncl < base) {
                asm volatile("atom.global.inc.u32 %0, [%1], %2;" : "=r"(ticket) : "l"(&g_ticket), "r"(ncl - 1) : "memory");
              } else if (nxt + ncl < base) {
#pragma unroll
                for (int r = 0; r < 2; r++)
                  asm volatile("st.async.shared::cluster.mbarrier::complete_tx::bytes.b32 [%0], %1, [%2];" ::"r"(mapa(bars + W_TICK, r)),
                               "r"(ticket), "r"(mapa(bars + B_TICK, r))
                               : "memory");
              }
            }
          }
        }
        __syncwarp();
      }
      return true;
    };
    while (step(IC<0>{}) && step(IC<1>{})) ph ^= 1;
    tok_wait<T0>();
    tok_pass<T1>();
    tok_wait<T2>();
    tok_pass<T3>();
    tok_wait<T7>();
    tok_wait<T5>();
  } else {
    const int a = wg - (KV_WG == 0 ? 1 : 0);
    const int g = lane >> 2, q = lane & 3;
    const uint32_t bar = bars + 8 * a;
    if (a == 0) {
      tok_pass<T2>();
      tok_pass<T5>();
    }
    asm volatile("setmaxnreg.dec.sync.aligned.u32 144;");
    uint32_t braw[32];
    {
      const int ty = 4 * (warp >> 1) + (g >> 1), tx = 4 * (warp & 1) + (g & 1);
      const int* ip = rp_idx + (ty * 8 + tx) * 64 + 8 * q;
#pragma unroll
      for (int c = 0; c < 8; c++)
        asm volatile("ld.global.nc.v4.b32 {%0,%1,%2,%3}, [%4];"
                     : "=r"(braw[4 * c]), "=r"(braw[4 * c + 1]), "=r"(braw[4 * c + 2]), "=r"(braw[4 * c + 3])
                     : "l"(ip + (c >> 2) * 128 + ((c >> 1) & 1) * 32 + (c & 1) * 4));
      const int e = a * 128 + (tid & 127);
      uint32_t v = 0;
      if (e < 225) asm volatile("ld.global.nc.b32 %0, [%1];" : "=r"(v) : "l"(reinterpret_cast<const uint32_t*>(rpb) + e * 2 + rank));
      asm volatile("st.shared.b32 [%0], %1;" ::"r"(sb + OFF_RPB + e * 4), "r"(v) : "memory");
      tok_wait<BAR_BIAS>();
#pragma unroll
      for (int j = 0; j < 32; j++)
        asm volatile("ld.shared.b32 %0, [%1];" : "=r"(braw[j]) : "r"(sb + OFF_RPB + braw[j] * 4) : "memory");
    }
    asm volatile("barrier.cluster.wait.aligned;" ::: "memory");

    const int mrow = 16 * warp + (g >> 1) + 4 * (g & 1);
#undef SF
#define SF sched_fence(mk_addr, never)
    uint32_t mk_addr = sb + OFF_MASK + a * STAGE + mrow * 128 + ((q ^ (mrow & 7)) << 4);
    const uint32_t ostage = sb + OFF_OIN + a * STAGE + warp * 3072;
    const uint32_t ost = ostage + ((lane >> 3) & 1) * 1536 + (lane & 7) * 64 + (((lane >> 4) ^ ((lane & 7) >> 1)) << 4);
    const uint32_t oin_rem = mapa(ostage + g * 64 + ((q ^ (g >> 1)) << 4), rank ^ 1);
    const uint32_t bar_rem = mapa(bar, rank ^ 1);

    auto store_out = [&](int win) {
      fence_async();
      __syncwarp();
      if (elect()) {
        int yy = (((win >> 3) & ~7) + 4 + 4 * (warp >> 1)) & 511;
        int xh = (win * 4 + 2 + 2 * (warp & 1)) & 255;
        asm volatile("cp.async.bulk.tensor.5d.global.shared::cta.bulk_group [%0, {0, 0, %2, %3, %4}], [%1];" ::"l"(&maps.out), "r"(ostage),
                     "r"(yy), "r"(3 * rank), "r"(xh)
                     : "memory");
        asm volatile("cp.async.bulk.commit_group;" ::: "memory");
      }
      __syncwarp();
    };
    auto release_oin = [&]() {
      if (elect()) {
        asm volatile("cp.async.bulk.wait_group.read 0;" ::: "memory");
        if (warp == 0) mbar_expect_tx(bar + B_OFULL, O_BYTES);
        mbar_arrive_cluster(bar_rem + B_OEMPTY);
      }
      __syncwarp();
    };
    float qa[48];
    uint32_t bias0[16], bias1[16];
    uint32_t mk[16];
    auto load_mask = [&](uint32_t z) {
#pragma unroll
      for (int c = 0; c < 4; c++)
        lds128((c & 1 ? mk_addr ^ (64 + z) : mk_addr) + (c >> 1) * 1024, mk[4 * c], mk[4 * c + 1], mk[4 * c + 2], mk[4 * c + 3]);
    };
    auto clamp_mask = [&]() {
      SF;
#pragma unroll
      for (int j = 0; j < 16; j++) asm("max.NaN.bf16x2 %0, %0, %1;" : "+r"(mk[j]) : "r"(0xFD80FD80u));
      pin(mk);
    };
    auto issue_q = [&](uint32_t ua, bool tok, int win) {
#pragma unroll
      for (int ks = 0; ks < 12; ks++) {
        if (ks == Q_SPLIT && tok) {
          tok_pass<T4>();
          store_out(win);
          tok_wait<T7>();
          wg_fence();
        }
        uint64_t da = mkdesc(ua + LO_X + (((ks >> 2) * 1024 + (ks & 3) * 32) >> 4), HI_X);
        uint64_t db = mkdesc(LO_WQ + ks * 64, HI_W);
        if (ks == 0) mma_q_init(qa, da, db);
        else mma_q(qa, da, db);
      }
      wg_commit();
      if (tok) tok_pass<T5>();
    };
#pragma unroll
    for (int j = 0; j < 16; j++) {
      const uint32_t b0 = braw[2 * j], b1 = braw[2 * j + 1];
      bias0[j] = pack_bias(__uint_as_float(b0 << 16), __uint_as_float(b1 << 16));
      bias1[j] = pack_bias(__uint_as_float(b0 & 0xffff0000u), __uint_as_float(b1 & 0xffff0000u));
    }
    pin(bias0);
    pin(bias1);
    SF;
    mbar_wait(bars + B_WQ, 0);
    wg_fence();
    if (a == 0) tok_wait<T3>();
    else tok_wait<T1>();
    issue_q(a * (STAGE >> 4), false, 0);
    if (a == 0) mbar_wait(bars + B_M0, 0);
    else tok_pass<T2>();
    load_mask(0);
    if (a == 1) {
      tok_wait<T3>();
      tok_pass<T4>();
      tok_pass<T5>();
      tok_wait<T7>();
    }
    clamp_mask();
    uint32_t ph = 0;
    int win = cl + a * ncl;
    for (;; win += 2 * ncl, ph ^= 1) {
      const uint32_t ua = a * (STAGE >> 4) + (win >> 20);
      const uint32_t kd = ua + LO_KV;
      float s0[32], s1[32];
      wg_wait<0>();
      pin(qa);
      uint32_t q0[12], q1[12];
#pragma unroll
      for (int j = 0; j < 12; j++) q0[j] = pack_bf16(qa[2 * j], qa[2 * j + 1]);
#pragma unroll
      for (int j = 0; j < 12; j++) q1[j] = pack_bf16(qa[24 + 2 * j], qa[25 + 2 * j]);
      pin(q0);
      pin(q1);
      s_init(s0, mk, bias0);
      s_init(s1, mk, bias1);
      wg_fence();
      tok_wait<T6>();
#pragma unroll
      for (int ks = 0; ks < 3; ks++)
        mma_s(s0, q0[4 * ks], q0[4 * ks + 1], q0[4 * ks + 2], q0[4 * ks + 3], mkdesc(kd + ks * 128, HI_KV));
      wg_commit();
#pragma unroll
      for (int ks = 0; ks < 3; ks++)
        mma_s(s1, q1[4 * ks], q1[4 * ks + 1], q1[4 * ks + 2], q1[4 * ks + 3], mkdesc(kd + (3 + ks) * 128, HI_KV));
      wg_commit();
      tok_pass<T0>();
      release_oin();
      int x0, x1, y0, y1;
      uint32_t p0[16], p1[16];
      wg_wait<1>();
      pin(s0);
      pin(q0);
      rowmax_i(s0, x0, x1);
      quadmax_i(x0, x1, 1);
      wg_wait<0>();
      pin(s1);
      pin(q1);
      rowmax_i(s1, y0, y1);
      quadmax_i(x0, x1, 2);
      quadmax_i(y0, y1, 1);
      quadmax_i(y0, y1, 2);
      if (__builtin_expect(__any_sync(0xffffffffu, (x0 | x1 | y0 | y1) < 0), 0)) {
        rowmax_f(s0, x0, x1);
        rowmax_f(s1, y0, y1);
      }
      exp_rows<EXP_CH>(s0, p0, x0, x1, mk_addr, never);
      exp_rows<EXP_CH>(s1, p1, y0, y1, mk_addr, never);
      float o0[28], o1[28];
      wg_fence();
      SF;
      tok_wait<T4>();
      issue_p(o0, p0, kd + ((96 * 128) >> 4));
      issue_p(o1, p1, kd + ((144 * 128) >> 4));
      tok_pass<T7>();
      mbar_wait(bar + B_OEMPTY, ph);
      uint32_t f0[12], f1[12];
      wg_wait<1>();
      pin(o0);
      pin(p0);
      normalize<24, 0>(o0, f0);
      st_async<0>(oin_rem, bar_rem + B_OFULL, f0[0], f0[2], f0[4], f0[6]);
      st_async<1536>(oin_rem, bar_rem + B_OFULL, f0[1], f0[3], f0[5], f0[7]);
      wg_wait<0>();
      pin(o1);
      pin(p1);
      normalize<0, 4>(o1, f1);
      st_async<512>(oin_rem, bar_rem + B_OFULL, f0[8], f0[10], f1[0], f1[2]);
      st_async<2048>(oin_rem, bar_rem + B_OFULL, f0[9], f0[11], f1[1], f1[3]);
      st_async<1024>(oin_rem, bar_rem + B_OFULL, f1[4], f1[6], f1[8], f1[10]);
      st_async<2560>(oin_rem, bar_rem + B_OFULL, f1[5], f1[7], f1[9], f1[11]);
      pin(f0);
      pin(f1);
      float (&oa)[48] = qa;
      int wn1 = 0, wn2 = 0;
      if ((unsigned)(win - 2 * ncl) >= (unsigned)(base - 4 * ncl)) {
        if (win < 2 * ncl) {
          mbar_wait(bars + B_WO, 0);
        } else {
          read_ticket();
          wn1 = window(win + ncl), wn2 = window(win + 2 * ncl);
        }
      }
      const bool last = wn1 >= NWIN;
      if (!last) tok_wait<T1>();
      wg_fence();
#pragma unroll
      for (int ks = 0; ks < 3; ks++) {
        uint64_t db = mkdesc(LO_WO + ks * 64, HI_W);
        if (ks == 0) mma_o_init(oa, f0[0], f0[1], f0[2], f0[3], db);
        else mma_o(oa, f0[4 * ks], f0[4 * ks + 1], f0[4 * ks + 2], f0[4 * ks + 3], db);
      }
#pragma unroll
      for (int ks = 0; ks < 3; ks++)
        mma_o(oa, f1[4 * ks], f1[4 * ks + 1], f1[4 * ks + 2], f1[4 * ks + 3], mkdesc(LO_WO + (3 + ks) * 64, HI_W));
      mbar_wait(bar + B_OFULL, ph);
      asm volatile("fence.proxy.async::generic.acquire.sync_restrict::shared::cluster.cluster;" ::: "memory");
      wg_fence();
#pragma unroll
      for (int ks = 0; ks < 6; ks++)
        mma_q(oa, mkdesc(ua + LO_O + (((ks >> 1) * 512 + (ks & 1) * 32) >> 4), HI_O), mkdesc(LO_WO + (18432 >> 4) + ks * 64, HI_W));
      wg_commit();
      if (!last) tok_pass<T2>();
      load_mask(win >> 20);
      wg_wait<0>();
      pin(oa);
      pin(f0);
      pin(f1);
#pragma unroll
      for (int jj = 0; jj < 6; jj++)
        stsm4((jj & 1 ? ost ^ (32 + (win >> 20)) : ost) + (jj >> 1) * 512, pack_bf16(oa[8 * jj], oa[8 * jj + 1]), pack_bf16(oa[8 * jj + 2], oa[8 * jj + 3]),
              pack_bf16(oa[8 * jj + 4], oa[8 * jj + 5]), pack_bf16(oa[8 * jj + 6], oa[8 * jj + 7]));
      if (wn2 >= NWIN) {
        if (!last) {
          tok_wait<T3>();
          tok_pass<T4>();
          tok_pass<T5>();
          tok_wait<T7>();
        }
        break;
      }
      wg_fence();
      tok_wait<T3>();
      issue_q(ua, true, win);
      clamp_mask();
    }
    store_out(window(win));
    asm volatile("cp.async.bulk.wait_group.read 0;" ::: "memory");
    __syncwarp();
  }
}

typedef CUresult (*EncodeFn)(CUtensorMap*, CUtensorMapDataType, cuuint32_t, void*, const cuuint64_t*, const cuuint64_t*,
                             const cuuint32_t*, const cuuint32_t*, CUtensorMapInterleave, CUtensorMapSwizzle,
                             CUtensorMapL2promotion, CUtensorMapFloatOOBfill);

void encode_map(EncodeFn encode, CUtensorMap* m, void* p, int rank, const cuuint64_t* dim, const cuuint64_t* str,
                const cuuint32_t* box, CUtensorMapSwizzle sw) {
  const cuuint32_t es[5] = {1, 1, 1, 1, 1};
  CUresult r = encode(m, CU_TENSOR_MAP_DATA_TYPE_BFLOAT16, rank, p, dim, str, box, es, CU_TENSOR_MAP_INTERLEAVE_NONE, sw,
                      CU_TENSOR_MAP_L2_PROMOTION_L2_128B, CU_TENSOR_MAP_FLOAT_OOB_FILL_NONE);
  if (r != CUDA_SUCCESS) fprintf(stderr, "tensor map encode failed: %d\n", (int)r);
}

}

extern "C" void kernel_launch(void* const* d_in, const int* in_sizes, int n_in, void* d_out, int out_size) {
  static EncodeFn encode = nullptr;
  static int grid = 0;
  if (!encode) {
    cudaDriverEntryPointQueryResult qr;
    void* fn = nullptr;
    cudaGetDriverEntryPoint("cuTensorMapEncodeTiled", &fn, cudaEnableDefault, &qr);
    encode = (EncodeFn)fn;
    cudaFuncSetAttribute(swin_attn_kernel, cudaFuncAttributeMaxDynamicSharedMemorySize, SMEM_BYTES);
    cudaLaunchConfig_t cfg = {};
    cfg.gridDim = dim3(132);
    cfg.blockDim = dim3(384);
    cfg.dynamicSmemBytes = SMEM_BYTES;
    cudaLaunchAttribute at;
    at.id = cudaLaunchAttributeClusterDimension;
    at.val.clusterDim.x = 2;
    at.val.clusterDim.y = 1;
    at.val.clusterDim.z = 1;
    cfg.attrs = &at;
    cfg.numAttrs = 1;
    int ncl = 0;
    if (cudaOccupancyMaxActiveClusters(&ncl, swin_attn_kernel, &cfg) != cudaSuccess || ncl < 1) {
      (void)cudaGetLastError();
      ncl = 66;
    }
    if (ncl > 256) ncl = 256;
    grid = 2 * ncl;
  }
  Maps maps;
  {
    const cuuint64_t dim[5] = {64, 2, 512, 3, 256}, str[4] = {384, 512 * 384, 128, 768};
    const cuuint32_t box[5] = {64, 2, 4, 3, 2};
    encode_map(encode, &maps.x, d_in[0], 5, dim, str, box, CU_TENSOR_MAP_SWIZZLE_128B);
  }
  {
    const cuuint64_t dim[5] = {64, 4, 2, 4, 8192}, str[4] = {1024, 128, 256, 4096};
    const cuuint32_t box[5] = {64, 4, 2, 4, 1};
    encode_map(encode, &maps.mask, d_in[5], 5, dim, str, box, CU_TENSOR_MAP_SWIZZLE_128B);
  }
  {
    const cuuint64_t dim[5] = {32, 2, 512, 6, 256}, str[4] = {384, 512 * 384, 64, 768};
    const cuuint32_t box[5] = {32, 2, 4, 3, 2};
    encode_map(encode, &maps.out, d_out, 5, dim, str, box, CU_TENSOR_MAP_SWIZZLE_64B);
  }
  {
    const cuuint64_t dim[3] = {32, 192, 18}, str[2] = {576 * 2, 64};
    const cuuint32_t box[3] = {32, 192, 1};
    encode_map(encode, &maps.wqkv, d_in[1], 3, dim, str, box, CU_TENSOR_MAP_SWIZZLE_64B);
    const cuuint64_t dim2[3] = {32, 192, 6}, str2[2] = {192 * 2, 64};
    const cuuint32_t box2[3] = {32, 96, 3};
    encode_map(encode, &maps.wo, d_in[2], 3, dim2, str2, box2, CU_TENSOR_MAP_SWIZZLE_64B);
    const cuuint64_t dim3_[5] = {192, 2, 4, 4, 6}, str3[4] = {384, 8 * 384, 2 * 384, 32 * 384};
    const cuuint32_t box3[5] = {32, 2, 4, 4, 3};
    encode_map(encode, &maps.wop, d_in[2], 5, dim3_, str3, box3, CU_TENSOR_MAP_SWIZZLE_64B);
  }
  swin_attn_kernel<<<grid, 384, SMEM_BYTES>>>(maps, (const __nv_bfloat16*)d_in[3], (const int*)d_in[4], NWIN / (grid / 2) * (grid / 2), 0);
}
```

```cpp
#include <cuda_runtime.h>
#include <cuda_bf16.h>
#include <cuda.h>
#include <stdint.h>
#include <stdio.h>

namespace {

constexpr int NWIN = 4096;
constexpr int KV_WG = 0;
constexpr int Q_SPLIT = 4;
constexpr int EXP_CH = 4;

constexpr uint32_t SM_BASE  = 1024;
constexpr uint32_t OFF_WQ   = 0;
constexpr uint32_t OFF_WO   = 36864;
constexpr uint32_t STAGE    = 70656;
constexpr uint32_t OFF_X    = 73728;
constexpr uint32_t X_BYTES  = 24576;
constexpr uint32_t OFF_MASK = OFF_X + X_BYTES;
constexpr uint32_t M_BYTES  = 8192;
constexpr uint32_t OFF_KV   = OFF_MASK + M_BYTES;
constexpr uint32_t OFF_OIN  = OFF_KV + 25600;
constexpr uint32_t O_BYTES  = 12288;
constexpr uint32_t OFF_BAR  = 215040;
constexpr uint32_t OFF_RPB  = OFF_BAR + 1024;
constexpr uint32_t SMEM_BYTES = OFF_RPB + 1024;
constexpr uint32_t B_XFULL = 0, B_XEMPTY = 16, B_OFULL = 32, B_OEMPTY = 48, B_WKV = 64  , B_WQ = 88, B_WO = 96,
                   B_TICK = 104, B_M0 = 112, W_TICK = 120;
enum { T0 = 1, T1, T2, T3, T4, T5, T6, T7, BAR_BIAS, BAR_STAGE };

__device__ unsigned int g_ticket;

template <int V> struct IC { static constexpr int value = V; };
struct Maps { CUtensorMap x, mask, out, wqkv, wo, wop; };

__device__ __forceinline__ void mma_q_init(float (&d)[48], uint64_t descA, uint64_t descB) {
  asm volatile("wgmma.mma_async.sync.aligned.m64n96k16.f32.bf16.bf16 {%0, %1, %2, %3, %4, %5, %6, %7, %8, %9, %10, %11, %12, %13, %14, %15, %16, %17, %18, %19, %20, %21, %22, %23, %24, %25, %26, %27, %28, %29, %30, %31, %32, %33, %34, %35, %36, %37, %38, %39, %40, %41, %42, %43, %44, %45, %46, %47}, "
    "%48, %49, 0, 1, 1, 0, 1;"
    : "+f"(d[0]), "+f"(d[1]), "+f"(d[2]), "+f"(d[3]), "+f"(d[4]), "+f"(d[5]), "+f"(d[6]), "+f"(d[7]), "+f"(d[8]), "+f"(d[9]), "+f"(d[10]), "+f"(d[11]), "+f"(d[12]), "+f"(d[13]), "+f"(d[14]), "+f"(d[15]), "+f"(d[16]), "+f"(d[17]), "+f"(d[18]), "+f"(d[19]), "+f"(d[20]), "+f"(d[21]), "+f"(d[22]), "+f"(d[23]), "+f"(d[24]), "+f"(d[25]), "+f"(d[26]), "+f"(d[27]), "+f"(d[28]), "+f"(d[29]), "+f"(d[30]), "+f"(d[31]), "+f"(d[32]), "+f"(d[33]), "+f"(d[34]), "+f"(d[35]), "+f"(d[36]), "+f"(d[37]), "+f"(d[38]), "+f"(d[39]), "+f"(d[40]), "+f"(d[41]), "+f"(d[42]), "+f"(d[43]), "+f"(d[44]), "+f"(d[45]), "+f"(d[46]), "+f"(d[47])
    : "l"(descA), "l"(descB));
}
__device__ __forceinline__ void mma_q(float (&d)[48], uint64_t descA, uint64_t descB) {
  asm volatile("wgmma.mma_async.sync.aligned.m64n96k16.f32.bf16.bf16 {%0, %1, %2, %3, %4, %5, %6, %7, %8, %9, %10, %11, %12, %13, %14, %15, %16, %17, %18, %19, %20, %21, %22, %23, %24, %25, %26, %27, %28, %29, %30, %31, %32, %33, %34, %35, %36, %37, %38, %39, %40, %41, %42, %43, %44, %45, %46, %47}, "
    "%48, %49, 1, 1, 1, 0, 1;"
    : "+f"(d[0]), "+f"(d[1]), "+f"(d[2]), "+f"(d[3]), "+f"(d[4]), "+f"(d[5]), "+f"(d[6]), "+f"(d[7]), "+f"(d[8]), "+f"(d[9]), "+f"(d[10]), "+f"(d[11]), "+f"(d[12]), "+f"(d[13]), "+f"(d[14]), "+f"(d[15]), "+f"(d[16]), "+f"(d[17]), "+f"(d[18]), "+f"(d[19]), "+f"(d[20]), "+f"(d[21]), "+f"(d[22]), "+f"(d[23]), "+f"(d[24]), "+f"(d[25]), "+f"(d[26]), "+f"(d[27]), "+f"(d[28]), "+f"(d[29]), "+f"(d[30]), "+f"(d[31]), "+f"(d[32]), "+f"(d[33]), "+f"(d[34]), "+f"(d[35]), "+f"(d[36]), "+f"(d[37]), "+f"(d[38]), "+f"(d[39]), "+f"(d[40]), "+f"(d[41]), "+f"(d[42]), "+f"(d[43]), "+f"(d[44]), "+f"(d[45]), "+f"(d[46]), "+f"(d[47])
    : "l"(descA), "l"(descB));
}
__device__ __forceinline__ void mma_kv_init(float (&d)[32], uint32_t a0, uint32_t a1, uint32_t a2, uint32_t a3, uint64_t descB) {
  asm volatile("wgmma.mma_async.sync.aligned.m64n64k16.f32.bf16.bf16 {%0, %1, %2, %3, %4, %5, %6, %7, %8, %9, %10, %11, %12, %13, %14, %15, %16, %17, %18, %19, %20, %21, %22, %23, %24, %25, %26, %27, %28, %29, %30, %31}, "
    "{%32, %33, %34, %35}, %36, 0, 1, 1, 0;"
    : "+f"(d[0]), "+f"(d[1]), "+f"(d[2]), "+f"(d[3]), "+f"(d[4]), "+f"(d[5]), "+f"(d[6]), "+f"(d[7]), "+f"(d[8]), "+f"(d[9]), "+f"(d[10]), "+f"(d[11]), "+f"(d[12]), "+f"(d[13]), "+f"(d[14]), "+f"(d[15]), "+f"(d[16]), "+f"(d[17]), "+f"(d[18]), "+f"(d[19]), "+f"(d[20]), "+f"(d[21]), "+f"(d[22]), "+f"(d[23]), "+f"(d[24]), "+f"(d[25]), "+f"(d[26]), "+f"(d[27]), "+f"(d[28]), "+f"(d[29]), "+f"(d[30]), "+f"(d[31])
    : "r"(a0), "r"(a1), "r"(a2), "r"(a3), "l"(descB));
}
__device__ __forceinline__ void mma_kv(float (&d)[32], uint32_t a0, uint32_t a1, uint32_t a2, uint32_t a3, uint64_t descB) {
  asm volatile("wgmma.mma_async.sync.aligned.m64n64k16.f32.bf16.bf16 {%0, %1, %2, %3, %4, %5, %6, %7, %8, %9, %10, %11, %12, %13, %14, %15, %16, %17, %18, %19, %20, %21, %22, %23, %24, %25, %26, %27, %28, %29, %30, %31}, "
    "{%32, %33, %34, %35}, %36, 1, 1, 1, 0;"
    : "+f"(d[0]), "+f"(d[1]), "+f"(d[2]), "+f"(d[3]), "+f"(d[4]), "+f"(d[5]), "+f"(d[6]), "+f"(d[7]), "+f"(d[8]), "+f"(d[9]), "+f"(d[10]), "+f"(d[11]), "+f"(d[12]), "+f"(d[13]), "+f"(d[14]), "+f"(d[15]), "+f"(d[16]), "+f"(d[17]), "+f"(d[18]), "+f"(d[19]), "+f"(d[20]), "+f"(d[21]), "+f"(d[22]), "+f"(d[23]), "+f"(d[24]), "+f"(d[25]), "+f"(d[26]), "+f"(d[27]), "+f"(d[28]), "+f"(d[29]), "+f"(d[30]), "+f"(d[31])
    : "r"(a0), "r"(a1), "r"(a2), "r"(a3), "l"(descB));
}
__device__ __forceinline__ void mma_s(float (&d)[32], uint32_t a0, uint32_t a1, uint32_t a2, uint32_t a3, uint64_t descB) {
  asm volatile("wgmma.mma_async.sync.aligned.m64n64k16.f32.bf16.bf16 {%0, %1, %2, %3, %4, %5, %6, %7, %8, %9, %10, %11, %12, %13, %14, %15, %16, %17, %18, %19, %20, %21, %22, %23, %24, %25, %26, %27, %28, %29, %30, %31}, "
    "{%32, %33, %34, %35}, %36, 1, 1, 1, 1;"
    : "+f"(d[0]), "+f"(d[1]), "+f"(d[2]), "+f"(d[3]), "+f"(d[4]), "+f"(d[5]), "+f"(d[6]), "+f"(d[7]), "+f"(d[8]), "+f"(d[9]), "+f"(d[10]), "+f"(d[11]), "+f"(d[12]), "+f"(d[13]), "+f"(d[14]), "+f"(d[15]), "+f"(d[16]), "+f"(d[17]), "+f"(d[18]), "+f"(d[19]), "+f"(d[20]), "+f"(d[21]), "+f"(d[22]), "+f"(d[23]), "+f"(d[24]), "+f"(d[25]), "+f"(d[26]), "+f"(d[27]), "+f"(d[28]), "+f"(d[29]), "+f"(d[30]), "+f"(d[31])
    : "r"(a0), "r"(a1), "r"(a2), "r"(a3), "l"(descB));
}
__device__ __forceinline__ void mma_p_init(float (&d)[28], uint32_t a0, uint32_t a1, uint32_t a2, uint32_t a3, uint64_t descB) {
  asm volatile("wgmma.mma_async.sync.aligned.m64n56k16.f32.bf16.bf16 {%0, %1, %2, %3, %4, %5, %6, %7, %8, %9, %10, %11, %12, %13, %14, %15, %16, %17, %18, %19, %20, %21, %22, %23, %24, %25, %26, %27}, "
    "{%28, %29, %30, %31}, %32, 0, 1, 1, 0;"
    : "=f"(d[0]), "=f"(d[1]), "=f"(d[2]), "=f"(d[3]), "=f"(d[4]), "=f"(d[5]), "=f"(d[6]), "=f"(d[7]), "=f"(d[8]), "=f"(d[9]), "=f"(d[10]), "=f"(d[11]), "=f"(d[12]), "=f"(d[13]), "=f"(d[14]), "=f"(d[15]), "=f"(d[16]), "=f"(d[17]), "=f"(d[18]), "=f"(d[19]), "=f"(d[20]), "=f"(d[21]), "=f"(d[22]), "=f"(d[23]), "=f"(d[24]), "=f"(d[25]), "=f"(d[26]), "=f"(d[27])
    : "r"(a0), "r"(a1), "r"(a2), "r"(a3), "l"(descB));
}
__device__ __forceinline__ void mma_p(float (&d)[28], uint32_t a0, uint32_t a1, uint32_t a2, uint32_t a3, uint64_t descB) {
  asm volatile("wgmma.mma_async.sync.aligned.m64n56k16.f32.bf16.bf16 {%0, %1, %2, %3, %4, %5, %6, %7, %8, %9, %10, %11, %12, %13, %14, %15, %16, %17, %18, %19, %20, %21, %22, %23, %24, %25, %26, %27}, "
    "{%28, %29, %30, %31}, %32, 1, 1, 1, 0;"
    : "+f"(d[0]), "+f"(d[1]), "+f"(d[2]), "+f"(d[3]), "+f"(d[4]), "+f"(d[5]), "+f"(d[6]), "+f"(d[7]), "+f"(d[8]), "+f"(d[9]), "+f"(d[10]), "+f"(d[11]), "+f"(d[12]), "+f"(d[13]), "+f"(d[14]), "+f"(d[15]), "+f"(d[16]), "+f"(d[17]), "+f"(d[18]), "+f"(d[19]), "+f"(d[20]), "+f"(d[21]), "+f"(d[22]), "+f"(d[23]), "+f"(d[24]), "+f"(d[25]), "+f"(d[26]), "+f"(d[27])
    : "r"(a0), "r"(a1), "r"(a2), "r"(a3), "l"(descB));
}
__device__ __forceinline__ void mma_o_init(float (&d)[48], uint32_t a0, uint32_t a1, uint32_t a2, uint32_t a3, uint64_t descB) {
  asm volatile("wgmma.mma_async.sync.aligned.m64n96k16.f32.bf16.bf16 {%0, %1, %2, %3, %4, %5, %6, %7, %8, %9, %10, %11, %12, %13, %14, %15, %16, %17, %18, %19, %20, %21, %22, %23, %24, %25, %26, %27, %28, %29, %30, %31, %32, %33, %34, %35, %36, %37, %38, %39, %40, %41, %42, %43, %44, %45, %46, %47}, "
    "{%48, %49, %50, %51}, %52, 0, 1, 1, 1;"
    : "=f"(d[0]), "=f"(d[1]), "=f"(d[2]), "=f"(d[3]), "=f"(d[4]), "=f"(d[5]), "=f"(d[6]), "=f"(d[7]), "=f"(d[8]), "=f"(d[9]), "=f"(d[10]), "=f"(d[11]), "=f"(d[12]), "=f"(d[13]), "=f"(d[14]), "=f"(d[15]), "=f"(d[16]), "=f"(d[17]), "=f"(d[18]), "=f"(d[19]), "=f"(d[20]), "=f"(d[21]), "=f"(d[22]), "=f"(d[23]), "=f"(d[24]), "=f"(d[25]), "=f"(d[26]), "=f"(d[27]), "=f"(d[28]), "=f"(d[29]), "=f"(d[30]), "=f"(d[31]), "=f"(d[32]), "=f"(d[33]), "=f"(d[34]), "=f"(d[35]), "=f"(d[36]), "=f"(d[37]), "=f"(d[38]), "=f"(d[39]), "=f"(d[40]), "=f"(d[41]), "=f"(d[42]), "=f"(d[43]), "=f"(d[44]), "=f"(d[45]), "=f"(d[46]), "=f"(d[47])
    : "r"(a0), "r"(a1), "r"(a2), "r"(a3), "l"(descB));
}
__device__ __forceinline__ void mma_o(float (&d)[48], uint32_t a0, uint32_t a1, uint32_t a2, uint32_t a3, uint64_t descB) {
  asm volatile("wgmma.mma_async.sync.aligned.m64n96k16.f32.bf16.bf16 {%0, %1, %2, %3, %4, %5, %6, %7, %8, %9, %10, %11, %12, %13, %14, %15, %16, %17, %18, %19, %20, %21, %22, %23, %24, %25, %26, %27, %28, %29, %30, %31, %32, %33, %34, %35, %36, %37, %38, %39, %40, %41, %42, %43, %44, %45, %46, %47}, "
    "{%48, %49, %50, %51}, %52, 1, 1, 1, 1;"
    : "+f"(d[0]), "+f"(d[1]), "+f"(d[2]), "+f"(d[3]), "+f"(d[4]), "+f"(d[5]), "+f"(d[6]), "+f"(d[7]), "+f"(d[8]), "+f"(d[9]), "+f"(d[10]), "+f"(d[11]), "+f"(d[12]), "+f"(d[13]), "+f"(d[14]), "+f"(d[15]), "+f"(d[16]), "+f"(d[17]), "+f"(d[18]), "+f"(d[19]), "+f"(d[20]), "+f"(d[21]), "+f"(d[22]), "+f"(d[23]), "+f"(d[24]), "+f"(d[25]), "+f"(d[26]), "+f"(d[27]), "+f"(d[28]), "+f"(d[29]), "+f"(d[30]), "+f"(d[31]), "+f"(d[32]), "+f"(d[33]), "+f"(d[34]), "+f"(d[35]), "+f"(d[36]), "+f"(d[37]), "+f"(d[38]), "+f"(d[39]), "+f"(d[40]), "+f"(d[41]), "+f"(d[42]), "+f"(d[43]), "+f"(d[44]), "+f"(d[45]), "+f"(d[46]), "+f"(d[47])
    : "r"(a0), "r"(a1), "r"(a2), "r"(a3), "l"(descB));
}

__device__ __forceinline__ void wg_fence() { asm volatile("wgmma.fence.sync.aligned;" ::: "memory"); }
__device__ __forceinline__ void wg_commit() { asm volatile("wgmma.commit_group.sync.aligned;" ::: "memory"); }
template <int N> __device__ __forceinline__ void wg_wait() { asm volatile("wgmma.wait_group.sync.aligned %0;" ::"n"(N) : "memory"); }
template <int N> __device__ __forceinline__ void pin(float (&d)[N]) {
#pragma unroll
  for (int i = 0; i < N; i++) asm volatile("" : "+f"(d[i])::"memory");
}
template <int N> __device__ __forceinline__ void pin(uint32_t (&d)[N]) {
#pragma unroll
  for (int i = 0; i < N; i++) asm volatile("" : "+r"(d[i])::"memory");
}
__device__ __forceinline__ uint64_t mkdesc(uint32_t lo, uint32_t hi) { return ((uint64_t)hi << 32) | lo; }
constexpr uint64_t EVICT_FIRST = 0x12F0000000000000ull;
constexpr uint32_t HI_X = (3072 >> 4) | (1u << 30);
constexpr uint32_t HI_KV = (1024 >> 4) | (1u << 30);
constexpr uint32_t HI_W = (512 >> 4) | (2u << 30);
constexpr uint32_t HI_O = (1536 >> 4) | (2u << 30);
constexpr uint32_t LO_O = (1u << 16) + ((SM_BASE + OFF_OIN) >> 4);
constexpr uint32_t LO_WQ = ((12288 >> 4) << 16) + ((SM_BASE + OFF_WQ) >> 4);
constexpr uint32_t LO_WO = ((6144 >> 4) << 16) + ((SM_BASE + OFF_WO) >> 4);
constexpr uint32_t LO_X = (1u << 16) + ((SM_BASE + OFF_X) >> 4);
constexpr uint32_t LO_KV = (1u << 16) + ((SM_BASE + OFF_KV) >> 4);

__device__ __forceinline__ uint32_t pack_bf16(float lo, float hi) {
  uint32_t r;
  asm("cvt.rn.bf16x2.f32 %0, %1, %2;" : "=r"(r) : "f"(hi), "f"(lo));
  return r;
}
__device__ __forceinline__ float ex2(float x) {
  float r;
  asm("ex2.approx.ftz.f32 %0, %1;" : "=f"(r) : "f"(x));
  return r;
}
__device__ __forceinline__ float rcp(float x) {
  float r;
  asm("rcp.approx.ftz.f32 %0, %1;" : "=f"(r) : "f"(x));
  return r;
}
__device__ __forceinline__ bool elect() {
  uint32_t p;
  asm volatile("{\n.reg .pred P;\nelect.sync _|P, 0xffffffff;\nselp.u32 %0, 1, 0, P;\n}" : "=r"(p));
  return p;
}
__device__ __forceinline__ void mbar_init(uint32_t bar, uint32_t cnt) {
  asm volatile("mbarrier.init.shared::cta.b64 [%0], %1;" ::"r"(bar), "r"(cnt) : "memory");
}
__device__ __forceinline__ void mbar_wait(uint32_t bar, uint32_t parity) {
  asm volatile(
      "{\n.reg .pred p;\n.reg .u32 n;\n"
      "mbarrier.try_wait.parity.shared::cta.b64 p, [%0], %1;\n"
      "@p bra DONE;\n"
      "mov.u32 n, 0;\n"
      "LOOP:\n"
      "mbarrier.try_wait.parity.shared::cta.b64 p, [%0], %1;\n"
      "@p bra DONE;\n"
      "add.u32 n, n, 1;\n"
      "setp.lt.u32 p, n, 0x400000;\n"
      "@p bra LOOP;\n"
      "trap;\n"
      "DONE:\n}\n" ::"r"(bar), "r"(parity)
      : "memory");
}
__device__ __forceinline__ void mbar_arrive_cluster(uint32_t bar) {
  asm volatile("mbarrier.arrive.shared::cluster.b64 _, [%0];" ::"r"(bar) : "memory");
}
__device__ __forceinline__ void mbar_expect_tx(uint32_t bar, uint32_t bytes) {
  asm volatile("mbarrier.arrive.expect_tx.shared::cta.b64 _, [%0], %1;" ::"r"(bar), "r"(bytes) : "memory");
}
__device__ __forceinline__ uint32_t mapa(uint32_t addr, uint32_t rank) {
  uint32_t r;
  asm("mapa.shared::cluster.u32 %0, %1, %2;" : "=r"(r) : "r"(addr), "r"(rank));
  return r;
}
__device__ __forceinline__ void sched_fence(uint32_t& keep, int never) {
  asm volatile("{\n.reg .pred p;\nsetp.ne.s32 p, %1, 0;\n@p mov.u32 %0, %clock;\n}" : "+r"(keep) : "r"(never) : "memory");
}
template <int ID> __device__ __forceinline__ void tok_wait() { asm volatile("bar.sync %0, %1;" ::"n"(ID), "n"(ID == T7 ? 384 : 256) : "memory"); }
template <int ID> __device__ __forceinline__ void tok_pass() { asm volatile("bar.arrive %0, %1;" ::"n"(ID), "n"(ID == T7 ? 384 : 256) : "memory"); }
__device__ __forceinline__ void fence_async() { asm volatile("fence.proxy.async.shared::cta;" ::: "memory"); }
__device__ __forceinline__ void stsm4(uint32_t addr, uint32_t r0, uint32_t r1, uint32_t r2, uint32_t r3) {
  asm volatile("stmatrix.sync.aligned.m8n8.x4.shared.b16 [%0], {%1,%2,%3,%4};" ::"r"(addr), "r"(r0), "r"(r1), "r"(r2), "r"(r3) : "memory");
}
__device__ __forceinline__ void lds128(uint32_t addr, uint32_t& r0, uint32_t& r1, uint32_t& r2, uint32_t& r3) {
  asm volatile("ld.shared.v4.b32 {%0,%1,%2,%3}, [%4];" : "=r"(r0), "=r"(r1), "=r"(r2), "=r"(r3) : "r"(addr) : "memory");
}
template <int OFF>
__device__ __forceinline__ void st_async(uint32_t addr, uint32_t bar, uint32_t r0, uint32_t r1, uint32_t r2, uint32_t r3) {
  asm volatile("st.async.shared::cluster.mbarrier::complete_tx::bytes.v4.b32 [%0+%6], {%1,%2,%3,%4}, [%5];" ::"r"(addr), "r"(r0),
               "r"(r1), "r"(r2), "r"(r3), "r"(bar), "n"(OFF)
               : "memory");
}
__device__ __forceinline__ void tma5_mc(uint32_t dst, const CUtensorMap* tm, uint32_t bar, int c2, int c4) {
  asm volatile(
      "cp.async.bulk.tensor.5d.shared::cluster.global.mbarrier::complete_tx::bytes.multicast::cluster.L2::cache_hint "
      "[%0], [%1, {0, 0, %3, 0, %4}], [%2], %5, %6;" ::"r"(dst), "l"(tm), "r"(bar), "r"(c2), "r"(c4), "h"((uint16_t)3), "l"(EVICT_FIRST)
      : "memory");
}
__device__ __forceinline__ void tma5_pf(const CUtensorMap* tm, int c2, int c4) {
  asm volatile("cp.async.bulk.prefetch.tensor.5d.L2.global [%0, {0, 0, %1, 0, %2}];" ::"l"(tm), "r"(c2), "r"(c4) : "memory");
}
__device__ __forceinline__ void tma3(uint32_t dst, const CUtensorMap* tm, uint32_t bar, int c1, int c2) {
  asm volatile("cp.async.bulk.tensor.3d.shared::cluster.global.mbarrier::complete_tx::bytes [%0], [%1, {0, %3, %4}], [%2];" ::"r"(dst),
               "l"(tm), "r"(bar), "r"(c1), "r"(c2)
               : "memory");
}

constexpr float SQRT_HD = 6.92820323027551f;
constexpr float SM_C = 1.4426950408889634f / SQRT_HD;

__device__ __forceinline__ void s_init(float (&s)[32], const uint32_t (&mk)[16], const uint32_t (&b)[16]) {
#pragma unroll
  for (int i = 0; i < 16; i++) {
    const int o = 4 * (i & 7) + 2 * (i >> 3);
    uint32_t t0, t1;
    asm("{\n.reg .b16 ml, mh, bl, bh;\n.reg .b32 m2, b2;\n"
        "mov.b32 {ml, mh}, %1;\nmov.b32 {bl, bh}, %3;\nmov.b32 m2, {ml, ml};\nmov.b32 b2, {bl, bl};\n"
        "fma.rn.bf16x2 %0, m2, %2, b2;\n}"
        : "=r"(t0)
        : "r"(mk[i]), "r"(0x40DE40DEu), "r"(b[i]));
    asm("fma.rn.bf16x2 %0, %1, %2, %3;" : "=r"(t1) : "r"(mk[i]), "r"(0x40DE40DEu), "r"(b[i]));
    s[o] = __uint_as_float(t0);
    s[o + 1] = __uint_as_float(t1);
    asm volatile("" : "+f"(s[o]), "+f"(s[o + 1])::"memory");
  }
}
__device__ __forceinline__ uint32_t pack_bias(float lo, float hi) {
  uint32_t l = __float_as_uint(fmaf(lo, SQRT_HD, 0x1p-100f)), h = __float_as_uint(fmaf(hi, SQRT_HD, 0x1p-100f));
  l = (l - (l >> 16) + 0x8000u) >> 16;
  return ((h - l + 0x8000u) & 0xffff0000u) | l;
}
template <bool NEG>
__device__ __forceinline__ int pick3(int a, int b, int c) { return NEG ? (int)__vimin3_u32(a, b, c) : __vimax3_s32(a, b, c); }
template <bool NEG>
__device__ __forceinline__ int pick2(int a, int b) { return NEG ? (int)min((unsigned)a, (unsigned)b) : max(a, b); }
template <bool NEG>
__device__ __forceinline__ void row_pick(const float (&s)[32], int& i0, int& i1) {
#define FI(x) __float_as_int(x)
  i0 = pick2<NEG>(FI(s[0]), FI(s[1])), i1 = pick2<NEG>(FI(s[2]), FI(s[3]));
  int k0 = pick3<NEG>(FI(s[4]), FI(s[5]), FI(s[8])), k1 = pick3<NEG>(FI(s[6]), FI(s[7]), FI(s[10]));
  i0 = pick3<NEG>(i0, FI(s[9]), FI(s[12]));   i1 = pick3<NEG>(i1, FI(s[11]), FI(s[14]));
  k0 = pick3<NEG>(k0, FI(s[13]), FI(s[16]));  k1 = pick3<NEG>(k1, FI(s[15]), FI(s[18]));
  i0 = pick3<NEG>(i0, FI(s[17]), FI(s[20]));  i1 = pick3<NEG>(i1, FI(s[19]), FI(s[22]));
  k0 = pick3<NEG>(k0, FI(s[21]), FI(s[24]));  k1 = pick3<NEG>(k1, FI(s[23]), FI(s[26]));
  i0 = pick3<NEG>(i0, FI(s[25]), FI(s[28]));  i1 = pick3<NEG>(i1, FI(s[27]), FI(s[30]));
  i0 = pick3<NEG>(i0, k0, FI(s[29]));         i1 = pick3<NEG>(i1, k1, FI(s[31]));
#undef FI
}
template <bool NEG>
__device__ __forceinline__ void quad_pick(int& i0, int& i1, int x) {
  i0 = pick2<NEG>(i0, __shfl_xor_sync(0xffffffffu, i0, x));
  i1 = pick2<NEG>(i1, __shfl_xor_sync(0xffffffffu, i1, x));
}
__device__ __forceinline__ void fix_negative_rows(const float (&s)[32], int& i0, int& i1) {
  int n0, n1;
  row_pick<true>(s, n0, n1);
  quad_pick<true>(n0, n1, 1);
  quad_pick<true>(n0, n1, 2);
  if (i0 < 0) i0 = n0;
  if (i1 < 0) i1 = n1;
}
template <int CH>
__device__ __forceinline__ void exp_rows(const float (&s)[32], uint32_t (&p)[16], int max0, int max1, uint32_t& keep, int never) {
  const float m0 = __int_as_float(max0) * -SM_C, m1 = __int_as_float(max1) * -SM_C;
  float t[32];
#pragma unroll
  for (int c = 0; c <= 16 / CH; c++) {
#pragma unroll
    for (int i = 2 * CH * c; i < 2 * CH * (c + 1) && i < 32; i++) {
      t[i] = fmaf(s[i], SM_C, (i & 2) ? m1 : m0);
      asm volatile("" : "+f"(t[i]));
    }
    if (c > 0) {
#pragma unroll
      for (int i = CH * (c - 1); i < CH * c; i++) {
        t[2 * i] = ex2(t[2 * i]), t[2 * i + 1] = ex2(t[2 * i + 1]);
        asm volatile("" : "+f"(t[2 * i]), "+f"(t[2 * i + 1]));
      }
    }
    if (c > 1) {
#pragma unroll
      for (int i = CH * (c - 2); i < CH * (c - 1); i++) {
        p[i] = pack_bf16(t[2 * i], t[2 * i + 1]);
        asm volatile("" : "+r"(p[i]));
      }
    }
    if (c < 16 / CH) sched_fence(keep, never);
  }
#pragma unroll
  for (int i = 16 - CH; i < 16; i++) p[i] = pack_bf16(t[2 * i], t[2 * i + 1]);
  pin(p);
}
__device__ __forceinline__ void issue_p(float (&o)[28], const uint32_t (&p)[16], uint32_t lo) {
#pragma unroll
  for (int ks = 0; ks < 4; ks++) {
    uint64_t db = mkdesc(lo + ks * 2, HI_KV);
    if (ks == 0) mma_p_init(o, p[0], p[1], p[2], p[3], db);
    else mma_p(o, p[4 * ks], p[4 * ks + 1], p[4 * ks + 2], p[4 * ks + 3], db);
  }
  wg_commit();
}
template <int SUM, int OFF>
__device__ __forceinline__ void normalize(const float (&o)[28], uint32_t (&f)[12]) {
  const float r0 = rcp(o[SUM]), r1 = rcp(o[SUM + 2]);
  uint32_t h0 = pack_bf16(r0, r0), h1 = pack_bf16(r1, r1);
#pragma unroll
  for (int j = 0; j < 12; j++)
    asm("mul.rn.bf16x2 %0, %1, %2;" : "=r"(f[j]) : "r"(pack_bf16(o[OFF + 2 * j], o[OFF + 2 * j + 1])), "r"((j & 1) ? h1 : h0));
}

__global__ void __cluster_dims__(2, 1, 1) __launch_bounds__(384, 1)
swin_attn_kernel(const __grid_constant__ Maps maps, const __nv_bfloat16* __restrict__ rpb, const int* __restrict__ rp_idx, int base, int never) {
  extern __shared__ __align__(1024) uint8_t smem_raw[];
  const uint32_t sb = (uint32_t)__cvta_generic_to_shared(smem_raw);
  const int tid = threadIdx.x;
  const int wg = __shfl_sync(0xffffffffu, tid >> 7, 0);
  const int warp = __shfl_sync(0xffffffffu, (tid >> 5) & 3, 0);
  const int lane = tid & 31;
  const int rank = blockIdx.x & 1;
  const int cl = blockIdx.x >> 1;
  const int ncl = gridDim.x >> 1;
  const uint32_t bars = sb + OFF_BAR;
  int extra = NWIN;
  auto read_ticket = [&]() {
    mbar_wait(bars + B_TICK, 0);
    uint32_t t;
    asm volatile("ld.shared.b32 %0, [%1];" : "=r"(t) : "r"(bars + W_TICK) : "memory");
    extra = base + __shfl_sync(0xffffffffu, t, 0);
  };
  auto window = [&](int v) { return v < base ? v : (v < base + ncl ? extra : NWIN); };
  auto prefetch = [&](int p, int win) {
    if (p < 2) tma5_pf(&maps.x, (((win >> 3) & ~7) + 4 + 4 * rank) & 511, (win * 4 + 2 + 2 * p) & 255);
    else tma5_pf(&maps.mask, 0, 2 * win + rank);
  };
  auto load = [&](int p, int win, int a) {
    if (p < 2)
      tma5_mc(sb + OFF_X + a * STAGE + rank * 12288 + p * 6144, &maps.x, bars + B_XFULL + 8 * a,
              (((win >> 3) & ~7) + 4 + 4 * rank) & 511, (win * 4 + 2 + 2 * p) & 255);
    else tma5_mc(sb + OFF_MASK + a * STAGE + rank * 4096, &maps.mask, bars + B_XFULL + 8 * a, 0, 2 * win + rank);
  };
  auto load_wkv = [&](int b) {
    tma3(sb + OFF_KV + (b < 3 ? b * 12288 : STAGE + (b - 3) * 12288), &maps.wqkv, bars + B_WKV + 8 * (b >> 1), 0,
         (b < 3 ? 6 : 9) + b + 3 * rank);
  };
  auto startup_loads = [&]() {
    if ((sb & 0x3FFFF) != SM_BASE) __trap();
    if (blockIdx.x == 0) asm volatile("st.relaxed.gpu.global.u32 [%0], 0;" ::"l"(&g_ticket) : "memory");
    mbar_expect_tx(bars + B_XFULL, X_BYTES);
    mbar_expect_tx(bars + B_M0, M_BYTES);
    mbar_expect_tx(bars + B_WKV + 8, 24576);
    load_wkv(2);
    load_wkv(3);
    tma5_mc(sb + OFF_MASK + rank * 4096, &maps.mask, bars + B_M0, 0, 2 * cl + rank);
    mbar_expect_tx(bars + B_WQ, 36864);
    for (int nb = 0; nb < 3; nb++) tma3(sb + OFF_WQ + nb * 12288, &maps.wqkv, bars + B_WQ, 0, 3 * rank + nb);
    mbar_expect_tx(bars + B_WKV + 16, 24576);
    load_wkv(4);
    load_wkv(5);
    mbar_expect_tx(bars + B_XFULL + 8, X_BYTES + M_BYTES);
    for (int p = 0; p < 3; p++) load(p, cl + ncl, 1);
    mbar_expect_tx(bars + B_TICK, 4);
    mbar_expect_tx(bars + B_WO, 36864);
    tma3(sb + OFF_WO, &maps.wo, bars + B_WO, 96 * rank, 3 * rank);
    for (int nb = 0; nb < 3; nb++)
      asm volatile("cp.async.bulk.tensor.5d.shared::cluster.global.mbarrier::complete_tx::bytes [%0], [%1, {%3, 0, 0, 0, %4}], [%2];" ::"r"(
                       sb + OFF_WO + 18432 + nb * 6144), "l"(&maps.wop), "r"(bars + B_WO), "r"(96 * rank + 32 * nb), "r"(3 * (rank ^ 1))
                   : "memory");
  };
  if (wg == KV_WG && warp == 3) {
    if (elect()) {
#pragma unroll
      for (int k = 0; k < 15; k++) mbar_init(bars + 8 * k, (k >> 1) == B_OEMPTY / 16 ? 4 : 1);
      asm volatile("fence.mbarrier_init.release.cluster;" ::: "memory");
    }
    __syncwarp();
  }
  asm volatile("barrier.cluster.arrive.relaxed.aligned;" ::: "memory");

  if (wg == KV_WG) {
    if (warp == 3 && elect()) {
      fence_async();
      mbar_expect_tx(bars + B_WKV, 24576);
      load_wkv(0);
      load_wkv(1);
    }
    __syncwarp();
    asm volatile("barrier.cluster.wait.aligned;" ::: "memory");
    if (elect()) {
      if (warp < 2) load(warp, cl, 0);
      else if (warp == 3) startup_loads();
    }
    __syncwarp();
    asm volatile("setmaxnreg.inc.sync.aligned.u32 216;");
    uint32_t w[3][48];
    auto load_frags = [&](int s) {
      const uint32_t la = sb + OFF_KV + (warp >> 1) * 12288 + (8 * (lane >> 4) + (lane & 7)) * 64 +
                          (((2 * (warp & 1) + ((lane >> 3) & 1)) ^ ((lane & 7) >> 1)) << 4);
      mbar_wait(bars + B_WKV + 8 * s, 0);
#pragma unroll
      for (int ks = 0; ks < 12; ks++)
        asm volatile("ldmatrix.sync.aligned.m8n8.x4.trans.shared.b16 {%0,%1,%2,%3}, [%4];"
                     : "=r"(w[s][4 * ks]), "=r"(w[s][4 * ks + 1]), "=r"(w[s][4 * ks + 2]), "=r"(w[s][4 * ks + 3])
                     : "r"(la + s * 24576 + (s == 2 || (s == 1 && warp >= 2) ? STAGE - 36864 : 0) + ks * 1024)
                     : "memory");
    };
    load_frags(0);
    uint32_t sta[4];
#pragma unroll
    for (int jj = 0; jj < 4; jj++) {
      sta[jj] = sb + OFF_KV + (16 * warp + (lane & 15)) * 128 + (((2 * jj + (lane >> 4)) ^ (lane & 7)) << 4);
      asm volatile("" : "+r"(sta[jj]));
    }
    const uint32_t xe_rem = mapa(bars + B_XEMPTY, rank ^ 1);
    const uint32_t v1off = warp > 0 ? 1024 : 0;

#define SF sched_fence(sta[0], never)
    float acc[32];
    uint32_t pk[16];
    auto store = [&](uint32_t off) {
#pragma unroll
      for (int jj = 0; jj < 4; jj++) stsm4(sta[jj] + off, pk[4 * jj], pk[4 * jj + 1], pk[4 * jj + 2], pk[4 * jj + 3]);
    };
    auto issue = [&](int s, uint32_t xd, bool st, uint32_t off) {
#pragma unroll
      for (int ks = 0; ks < 12; ks++) {
        uint64_t db = mkdesc(xd + (((ks >> 2) * 1024 + (ks & 3) * 32) >> 4), HI_X);
        if (ks == 0) mma_kv_init(acc, w[s][0], w[s][1], w[s][2], w[s][3], db);
        else mma_kv(acc, w[s][4 * ks], w[s][4 * ks + 1], w[s][4 * ks + 2], w[s][4 * ks + 3], db);
        if (ks == 1 && st) {
          __syncwarp();
          store(off);
          __syncwarp();
        }
      }
      wg_commit();
    };
    auto convert = [&]() {
      wg_wait<0>();
      pin(acc);
#pragma unroll
      for (int j = 0; j < 16; j++) pk[j] = pack_bf16(acc[2 * j], acc[2 * j + 1]);
      pin(pk);
    };

    mbar_wait(bars + B_XFULL, 0);
    wg_fence();
    issue(0, LO_X, false, 0);
    load_frags(1);
    int nxt = cl + ncl;
    uint32_t ph = 0;
    uint32_t ticket = 0;
    auto step = [&](auto A) -> bool {
      constexpr int a = decltype(A)::value;
      constexpr uint32_t xd = LO_X + a * (STAGE >> 4);
      if (nxt + ncl >= base && nxt < base) read_ticket();
      const bool more = window(nxt) < NWIN;
      const int wn2 = window(nxt + ncl);
      convert();
      wg_fence();
      SF;
      tok_wait<T2>();
      issue(1, xd, true, a * STAGE);
      tok_pass<T3>();
      if (warp < 3 && wn2 < NWIN && elect()) prefetch(warp, wn2);
      __syncwarp();
      const bool first = a == 0 && nxt == cl + ncl;
      convert();
      SF;
      if (!first) tok_wait<T7>();
      store(a * STAGE + 8192);
      fence_async();
      if (first) {
        load_frags(2);
        asm volatile("bar.sync %0, 128;" ::"n"((int)BAR_STAGE) : "memory");
        asm volatile("st.shared.v4.b32 [%0], {%1,%1,%1,%1};" ::"r"(sb + OFF_KV + (warp >> 1) * STAGE + 144 * 128 + (tid & 63) * 16), "r"(0x3F803F80u) : "memory");
      }
      wg_fence();
      tok_wait<T5>();
      issue(2, xd, false, 0);
      tok_pass<T6>();
      if (!more) {
        convert();
        store(a * STAGE + 16384 + v1off);
        fence_async();
        return false;
      }
      mbar_wait(bars + B_XFULL + 8 * (a ^ 1), a ? ph ^ 1 : ph);
      convert();
      wg_fence();
      SF;
      tok_wait<T0>();
      if (tid == KV_WG * 128 && wn2 < NWIN) mbar_arrive_cluster(xe_rem + 8 * a);
      issue(0, LO_X + (a ^ 1) * (STAGE >> 4), true, a * STAGE + 16384 + v1off);
      tok_pass<T1>();
      fence_async();
      nxt += ncl;
      if (wn2 < NWIN) {
        mbar_wait(bars + B_XEMPTY + 8 * a, ph);
        if (elect()) {
          if (warp < 3) {
            load(warp, wn2, a);
          } else {
            mbar_expect_tx(bars + B_XFULL + 8 * a, X_BYTES + M_BYTES);
            if (rank == 0 && nxt + 3 * ncl >= base) {
              if (nxt + 2 * ncl < base) {
                asm volatile("atom.global.inc.u32 %0, [%1], %2;" : "=r"(ticket) : "l"(&g_ticket), "r"(ncl - 1) : "memory");
              } else if (nxt + ncl < base) {
#pragma unroll
                for (int r = 0; r < 2; r++)
                  asm volatile("st.async.shared::cluster.mbarrier::complete_tx::bytes.b32 [%0], %1, [%2];" ::"r"(mapa(bars + W_TICK, r)),
                               "r"(ticket), "r"(mapa(bars + B_TICK, r))
                               : "memory");
              }
            }
          }
        }
        __syncwarp();
      }
      return true;
    };
    while (step(IC<0>{}) && step(IC<1>{})) ph ^= 1;
    tok_wait<T0>();
    tok_pass<T1>();
    tok_wait<T2>();
    tok_pass<T3>();
    tok_wait<T7>();
    tok_wait<T5>();
  } else {
    const int a = wg - (KV_WG == 0 ? 1 : 0);
    const int g = lane >> 2, q = lane & 3;
    const uint32_t bar = bars + 8 * a;
    if (a == 0) {
      tok_pass<T2>();
      tok_pass<T5>();
    }
    asm volatile("setmaxnreg.dec.sync.aligned.u32 144;");
    uint32_t braw[32];
    {
      const int ty = 4 * (warp >> 1) + (g >> 1), tx = 4 * (warp & 1) + (g & 1);
      const int* ip = rp_idx + (ty * 8 + tx) * 64 + 8 * q;
#pragma unroll
      for (int c = 0; c < 8; c++)
        asm volatile("ld.global.nc.v4.b32 {%0,%1,%2,%3}, [%4];"
                     : "=r"(braw[4 * c]), "=r"(braw[4 * c + 1]), "=r"(braw[4 * c + 2]), "=r"(braw[4 * c + 3])
                     : "l"(ip + (c >> 2) * 128 + ((c >> 1) & 1) * 32 + (c & 1) * 4));
      const int e = a * 128 + (tid & 127);
      uint32_t v = 0;
      if (e < 225) asm volatile("ld.global.nc.b32 %0, [%1];" : "=r"(v) : "l"(reinterpret_cast<const uint32_t*>(rpb) + e * 2 + rank));
      asm volatile("st.shared.b32 [%0], %1;" ::"r"(sb + OFF_RPB + e * 4), "r"(v) : "memory");
      tok_wait<BAR_BIAS>();
#pragma unroll
      for (int j = 0; j < 32; j++)
        asm volatile("ld.shared.b32 %0, [%1];" : "=r"(braw[j]) : "r"(sb + OFF_RPB + braw[j] * 4) : "memory");
    }
    asm volatile("barrier.cluster.wait.aligned;" ::: "memory");

    const int mrow = 16 * warp + (g >> 1) + 4 * (g & 1);
#undef SF
#define SF sched_fence(mk_addr, never)
    uint32_t mk_addr = sb + OFF_MASK + a * STAGE + mrow * 128 + ((q ^ (mrow & 7)) << 4);
    const uint32_t ostage = sb + OFF_OIN + a * STAGE + warp * 3072;
    const uint32_t ost = ostage + ((lane >> 3) & 1) * 1536 + (lane & 7) * 64 + (((lane >> 4) ^ ((lane & 7) >> 1)) << 4);
    const uint32_t oin_rem = mapa(ostage + g * 64 + ((q ^ (g >> 1)) << 4), rank ^ 1);
    const uint32_t bar_rem = mapa(bar, rank ^ 1);

    auto store_out = [&](int win) {
      fence_async();
      __syncwarp();
      if (elect()) {
        int yy = (((win >> 3) & ~7) + 4 + 4 * (warp >> 1)) & 511;
        int xh = (win * 4 + 2 + 2 * (warp & 1)) & 255;
        asm volatile("cp.async.bulk.tensor.5d.global.shared::cta.bulk_group [%0, {0, 0, %2, %3, %4}], [%1];" ::"l"(&maps.out), "r"(ostage),
                     "r"(yy), "r"(3 * rank), "r"(xh)
                     : "memory");
        asm volatile("cp.async.bulk.commit_group;" ::: "memory");
      }
      __syncwarp();
    };
    auto release_oin = [&]() {
      if (elect()) {
        asm volatile("cp.async.bulk.wait_group.read 0;" ::: "memory");
        if (warp == 0) mbar_expect_tx(bar + B_OFULL, O_BYTES);
        mbar_arrive_cluster(bar_rem + B_OEMPTY);
      }
      __syncwarp();
    };
    float qa[48];
    uint32_t bias0[16], bias1[16];
    uint32_t mk[16];
    auto load_mask = [&](uint32_t z) {
#pragma unroll
      for (int c = 0; c < 4; c++)
        lds128((c & 1 ? mk_addr ^ (64 + z) : mk_addr) + (c >> 1) * 1024, mk[4 * c], mk[4 * c + 1], mk[4 * c + 2], mk[4 * c + 3]);
    };
    auto clamp_mask = [&]() {
      SF;
#pragma unroll
      for (int j = 0; j < 16; j++) asm("max.NaN.bf16x2 %0, %0, %1;" : "+r"(mk[j]) : "r"(0xFD80FD80u));
      pin(mk);
    };
    auto issue_q = [&](uint32_t ua, bool tok, int win) {
#pragma unroll
      for (int ks = 0; ks < 12; ks++) {
        if (ks == Q_SPLIT && tok) {
          tok_pass<T4>();
          store_out(win);
          tok_wait<T7>();
          wg_fence();
        }
        uint64_t da = mkdesc(ua + LO_X + (((ks >> 2) * 1024 + (ks & 3) * 32) >> 4), HI_X);
        uint64_t db = mkdesc(LO_WQ + ks * 64, HI_W);
        if (ks == 0) mma_q_init(qa, da, db);
        else mma_q(qa, da, db);
      }
      wg_commit();
      if (tok) tok_pass<T5>();
    };
#pragma unroll
    for (int j = 0; j < 16; j++) {
      const uint32_t b0 = braw[2 * j], b1 = braw[2 * j + 1];
      bias0[j] = pack_bias(__uint_as_float(b0 << 16), __uint_as_float(b1 << 16));
      bias1[j] = pack_bias(__uint_as_float(b0 & 0xffff0000u), __uint_as_float(b1 & 0xffff0000u));
    }
    pin(bias0);
    pin(bias1);
    SF;
    mbar_wait(bars + B_WQ, 0);
    wg_fence();
    if (a == 0) tok_wait<T3>();
    else tok_wait<T1>();
    issue_q(a * (STAGE >> 4), false, 0);
    if (a == 0) mbar_wait(bars + B_M0, 0);
    else tok_pass<T2>();
    load_mask(0);
    if (a == 1) {
      tok_wait<T3>();
      tok_pass<T4>();
      tok_pass<T5>();
      tok_wait<T7>();
    }
    clamp_mask();
    uint32_t ph = 0;
    int win = cl + a * ncl;
    for (;; win += 2 * ncl, ph ^= 1) {
      const uint32_t ua = a * (STAGE >> 4) + (win >> 20);
      const uint32_t kd = ua + LO_KV;
      float s0[32], s1[32];
      wg_wait<0>();
      pin(qa);
      uint32_t q0[12], q1[12];
#pragma unroll
      for (int j = 0; j < 12; j++) q0[j] = pack_bf16(qa[2 * j], qa[2 * j + 1]);
#pragma unroll
      for (int j = 0; j < 12; j++) q1[j] = pack_bf16(qa[24 + 2 * j], qa[25 + 2 * j]);
      pin(q0);
      pin(q1);
      s_init(s0, mk, bias0);
      s_init(s1, mk, bias1);
      wg_fence();
      tok_wait<T6>();
#pragma unroll
      for (int ks = 0; ks < 3; ks++)
        mma_s(s0, q0[4 * ks], q0[4 * ks + 1], q0[4 * ks + 2], q0[4 * ks + 3], mkdesc(kd + ks * 128, HI_KV));
      wg_commit();
#pragma unroll
      for (int ks = 0; ks < 3; ks++)
        mma_s(s1, q1[4 * ks], q1[4 * ks + 1], q1[4 * ks + 2], q1[4 * ks + 3], mkdesc(kd + (3 + ks) * 128, HI_KV));
      wg_commit();
      tok_pass<T0>();
      release_oin();
      int x0, x1, y0, y1;
      uint32_t p0[16], p1[16];
      wg_wait<1>();
      pin(s0);
      pin(q0);
      row_pick<false>(s0, x0, x1);
      quad_pick<false>(x0, x1, 1);
      wg_wait<0>();
      pin(s1);
      pin(q1);
      row_pick<false>(s1, y0, y1);
      quad_pick<false>(x0, x1, 2);
      quad_pick<false>(y0, y1, 1);
      quad_pick<false>(y0, y1, 2);
      if (__builtin_expect(__any_sync(0xffffffffu, (x0 | x1 | y0 | y1) < 0), 0)) {
        fix_negative_rows(s0, x0, x1);
        fix_negative_rows(s1, y0, y1);
      }
      exp_rows<EXP_CH>(s0, p0, x0, x1, mk_addr, never);
      exp_rows<EXP_CH>(s1, p1, y0, y1, mk_addr, never);
      float o0[28], o1[28];
      wg_fence();
      SF;
      tok_wait<T4>();
      issue_p(o0, p0, kd + ((96 * 128) >> 4));
      issue_p(o1, p1, kd + ((144 * 128) >> 4));
      tok_pass<T7>();
      mbar_wait(bar + B_OEMPTY, ph);
      uint32_t f0[12], f1[12];
      wg_wait<1>();
      pin(o0);
      pin(p0);
      normalize<24, 0>(o0, f0);
      st_async<0>(oin_rem, bar_rem + B_OFULL, f0[0], f0[2], f0[4], f0[6]);
      st_async<1536>(oin_rem, bar_rem + B_OFULL, f0[1], f0[3], f0[5], f0[7]);
      wg_wait<0>();
      pin(o1);
      pin(p1);
      normalize<0, 4>(o1, f1);
      st_async<512>(oin_rem, bar_rem + B_OFULL, f0[8], f0[10], f1[0], f1[2]);
      st_async<2048>(oin_rem, bar_rem + B_OFULL, f0[9], f0[11], f1[1], f1[3]);
      st_async<1024>(oin_rem, bar_rem + B_OFULL, f1[4], f1[6], f1[8], f1[10]);
      st_async<2560>(oin_rem, bar_rem + B_OFULL, f1[5], f1[7], f1[9], f1[11]);
      pin(f0);
      pin(f1);
      float (&oa)[48] = qa;
      int wn1 = 0, wn2 = 0;
      if ((unsigned)(win - 2 * ncl) >= (unsigned)(base - 4 * ncl)) {
        if (win < 2 * ncl) {
          mbar_wait(bars + B_WO, 0);
        } else {
          read_ticket();
          wn1 = window(win + ncl), wn2 = window(win + 2 * ncl);
        }
      }
      const bool last = wn1 >= NWIN;
      if (!last) tok_wait<T1>();
      wg_fence();
#pragma unroll
      for (int ks = 0; ks < 3; ks++) {
        uint64_t db = mkdesc(LO_WO + ks * 64, HI_W);
        if (ks == 0) mma_o_init(oa, f0[0], f0[1], f0[2], f0[3], db);
        else mma_o(oa, f0[4 * ks], f0[4 * ks + 1], f0[4 * ks + 2], f0[4 * ks + 3], db);
      }
#pragma unroll
      for (int ks = 0; ks < 3; ks++)
        mma_o(oa, f1[4 * ks], f1[4 * ks + 1], f1[4 * ks + 2], f1[4 * ks + 3], mkdesc(LO_WO + (3 + ks) * 64, HI_W));
      mbar_wait(bar + B_OFULL, ph);
      asm volatile("fence.proxy.async::generic.acquire.sync_restrict::shared::cluster.cluster;" ::: "memory");
      wg_fence();
#pragma unroll
      for (int ks = 0; ks < 6; ks++)
        mma_q(oa, mkdesc(ua + LO_O + (((ks >> 1) * 512 + (ks & 1) * 32) >> 4), HI_O), mkdesc(LO_WO + (18432 >> 4) + ks * 64, HI_W));
      wg_commit();
      if (!last) tok_pass<T2>();
      load_mask(win >> 20);
      wg_wait<0>();
      pin(oa);
      pin(f0);
      pin(f1);
#pragma unroll
      for (int jj = 0; jj < 6; jj++)
        stsm4((jj & 1 ? ost ^ (32 + (win >> 20)) : ost) + (jj >> 1) * 512, pack_bf16(oa[8 * jj], oa[8 * jj + 1]), pack_bf16(oa[8 * jj + 2], oa[8 * jj + 3]),
              pack_bf16(oa[8 * jj + 4], oa[8 * jj + 5]), pack_bf16(oa[8 * jj + 6], oa[8 * jj + 7]));
      if (wn2 >= NWIN) {
        if (!last) {
          tok_wait<T3>();
          tok_pass<T4>();
          tok_pass<T5>();
          tok_wait<T7>();
        }
        break;
      }
      wg_fence();
      tok_wait<T3>();
      issue_q(ua, true, win);
      clamp_mask();
    }
    store_out(window(win));
    asm volatile("cp.async.bulk.wait_group.read 0;" ::: "memory");
    __syncwarp();
  }
}

typedef CUresult (*EncodeFn)(CUtensorMap*, CUtensorMapDataType, cuuint32_t, void*, const cuuint64_t*, const cuuint64_t*,
                             const cuuint32_t*, const cuuint32_t*, CUtensorMapInterleave, CUtensorMapSwizzle,
                             CUtensorMapL2promotion, CUtensorMapFloatOOBfill);

void encode_map(EncodeFn encode, CUtensorMap* m, void* p, int rank, const cuuint64_t* dim, const cuuint64_t* str,
                const cuuint32_t* box, CUtensorMapSwizzle sw) {
  const cuuint32_t es[5] = {1, 1, 1, 1, 1};
  CUresult r = encode(m, CU_TENSOR_MAP_DATA_TYPE_BFLOAT16, rank, p, dim, str, box, es, CU_TENSOR_MAP_INTERLEAVE_NONE, sw,
                      CU_TENSOR_MAP_L2_PROMOTION_L2_128B, CU_TENSOR_MAP_FLOAT_OOB_FILL_NONE);
  if (r != CUDA_SUCCESS) fprintf(stderr, "tensor map encode failed: %d\n", (int)r);
}

}

extern "C" void kernel_launch(void* const* d_in, const int* in_sizes, int n_in, void* d_out, int out_size) {
  static EncodeFn encode = nullptr;
  static int grid = 0;
  if (!encode) {
    cudaDriverEntryPointQueryResult qr;
    void* fn = nullptr;
    cudaGetDriverEntryPoint("cuTensorMapEncodeTiled", &fn, cudaEnableDefault, &qr);
    encode = (EncodeFn)fn;
    cudaFuncSetAttribute(swin_attn_kernel, cudaFuncAttributeMaxDynamicSharedMemorySize, SMEM_BYTES);
    cudaLaunchConfig_t cfg = {};
    cfg.gridDim = dim3(132);
    cfg.blockDim = dim3(384);
    cfg.dynamicSmemBytes = SMEM_BYTES;
    cudaLaunchAttribute at;
    at.id = cudaLaunchAttributeClusterDimension;
    at.val.clusterDim.x = 2;
    at.val.clusterDim.y = 1;
    at.val.clusterDim.z = 1;
    cfg.attrs = &at;
    cfg.numAttrs = 1;
    int ncl = 0;
    if (cudaOccupancyMaxActiveClusters(&ncl, swin_attn_kernel, &cfg) != cudaSuccess || ncl < 1) {
      (void)cudaGetLastError();
      ncl = 66;
    }
    if (ncl > 256) ncl = 256;
    grid = 2 * ncl;
  }
  Maps maps;
  {
    const cuuint64_t dim[5] = {64, 2, 512, 3, 256}, str[4] = {384, 512 * 384, 128, 768};
    const cuuint32_t box[5] = {64, 2, 4, 3, 2};
    encode_map(encode, &maps.x, d_in[0], 5, dim, str, box, CU_TENSOR_MAP_SWIZZLE_128B);
  }
  {
    const cuuint64_t dim[5] = {64, 4, 2, 4, 8192}, str[4] = {1024, 128, 256, 4096};
    const cuuint32_t box[5] = {64, 4, 2, 4, 1};
    encode_map(encode, &maps.mask, d_in[5], 5, dim, str, box, CU_TENSOR_MAP_SWIZZLE_128B);
  }
  {
    const cuuint64_t dim[5] = {32, 2, 512, 6, 256}, str[4] = {384, 512 * 384, 64, 768};
    const cuuint32_t box[5] = {32, 2, 4, 3, 2};
    encode_map(encode, &maps.out, d_out, 5, dim, str, box, CU_TENSOR_MAP_SWIZZLE_64B);
  }
  {
    const cuuint64_t dim[3] = {32, 192, 18}, str[2] = {576 * 2, 64};
    const cuuint32_t box[3] = {32, 192, 1};
    encode_map(encode, &maps.wqkv, d_in[1], 3, dim, str, box, CU_TENSOR_MAP_SWIZZLE_64B);
    const cuuint64_t dim2[3] = {32, 192, 6}, str2[2] = {192 * 2, 64};
    const cuuint32_t box2[3] = {32, 96, 3};
    encode_map(encode, &maps.wo, d_in[2], 3, dim2, str2, box2, CU_TENSOR_MAP_SWIZZLE_64B);
    const cuuint64_t dim3_[5] = {192, 2, 4, 4, 6}, str3[4] = {384, 8 * 384, 2 * 384, 32 * 384};
    const cuuint32_t box3[5] = {32, 2, 4, 4, 3};
    encode_map(encode, &maps.wop, d_in[2], 5, dim3_, str3, box3, CU_TENSOR_MAP_SWIZZLE_64B);
  }
  swin_attn_kernel<<<grid, 384, SMEM_BYTES>>>(maps, (const __nv_bfloat16*)d_in[3], (const int*)d_in[4], NWIN / (grid / 2) * (grid / 2), 0);
}
```

```cpp
#include <cuda_runtime.h>
#include <cuda_bf16.h>
#include <cuda.h>
#include <stdint.h>
#include <stdio.h>

namespace {

constexpr int NWIN = 4096;
constexpr int KV_WG = 0;
constexpr int Q_SPLIT = 4;
constexpr int EXP_CH = 4;

constexpr uint32_t SM_BASE  = 1024;
constexpr uint32_t OFF_WQ   = 0;
constexpr uint32_t OFF_WO   = 36864;
constexpr uint32_t STAGE    = 70656;
constexpr uint32_t OFF_X    = 73728;
constexpr uint32_t X_BYTES  = 24576;
constexpr uint32_t OFF_MASK = OFF_X + X_BYTES;
constexpr uint32_t M_BYTES  = 8192;
constexpr uint32_t OFF_KV   = OFF_MASK + M_BYTES;
constexpr uint32_t OFF_OIN  = OFF_KV + 25600;
constexpr uint32_t O_BYTES  = 12288;
constexpr uint32_t OFF_BAR  = 215040;
constexpr uint32_t OFF_RPB  = OFF_BAR + 1024;
constexpr uint32_t SMEM_BYTES = OFF_RPB + 1024;
constexpr uint32_t B_XFULL = 0, B_XEMPTY = 16, B_OFULL = 32, B_OEMPTY = 48, B_WKV = 64  , B_WQ = 88, B_WO = 96,
                   B_TICK = 104, B_M0 = 112, W_TICK = 120;
enum { T0 = 1, T1, T2, T3, T4, T5, T6, T7, BAR_BIAS, BAR_STAGE };

__device__ unsigned int g_ticket;

template <int V> struct IC { static constexpr int value = V; };
struct Maps { CUtensorMap x, mask, out, wqkv, wo, wop, xpf, mpf; };

__device__ __forceinline__ void mma_q_init(float (&d)[48], uint64_t descA, uint64_t descB) {
  asm volatile("wgmma.mma_async.sync.aligned.m64n96k16.f32.bf16.bf16 {%0, %1, %2, %3, %4, %5, %6, %7, %8, %9, %10, %11, %12, %13, %14, %15, %16, %17, %18, %19, %20, %21, %22, %23, %24, %25, %26, %27, %28, %29, %30, %31, %32, %33, %34, %35, %36, %37, %38, %39, %40, %41, %42, %43, %44, %45, %46, %47}, "
    "%48, %49, 0, 1, 1, 0, 1;"
    : "+f"(d[0]), "+f"(d[1]), "+f"(d[2]), "+f"(d[3]), "+f"(d[4]), "+f"(d[5]), "+f"(d[6]), "+f"(d[7]), "+f"(d[8]), "+f"(d[9]), "+f"(d[10]), "+f"(d[11]), "+f"(d[12]), "+f"(d[13]), "+f"(d[14]), "+f"(d[15]), "+f"(d[16]), "+f"(d[17]), "+f"(d[18]), "+f"(d[19]), "+f"(d[20]), "+f"(d[21]), "+f"(d[22]), "+f"(d[23]), "+f"(d[24]), "+f"(d[25]), "+f"(d[26]), "+f"(d[27]), "+f"(d[28]), "+f"(d[29]), "+f"(d[30]), "+f"(d[31]), "+f"(d[32]), "+f"(d[33]), "+f"(d[34]), "+f"(d[35]), "+f"(d[36]), "+f"(d[37]), "+f"(d[38]), "+f"(d[39]), "+f"(d[40]), "+f"(d[41]), "+f"(d[42]), "+f"(d[43]), "+f"(d[44]), "+f"(d[45]), "+f"(d[46]), "+f"(d[47])
    : "l"(descA), "l"(descB));
}
__device__ __forceinline__ void mma_q(float (&d)[48], uint64_t descA, uint64_t descB) {
  asm volatile("wgmma.mma_async.sync.aligned.m64n96k16.f32.bf16.bf16 {%0, %1, %2, %3, %4, %5, %6, %7, %8, %9, %10, %11, %12, %13, %14, %15, %16, %17, %18, %19, %20, %21, %22, %23, %24, %25, %26, %27, %28, %29, %30, %31, %32, %33, %34, %35, %36, %37, %38, %39, %40, %41, %42, %43, %44, %45, %46, %47}, "
    "%48, %49, 1, 1, 1, 0, 1;"
    : "+f"(d[0]), "+f"(d[1]), "+f"(d[2]), "+f"(d[3]), "+f"(d[4]), "+f"(d[5]), "+f"(d[6]), "+f"(d[7]), "+f"(d[8]), "+f"(d[9]), "+f"(d[10]), "+f"(d[11]), "+f"(d[12]), "+f"(d[13]), "+f"(d[14]), "+f"(d[15]), "+f"(d[16]), "+f"(d[17]), "+f"(d[18]), "+f"(d[19]), "+f"(d[20]), "+f"(d[21]), "+f"(d[22]), "+f"(d[23]), "+f"(d[24]), "+f"(d[25]), "+f"(d[26]), "+f"(d[27]), "+f"(d[28]), "+f"(d[29]), "+f"(d[30]), "+f"(d[31]), "+f"(d[32]), "+f"(d[33]), "+f"(d[34]), "+f"(d[35]), "+f"(d[36]), "+f"(d[37]), "+f"(d[38]), "+f"(d[39]), "+f"(d[40]), "+f"(d[41]), "+f"(d[42]), "+f"(d[43]), "+f"(d[44]), "+f"(d[45]), "+f"(d[46]), "+f"(d[47])
    : "l"(descA), "l"(descB));
}
__device__ __forceinline__ void mma_kv_init(float (&d)[32], uint32_t a0, uint32_t a1, uint32_t a2, uint32_t a3, uint64_t descB) {
  asm volatile("wgmma.mma_async.sync.aligned.m64n64k16.f32.bf16.bf16 {%0, %1, %2, %3, %4, %5, %6, %7, %8, %9, %10, %11, %12, %13, %14, %15, %16, %17, %18, %19, %20, %21, %22, %23, %24, %25, %26, %27, %28, %29, %30, %31}, "
    "{%32, %33, %34, %35}, %36, 0, 1, 1, 0;"
    : "+f"(d[0]), "+f"(d[1]), "+f"(d[2]), "+f"(d[3]), "+f"(d[4]), "+f"(d[5]), "+f"(d[6]), "+f"(d[7]), "+f"(d[8]), "+f"(d[9]), "+f"(d[10]), "+f"(d[11]), "+f"(d[12]), "+f"(d[13]), "+f"(d[14]), "+f"(d[15]), "+f"(d[16]), "+f"(d[17]), "+f"(d[18]), "+f"(d[19]), "+f"(d[20]), "+f"(d[21]), "+f"(d[22]), "+f"(d[23]), "+f"(d[24]), "+f"(d[25]), "+f"(d[26]), "+f"(d[27]), "+f"(d[28]), "+f"(d[29]), "+f"(d[30]), "+f"(d[31])
    : "r"(a0), "r"(a1), "r"(a2), "r"(a3), "l"(descB));
}
__device__ __forceinline__ void mma_kv(float (&d)[32], uint32_t a0, uint32_t a1, uint32_t a2, uint32_t a3, uint64_t descB) {
  asm volatile("wgmma.mma_async.sync.aligned.m64n64k16.f32.bf16.bf16 {%0, %1, %2, %3, %4, %5, %6, %7, %8, %9, %10, %11, %12, %13, %14, %15, %16, %17, %18, %19, %20, %21, %22, %23, %24, %25, %26, %27, %28, %29, %30, %31}, "
    "{%32, %33, %34, %35}, %36, 1, 1, 1, 0;"
    : "+f"(d[0]), "+f"(d[1]), "+f"(d[2]), "+f"(d[3]), "+f"(d[4]), "+f"(d[5]), "+f"(d[6]), "+f"(d[7]), "+f"(d[8]), "+f"(d[9]), "+f"(d[10]), "+f"(d[11]), "+f"(d[12]), "+f"(d[13]), "+f"(d[14]), "+f"(d[15]), "+f"(d[16]), "+f"(d[17]), "+f"(d[18]), "+f"(d[19]), "+f"(d[20]), "+f"(d[21]), "+f"(d[22]), "+f"(d[23]), "+f"(d[24]), "+f"(d[25]), "+f"(d[26]), "+f"(d[27]), "+f"(d[28]), "+f"(d[29]), "+f"(d[30]), "+f"(d[31])
    : "r"(a0), "r"(a1), "r"(a2), "r"(a3), "l"(descB));
}
__device__ __forceinline__ void mma_s(float (&d)[32], uint32_t a0, uint32_t a1, uint32_t a2, uint32_t a3, uint64_t descB) {
  asm volatile("wgmma.mma_async.sync.aligned.m64n64k16.f32.bf16.bf16 {%0, %1, %2, %3, %4, %5, %6, %7, %8, %9, %10, %11, %12, %13, %14, %15, %16, %17, %18, %19, %20, %21, %22, %23, %24, %25, %26, %27, %28, %29, %30, %31}, "
    "{%32, %33, %34, %35}, %36, 1, 1, 1, 1;"
    : "+f"(d[0]), "+f"(d[1]), "+f"(d[2]), "+f"(d[3]), "+f"(d[4]), "+f"(d[5]), "+f"(d[6]), "+f"(d[7]), "+f"(d[8]), "+f"(d[9]), "+f"(d[10]), "+f"(d[11]), "+f"(d[12]), "+f"(d[13]), "+f"(d[14]), "+f"(d[15]), "+f"(d[16]), "+f"(d[17]), "+f"(d[18]), "+f"(d[19]), "+f"(d[20]), "+f"(d[21]), "+f"(d[22]), "+f"(d[23]), "+f"(d[24]), "+f"(d[25]), "+f"(d[26]), "+f"(d[27]), "+f"(d[28]), "+f"(d[29]), "+f"(d[30]), "+f"(d[31])
    : "r"(a0), "r"(a1), "r"(a2), "r"(a3), "l"(descB));
}
__device__ __forceinline__ void mma_p_init(float (&d)[28], uint32_t a0, uint32_t a1, uint32_t a2, uint32_t a3, uint64_t descB) {
  asm volatile("wgmma.mma_async.sync.aligned.m64n56k16.f32.bf16.bf16 {%0, %1, %2, %3, %4, %5, %6, %7, %8, %9, %10, %11, %12, %13, %14, %15, %16, %17, %18, %19, %20, %21, %22, %23, %24, %25, %26, %27}, "
    "{%28, %29, %30, %31}, %32, 0, 1, 1, 0;"
    : "=f"(d[0]), "=f"(d[1]), "=f"(d[2]), "=f"(d[3]), "=f"(d[4]), "=f"(d[5]), "=f"(d[6]), "=f"(d[7]), "=f"(d[8]), "=f"(d[9]), "=f"(d[10]), "=f"(d[11]), "=f"(d[12]), "=f"(d[13]), "=f"(d[14]), "=f"(d[15]), "=f"(d[16]), "=f"(d[17]), "=f"(d[18]), "=f"(d[19]), "=f"(d[20]), "=f"(d[21]), "=f"(d[22]), "=f"(d[23]), "=f"(d[24]), "=f"(d[25]), "=f"(d[26]), "=f"(d[27])
    : "r"(a0), "r"(a1), "r"(a2), "r"(a3), "l"(descB));
}
__device__ __forceinline__ void mma_p(float (&d)[28], uint32_t a0, uint32_t a1, uint32_t a2, uint32_t a3, uint64_t descB) {
  asm volatile("wgmma.mma_async.sync.aligned.m64n56k16.f32.bf16.bf16 {%0, %1, %2, %3, %4, %5, %6, %7, %8, %9, %10, %11, %12, %13, %14, %15, %16, %17, %18, %19, %20, %21, %22, %23, %24, %25, %26, %27}, "
    "{%28, %29, %30, %31}, %32, 1, 1, 1, 0;"
    : "+f"(d[0]), "+f"(d[1]), "+f"(d[2]), "+f"(d[3]), "+f"(d[4]), "+f"(d[5]), "+f"(d[6]), "+f"(d[7]), "+f"(d[8]), "+f"(d[9]), "+f"(d[10]), "+f"(d[11]), "+f"(d[12]), "+f"(d[13]), "+f"(d[14]), "+f"(d[15]), "+f"(d[16]), "+f"(d[17]), "+f"(d[18]), "+f"(d[19]), "+f"(d[20]), "+f"(d[21]), "+f"(d[22]), "+f"(d[23]), "+f"(d[24]), "+f"(d[25]), "+f"(d[26]), "+f"(d[27])
    : "r"(a0), "r"(a1), "r"(a2), "r"(a3), "l"(descB));
}
__device__ __forceinline__ void mma_o_init(float (&d)[48], uint32_t a0, uint32_t a1, uint32_t a2, uint32_t a3, uint64_t descB) {
  asm volatile("wgmma.mma_async.sync.aligned.m64n96k16.f32.bf16.bf16 {%0, %1, %2, %3, %4, %5, %6, %7, %8, %9, %10, %11, %12, %13, %14, %15, %16, %17, %18, %19, %20, %21, %22, %23, %24, %25, %26, %27, %28, %29, %30, %31, %32, %33, %34, %35, %36, %37, %38, %39, %40, %41, %42, %43, %44, %45, %46, %47}, "
    "{%48, %49, %50, %51}, %52, 0, 1, 1, 1;"
    : "=f"(d[0]), "=f"(d[1]), "=f"(d[2]), "=f"(d[3]), "=f"(d[4]), "=f"(d[5]), "=f"(d[6]), "=f"(d[7]), "=f"(d[8]), "=f"(d[9]), "=f"(d[10]), "=f"(d[11]), "=f"(d[12]), "=f"(d[13]), "=f"(d[14]), "=f"(d[15]), "=f"(d[16]), "=f"(d[17]), "=f"(d[18]), "=f"(d[19]), "=f"(d[20]), "=f"(d[21]), "=f"(d[22]), "=f"(d[23]), "=f"(d[24]), "=f"(d[25]), "=f"(d[26]), "=f"(d[27]), "=f"(d[28]), "=f"(d[29]), "=f"(d[30]), "=f"(d[31]), "=f"(d[32]), "=f"(d[33]), "=f"(d[34]), "=f"(d[35]), "=f"(d[36]), "=f"(d[37]), "=f"(d[38]), "=f"(d[39]), "=f"(d[40]), "=f"(d[41]), "=f"(d[42]), "=f"(d[43]), "=f"(d[44]), "=f"(d[45]), "=f"(d[46]), "=f"(d[47])
    : "r"(a0), "r"(a1), "r"(a2), "r"(a3), "l"(descB));
}
__device__ __forceinline__ void mma_o(float (&d)[48], uint32_t a0, uint32_t a1, uint32_t a2, uint32_t a3, uint64_t descB) {
  asm volatile("wgmma.mma_async.sync.aligned.m64n96k16.f32.bf16.bf16 {%0, %1, %2, %3, %4, %5, %6, %7, %8, %9, %10, %11, %12, %13, %14, %15, %16, %17, %18, %19, %20, %21, %22, %23, %24, %25, %26, %27, %28, %29, %30, %31, %32, %33, %34, %35, %36, %37, %38, %39, %40, %41, %42, %43, %44, %45, %46, %47}, "
    "{%48, %49, %50, %51}, %52, 1, 1, 1, 1;"
    : "+f"(d[0]), "+f"(d[1]), "+f"(d[2]), "+f"(d[3]), "+f"(d[4]), "+f"(d[5]), "+f"(d[6]), "+f"(d[7]), "+f"(d[8]), "+f"(d[9]), "+f"(d[10]), "+f"(d[11]), "+f"(d[12]), "+f"(d[13]), "+f"(d[14]), "+f"(d[15]), "+f"(d[16]), "+f"(d[17]), "+f"(d[18]), "+f"(d[19]), "+f"(d[20]), "+f"(d[21]), "+f"(d[22]), "+f"(d[23]), "+f"(d[24]), "+f"(d[25]), "+f"(d[26]), "+f"(d[27]), "+f"(d[28]), "+f"(d[29]), "+f"(d[30]), "+f"(d[31]), "+f"(d[32]), "+f"(d[33]), "+f"(d[34]), "+f"(d[35]), "+f"(d[36]), "+f"(d[37]), "+f"(d[38]), "+f"(d[39]), "+f"(d[40]), "+f"(d[41]), "+f"(d[42]), "+f"(d[43]), "+f"(d[44]), "+f"(d[45]), "+f"(d[46]), "+f"(d[47])
    : "r"(a0), "r"(a1), "r"(a2), "r"(a3), "l"(descB));
}

__device__ __forceinline__ void wg_fence() { asm volatile("wgmma.fence.sync.aligned;" ::: "memory"); }
__device__ __forceinline__ void wg_commit() { asm volatile("wgmma.commit_group.sync.aligned;" ::: "memory"); }
template <int N> __device__ __forceinline__ void wg_wait() { asm volatile("wgmma.wait_group.sync.aligned %0;" ::"n"(N) : "memory"); }
template <int N> __device__ __forceinline__ void pin(float (&d)[N]) {
#pragma unroll
  for (int i = 0; i < N; i++) asm volatile("" : "+f"(d[i])::"memory");
}
template <int N> __device__ __forceinline__ void pin(uint32_t (&d)[N]) {
#pragma unroll
  for (int i = 0; i < N; i++) asm volatile("" : "+r"(d[i])::"memory");
}
__device__ __forceinline__ uint64_t mkdesc(uint32_t lo, uint32_t hi) { return ((uint64_t)hi << 32) | lo; }
constexpr uint64_t EVICT_FIRST = 0x12F0000000000000ull;
constexpr uint32_t HI_X = (3072 >> 4) | (1u << 30);
constexpr uint32_t HI_KV = (1024 >> 4) | (1u << 30);
constexpr uint32_t HI_W = (512 >> 4) | (2u << 30);
constexpr uint32_t HI_O = (1536 >> 4) | (2u << 30);
constexpr uint32_t LO_O = (1u << 16) + ((SM_BASE + OFF_OIN) >> 4);
constexpr uint32_t LO_WQ = ((12288 >> 4) << 16) + ((SM_BASE + OFF_WQ) >> 4);
constexpr uint32_t LO_WO = ((6144 >> 4) << 16) + ((SM_BASE + OFF_WO) >> 4);
constexpr uint32_t LO_X = (1u << 16) + ((SM_BASE + OFF_X) >> 4);
constexpr uint32_t LO_KV = (1u << 16) + ((SM_BASE + OFF_KV) >> 4);

__device__ __forceinline__ uint32_t pack_bf16(float lo, float hi) {
  uint32_t r;
  asm("cvt.rn.bf16x2.f32 %0, %1, %2;" : "=r"(r) : "f"(hi), "f"(lo));
  return r;
}
__device__ __forceinline__ float ex2(float x) {
  float r;
  asm("ex2.approx.ftz.f32 %0, %1;" : "=f"(r) : "f"(x));
  return r;
}
__device__ __forceinline__ float rcp(float x) {
  float r;
  asm("rcp.approx.ftz.f32 %0, %1;" : "=f"(r) : "f"(x));
  return r;
}
__device__ __forceinline__ bool elect() {
  uint32_t p;
  asm volatile("{\n.reg .pred P;\nelect.sync _|P, 0xffffffff;\nselp.u32 %0, 1, 0, P;\n}" : "=r"(p));
  return p;
}
__device__ __forceinline__ void mbar_init(uint32_t bar, uint32_t cnt) {
  asm volatile("mbarrier.init.shared::cta.b64 [%0], %1;" ::"r"(bar), "r"(cnt) : "memory");
}
__device__ __forceinline__ void mbar_wait(uint32_t bar, uint32_t parity) {
  asm volatile(
      "{\n.reg .pred p;\n.reg .u32 n;\n"
      "mbarrier.try_wait.parity.shared::cta.b64 p, [%0], %1;\n"
      "@p bra DONE;\n"
      "mov.u32 n, 0;\n"
      "LOOP:\n"
      "mbarrier.try_wait.parity.shared::cta.b64 p, [%0], %1;\n"
      "@p bra DONE;\n"
      "add.u32 n, n, 1;\n"
      "setp.lt.u32 p, n, 0x400000;\n"
      "@p bra LOOP;\n"
      "trap;\n"
      "DONE:\n}\n" ::"r"(bar), "r"(parity)
      : "memory");
}
__device__ __forceinline__ void mbar_arrive_cluster(uint32_t bar) {
  asm volatile("mbarrier.arrive.shared::cluster.b64 _, [%0];" ::"r"(bar) : "memory");
}
__device__ __forceinline__ void mbar_expect_tx(uint32_t bar, uint32_t bytes) {
  asm volatile("mbarrier.arrive.expect_tx.shared::cta.b64 _, [%0], %1;" ::"r"(bar), "r"(bytes) : "memory");
}
__device__ __forceinline__ uint32_t mapa(uint32_t addr, uint32_t rank) {
  uint32_t r;
  asm("mapa.shared::cluster.u32 %0, %1, %2;" : "=r"(r) : "r"(addr), "r"(rank));
  return r;
}
__device__ __forceinline__ void sched_fence(uint32_t& keep, int never) {
  asm volatile("{\n.reg .pred p;\nsetp.ne.s32 p, %1, 0;\n@p mov.u32 %0, %clock;\n}" : "+r"(keep) : "r"(never) : "memory");
}
template <int ID> __device__ __forceinline__ void tok_wait() { asm volatile("bar.sync %0, %1;" ::"n"(ID), "n"(ID == T7 ? 384 : 256) : "memory"); }
template <int ID> __device__ __forceinline__ void tok_pass() { asm volatile("bar.arrive %0, %1;" ::"n"(ID), "n"(ID == T7 ? 384 : 256) : "memory"); }
__device__ __forceinline__ void fence_async() { asm volatile("fence.proxy.async.shared::cta;" ::: "memory"); }
__device__ __forceinline__ void stsm4(uint32_t addr, uint32_t r0, uint32_t r1, uint32_t r2, uint32_t r3) {
  asm volatile("stmatrix.sync.aligned.m8n8.x4.shared.b16 [%0], {%1,%2,%3,%4};" ::"r"(addr), "r"(r0), "r"(r1), "r"(r2), "r"(r3) : "memory");
}
__device__ __forceinline__ void lds128(uint32_t addr, uint32_t& r0, uint32_t& r1, uint32_t& r2, uint32_t& r3) {
  asm volatile("ld.shared.v4.b32 {%0,%1,%2,%3}, [%4];" : "=r"(r0), "=r"(r1), "=r"(r2), "=r"(r3) : "r"(addr) : "memory");
}
template <int OFF>
__device__ __forceinline__ void st_async(uint32_t addr, uint32_t bar, uint32_t r0, uint32_t r1, uint32_t r2, uint32_t r3) {
  asm volatile("st.async.shared::cluster.mbarrier::complete_tx::bytes.v4.b32 [%0+%6], {%1,%2,%3,%4}, [%5];" ::"r"(addr), "r"(r0),
               "r"(r1), "r"(r2), "r"(r3), "r"(bar), "n"(OFF)
               : "memory");
}
__device__ __forceinline__ void tma5_mc(uint32_t dst, const CUtensorMap* tm, uint32_t bar, int c2, int c4) {
  asm volatile(
      "cp.async.bulk.tensor.5d.shared::cluster.global.mbarrier::complete_tx::bytes.multicast::cluster.L2::cache_hint "
      "[%0], [%1, {0, 0, %3, 0, %4}], [%2], %5, %6;" ::"r"(dst), "l"(tm), "r"(bar), "r"(c2), "r"(c4), "h"((uint16_t)3), "l"(EVICT_FIRST)
      : "memory");
}
__device__ __forceinline__ void tma3_pf(const CUtensorMap* tm, int c1, int c2) {
  asm volatile("cp.async.bulk.prefetch.tensor.3d.L2.global [%0, {0, %1, %2}];" ::"l"(tm), "r"(c1), "r"(c2) : "memory");
}
__device__ __forceinline__ void tma3(uint32_t dst, const CUtensorMap* tm, uint32_t bar, int c1, int c2) {
  asm volatile("cp.async.bulk.tensor.3d.shared::cluster.global.mbarrier::complete_tx::bytes [%0], [%1, {0, %3, %4}], [%2];" ::"r"(dst),
               "l"(tm), "r"(bar), "r"(c1), "r"(c2)
               : "memory");
}

constexpr float SQRT_HD = 6.92820323027551f;
constexpr float SM_C = 1.4426950408889634f / SQRT_HD;

__device__ __forceinline__ void s_init(float (&s)[32], const uint32_t (&mk)[16], const uint32_t (&b)[16]) {
#pragma unroll
  for (int i = 0; i < 16; i++) {
    const int o = 4 * (i & 7) + 2 * (i >> 3);
    uint32_t t0, t1;
    asm("{\n.reg .b16 ml, mh, bl, bh;\n.reg .b32 m2, b2;\n"
        "mov.b32 {ml, mh}, %1;\nmov.b32 {bl, bh}, %3;\nmov.b32 m2, {ml, ml};\nmov.b32 b2, {bl, bl};\n"
        "fma.rn.bf16x2 %0, m2, %2, b2;\n}"
        : "=r"(t0)
        : "r"(mk[i]), "r"(0x40DE40DEu), "r"(b[i]));
    asm("fma.rn.bf16x2 %0, %1, %2, %3;" : "=r"(t1) : "r"(mk[i]), "r"(0x40DE40DEu), "r"(b[i]));
    s[o] = __uint_as_float(t0);
    s[o + 1] = __uint_as_float(t1);
    asm volatile("" : "+f"(s[o]), "+f"(s[o + 1])::"memory");
  }
}
__device__ __forceinline__ uint32_t pack_bias(float lo, float hi) {
  uint32_t l = __float_as_uint(fmaf(lo, SQRT_HD, 0x1p-100f)), h = __float_as_uint(fmaf(hi, SQRT_HD, 0x1p-100f));
  l = (l - (l >> 16) + 0x8000u) >> 16;
  return ((h - l + 0x8000u) & 0xffff0000u) | l;
}
template <bool NEG>
__device__ __forceinline__ int pick3(int a, int b, int c) { return NEG ? (int)__vimin3_u32(a, b, c) : __vimax3_s32(a, b, c); }
template <bool NEG>
__device__ __forceinline__ int pick2(int a, int b) { return NEG ? (int)min((unsigned)a, (unsigned)b) : max(a, b); }
template <bool NEG>
__device__ __forceinline__ void row_pick(const float (&s)[32], int& i0, int& i1) {
#define FI(x) __float_as_int(x)
  i0 = pick2<NEG>(FI(s[0]), FI(s[1])), i1 = pick2<NEG>(FI(s[2]), FI(s[3]));
  int k0 = pick3<NEG>(FI(s[4]), FI(s[5]), FI(s[8])), k1 = pick3<NEG>(FI(s[6]), FI(s[7]), FI(s[10]));
  i0 = pick3<NEG>(i0, FI(s[9]), FI(s[12]));   i1 = pick3<NEG>(i1, FI(s[11]), FI(s[14]));
  k0 = pick3<NEG>(k0, FI(s[13]), FI(s[16]));  k1 = pick3<NEG>(k1, FI(s[15]), FI(s[18]));
  i0 = pick3<NEG>(i0, FI(s[17]), FI(s[20]));  i1 = pick3<NEG>(i1, FI(s[19]), FI(s[22]));
  k0 = pick3<NEG>(k0, FI(s[21]), FI(s[24]));  k1 = pick3<NEG>(k1, FI(s[23]), FI(s[26]));
  i0 = pick3<NEG>(i0, FI(s[25]), FI(s[28]));  i1 = pick3<NEG>(i1, FI(s[27]), FI(s[30]));
  i0 = pick3<NEG>(i0, k0, FI(s[29]));         i1 = pick3<NEG>(i1, k1, FI(s[31]));
#undef FI
}
template <bool NEG>
__device__ __forceinline__ void quad_pick(int& i0, int& i1, int x) {
  i0 = pick2<NEG>(i0, __shfl_xor_sync(0xffffffffu, i0, x));
  i1 = pick2<NEG>(i1, __shfl_xor_sync(0xffffffffu, i1, x));
}
__device__ __forceinline__ void fix_negative_rows(const float (&s)[32], int& i0, int& i1) {
  int n0, n1;
  row_pick<true>(s, n0, n1);
  quad_pick<true>(n0, n1, 1);
  quad_pick<true>(n0, n1, 2);
  if (i0 < 0) i0 = n0;
  if (i1 < 0) i1 = n1;
}
template <int CH>
__device__ __forceinline__ void exp_rows(const float (&s)[32], uint32_t (&p)[16], int max0, int max1, uint32_t& keep, int never) {
  const float m0 = __int_as_float(max0) * -SM_C, m1 = __int_as_float(max1) * -SM_C;
  float t[32];
#pragma unroll
  for (int c = 0; c <= 16 / CH; c++) {
#pragma unroll
    for (int i = 2 * CH * c; i < 2 * CH * (c + 1) && i < 32; i++) {
      t[i] = fmaf(s[i], SM_C, (i & 2) ? m1 : m0);
      asm volatile("" : "+f"(t[i]));
    }
    if (c > 0) {
#pragma unroll
      for (int i = CH * (c - 1); i < CH * c; i++) {
        t[2 * i] = ex2(t[2 * i]), t[2 * i + 1] = ex2(t[2 * i + 1]);
        asm volatile("" : "+f"(t[2 * i]), "+f"(t[2 * i + 1]));
      }
    }
    if (c > 1) {
#pragma unroll
      for (int i = CH * (c - 2); i < CH * (c - 1); i++) {
        p[i] = pack_bf16(t[2 * i], t[2 * i + 1]);
        asm volatile("" : "+r"(p[i]));
      }
    }
    if (c < 16 / CH) sched_fence(keep, never);
  }
#pragma unroll
  for (int i = 16 - CH; i < 16; i++) p[i] = pack_bf16(t[2 * i], t[2 * i + 1]);
  pin(p);
}
__device__ __forceinline__ void issue_p(float (&o)[28], const uint32_t (&p)[16], uint32_t lo) {
#pragma unroll
  for (int ks = 0; ks < 4; ks++) {
    uint64_t db = mkdesc(lo + ks * 2, HI_KV);
    if (ks == 0) mma_p_init(o, p[0], p[1], p[2], p[3], db);
    else mma_p(o, p[4 * ks], p[4 * ks + 1], p[4 * ks + 2], p[4 * ks + 3], db);
  }
  wg_commit();
}
template <int SUM, int OFF>
__device__ __forceinline__ void normalize(const float (&o)[28], uint32_t (&f)[12]) {
  const float r0 = rcp(o[SUM]), r1 = rcp(o[SUM + 2]);
  uint32_t h0 = pack_bf16(r0, r0), h1 = pack_bf16(r1, r1);
#pragma unroll
  for (int j = 0; j < 12; j++)
    asm("mul.rn.bf16x2 %0, %1, %2;" : "=r"(f[j]) : "r"(pack_bf16(o[OFF + 2 * j], o[OFF + 2 * j + 1])), "r"((j & 1) ? h1 : h0));
}

__global__ void __cluster_dims__(2, 1, 1) __launch_bounds__(384, 1)
swin_attn_kernel(const __grid_constant__ Maps maps, const __nv_bfloat16* __restrict__ rpb, const int* __restrict__ rp_idx, int base, int never) {
  extern __shared__ __align__(1024) uint8_t smem_raw[];
  const uint32_t sb = (uint32_t)__cvta_generic_to_shared(smem_raw);
  const int tid = threadIdx.x;
  const int wg = __shfl_sync(0xffffffffu, tid >> 7, 0);
  const int warp = __shfl_sync(0xffffffffu, (tid >> 5) & 3, 0);
  const int lane = tid & 31;
  const int rank = blockIdx.x & 1;
  const int cl = blockIdx.x >> 1;
  const int ncl = gridDim.x >> 1;
  const uint32_t bars = sb + OFF_BAR;
  int extra = NWIN;
  auto read_ticket = [&]() {
    mbar_wait(bars + B_TICK, 0);
    uint32_t t;
    asm volatile("ld.shared.b32 %0, [%1];" : "=r"(t) : "r"(bars + W_TICK) : "memory");
    extra = base + __shfl_sync(0xffffffffu, t, 0);
  };
  auto window = [&](int v) { return v < base ? v : (v < base + ncl ? extra : NWIN); };
  auto prefetch = [&](int p, int win) {
    if (p < 2) tma3_pf(&maps.xpf, ((win * 2 + 1 + p) & 127) * 6, (((win >> 3) & ~7) + 4 + 4 * rank) & 511);
    else tma3_pf(&maps.mpf, 0, 2 * win + rank);
  };
  auto load = [&](int p, int win, int a) {
    if (p < 2)
      tma5_mc(sb + OFF_X + a * STAGE + rank * 12288 + p * 6144, &maps.x, bars + B_XFULL + 8 * a,
              (((win >> 3) & ~7) + 4 + 4 * rank) & 511, (win * 4 + 2 + 2 * p) & 255);
    else tma5_mc(sb + OFF_MASK + a * STAGE + rank * 4096, &maps.mask, bars + B_XFULL + 8 * a, 0, 2 * win + rank);
  };
  auto load_wkv = [&](int b) {
    tma3(sb + OFF_KV + (b < 3 ? b * 12288 : STAGE + (b - 3) * 12288), &maps.wqkv, bars + B_WKV + 8 * (b >> 1), 0,
         (b < 3 ? 6 : 9) + b + 3 * rank);
  };
  auto startup_loads = [&]() {
    if ((sb & 0x3FFFF) != SM_BASE) __trap();
    if (blockIdx.x == 0) asm volatile("st.relaxed.gpu.global.u32 [%0], 0;" ::"l"(&g_ticket) : "memory");
    mbar_expect_tx(bars + B_XFULL, X_BYTES);
    mbar_expect_tx(bars + B_M0, M_BYTES);
    mbar_expect_tx(bars + B_WKV + 8, 24576);
    load_wkv(2);
    load_wkv(3);
    tma5_mc(sb + OFF_MASK + rank * 4096, &maps.mask, bars + B_M0, 0, 2 * cl + rank);
    mbar_expect_tx(bars + B_WQ, 36864);
    for (int nb = 0; nb < 3; nb++) tma3(sb + OFF_WQ + nb * 12288, &maps.wqkv, bars + B_WQ, 0, 3 * rank + nb);
    mbar_expect_tx(bars + B_WKV + 16, 24576);
    load_wkv(4);
    load_wkv(5);
    mbar_expect_tx(bars + B_XFULL + 8, X_BYTES + M_BYTES);
    for (int p = 0; p < 3; p++) load(p, cl + ncl, 1);
    mbar_expect_tx(bars + B_TICK, 4);
    mbar_expect_tx(bars + B_WO, 36864);
    tma3(sb + OFF_WO, &maps.wo, bars + B_WO, 96 * rank, 3 * rank);
    for (int nb = 0; nb < 3; nb++)
      asm volatile("cp.async.bulk.tensor.5d.shared::cluster.global.mbarrier::complete_tx::bytes [%0], [%1, {%3, 0, 0, 0, %4}], [%2];" ::"r"(
                       sb + OFF_WO + 18432 + nb * 6144), "l"(&maps.wop), "r"(bars + B_WO), "r"(96 * rank + 32 * nb), "r"(3 * (rank ^ 1))
                   : "memory");
  };
  if (wg == KV_WG && warp == 3) {
    if (elect()) {
#pragma unroll
      for (int k = 0; k < 15; k++) mbar_init(bars + 8 * k, (k >> 1) == B_OEMPTY / 16 ? 4 : 1);
      asm volatile("fence.mbarrier_init.release.cluster;" ::: "memory");
    }
    __syncwarp();
  }
  asm volatile("barrier.cluster.arrive.relaxed.aligned;" ::: "memory");

  if (wg == KV_WG) {
    if (warp == 3 && elect()) {
      fence_async();
      mbar_expect_tx(bars + B_WKV, 24576);
      load_wkv(0);
      load_wkv(1);
    }
    __syncwarp();
    asm volatile("barrier.cluster.wait.aligned;" ::: "memory");
    if (elect()) {
      if (warp < 2) load(warp, cl, 0);
      else if (warp == 3) startup_loads();
    }
    __syncwarp();
    asm volatile("setmaxnreg.inc.sync.aligned.u32 216;");
    uint32_t w[3][48];
    auto load_frags = [&](int s) {
      const uint32_t la = sb + OFF_KV + (warp >> 1) * 12288 + (8 * (lane >> 4) + (lane & 7)) * 64 +
                          (((2 * (warp & 1) + ((lane >> 3) & 1)) ^ ((lane & 7) >> 1)) << 4);
      mbar_wait(bars + B_WKV + 8 * s, 0);
#pragma unroll
      for (int ks = 0; ks < 12; ks++)
        asm volatile("ldmatrix.sync.aligned.m8n8.x4.trans.shared.b16 {%0,%1,%2,%3}, [%4];"
                     : "=r"(w[s][4 * ks]), "=r"(w[s][4 * ks + 1]), "=r"(w[s][4 * ks + 2]), "=r"(w[s][4 * ks + 3])
                     : "r"(la + s * 24576 + (s == 2 || (s == 1 && warp >= 2) ? STAGE - 36864 : 0) + ks * 1024)
                     : "memory");
    };
    load_frags(0);
    uint32_t sta[4];
#pragma unroll
    for (int jj = 0; jj < 4; jj++) {
      sta[jj] = sb + OFF_KV + (16 * warp + (lane & 15)) * 128 + (((2 * jj + (lane >> 4)) ^ (lane & 7)) << 4);
      asm volatile("" : "+r"(sta[jj]));
    }
    const uint32_t xe_rem = mapa(bars + B_XEMPTY, rank ^ 1);
    const uint32_t v1off = warp > 0 ? 1024 : 0;

#define SF sched_fence(sta[0], never)
    float acc[32];
    uint32_t pk[16];
    auto store = [&](uint32_t off) {
#pragma unroll
      for (int jj = 0; jj < 4; jj++) stsm4(sta[jj] + off, pk[4 * jj], pk[4 * jj + 1], pk[4 * jj + 2], pk[4 * jj + 3]);
    };
    auto issue = [&](int s, uint32_t xd, bool st, uint32_t off) {
#pragma unroll
      for (int ks = 0; ks < 12; ks++) {
        uint64_t db = mkdesc(xd + (((ks >> 2) * 1024 + (ks & 3) * 32) >> 4), HI_X);
        if (ks == 0) mma_kv_init(acc, w[s][0], w[s][1], w[s][2], w[s][3], db);
        else mma_kv(acc, w[s][4 * ks], w[s][4 * ks + 1], w[s][4 * ks + 2], w[s][4 * ks + 3], db);
        if (ks == 1 && st) {
          __syncwarp();
          store(off);
          __syncwarp();
        }
      }
      wg_commit();
    };
    auto convert = [&]() {
      wg_wait<0>();
      pin(acc);
#pragma unroll
      for (int j = 0; j < 16; j++) pk[j] = pack_bf16(acc[2 * j], acc[2 * j + 1]);
      pin(pk);
    };

    mbar_wait(bars + B_XFULL, 0);
    wg_fence();
    issue(0, LO_X, false, 0);
    load_frags(1);
    int nxt = cl + ncl;
    uint32_t ph = 0;
    uint32_t ticket = 0;
    auto step = [&](auto A) -> bool {
      constexpr int a = decltype(A)::value;
      constexpr uint32_t xd = LO_X + a * (STAGE >> 4);
      if (nxt + ncl >= base && nxt < base) read_ticket();
      const bool more = window(nxt) < NWIN;
      const int wn2 = window(nxt + ncl);
      convert();
      wg_fence();
      SF;
      tok_wait<T2>();
      issue(1, xd, true, a * STAGE);
      tok_pass<T3>();
      if (warp < 3 && wn2 < NWIN && elect()) prefetch(warp, wn2);
      __syncwarp();
      const bool first = a == 0 && nxt == cl + ncl;
      convert();
      SF;
      if (!first) tok_wait<T7>();
      store(a * STAGE + 8192);
      fence_async();
      if (first) {
        load_frags(2);
        asm volatile("bar.sync %0, 128;" ::"n"((int)BAR_STAGE) : "memory");
        asm volatile("st.shared.v4.b32 [%0], {%1,%1,%1,%1};" ::"r"(sb + OFF_KV + (warp >> 1) * STAGE + 144 * 128 + (tid & 63) * 16), "r"(0x3F803F80u) : "memory");
      }
      wg_fence();
      tok_wait<T5>();
      issue(2, xd, false, 0);
      tok_pass<T6>();
      if (!more) {
        convert();
        store(a * STAGE + 16384 + v1off);
        fence_async();
        return false;
      }
      mbar_wait(bars + B_XFULL + 8 * (a ^ 1), a ? ph ^ 1 : ph);
      convert();
      wg_fence();
      SF;
      tok_wait<T0>();
      if (tid == KV_WG * 128 && wn2 < NWIN) mbar_arrive_cluster(xe_rem + 8 * a);
      issue(0, LO_X + (a ^ 1) * (STAGE >> 4), true, a * STAGE + 16384 + v1off);
      tok_pass<T1>();
      fence_async();
      nxt += ncl;
      if (wn2 < NWIN) {
        mbar_wait(bars + B_XEMPTY + 8 * a, ph);
        if (elect()) {
          if (warp < 3) {
            load(warp, wn2, a);
          } else {
            mbar_expect_tx(bars + B_XFULL + 8 * a, X_BYTES + M_BYTES);
            if (rank == 0 && nxt + 3 * ncl >= base) {
              if (nxt + 2 * ncl < base) {
                asm volatile("atom.global.inc.u32 %0, [%1], %2;" : "=r"(ticket) : "l"(&g_ticket), "r"(ncl - 1) : "memory");
              } else if (nxt + ncl < base) {
#pragma unroll
                for (int r = 0; r < 2; r++)
                  asm volatile("st.async.shared::cluster.mbarrier::complete_tx::bytes.b32 [%0], %1, [%2];" ::"r"(mapa(bars + W_TICK, r)),
                               "r"(ticket), "r"(mapa(bars + B_TICK, r))
                               : "memory");
              }
            }
          }
        }
        __syncwarp();
      }
      return true;
    };
    while (step(IC<0>{}) && step(IC<1>{})) ph ^= 1;
    tok_wait<T0>();
    tok_pass<T1>();
    tok_wait<T2>();
    tok_pass<T3>();
    tok_wait<T7>();
    tok_wait<T5>();
  } else {
    const int a = wg - (KV_WG == 0 ? 1 : 0);
    const int g = lane >> 2, q = lane & 3;
    const uint32_t bar = bars + 8 * a;
    if (a == 0) {
      tok_pass<T2>();
      tok_pass<T5>();
    }
    asm volatile("setmaxnreg.dec.sync.aligned.u32 144;");
    uint32_t braw[32];
    {
      const int ty = 4 * (warp >> 1) + (g >> 1), tx = 4 * (warp & 1) + (g & 1);
      const int* ip = rp_idx + (ty * 8 + tx) * 64 + 8 * q;
#pragma unroll
      for (int c = 0; c < 8; c++)
        asm volatile("ld.global.nc.v4.b32 {%0,%1,%2,%3}, [%4];"
                     : "=r"(braw[4 * c]), "=r"(braw[4 * c + 1]), "=r"(braw[4 * c + 2]), "=r"(braw[4 * c + 3])
                     : "l"(ip + (c >> 2) * 128 + ((c >> 1) & 1) * 32 + (c & 1) * 4));
      const int e = a * 128 + (tid & 127);
      uint32_t v = 0;
      if (e < 225) asm volatile("ld.global.nc.b32 %0, [%1];" : "=r"(v) : "l"(reinterpret_cast<const uint32_t*>(rpb) + e * 2 + rank));
      asm volatile("st.shared.b32 [%0], %1;" ::"r"(sb + OFF_RPB + e * 4), "r"(v) : "memory");
      tok_wait<BAR_BIAS>();
#pragma unroll
      for (int j = 0; j < 32; j++)
        asm volatile("ld.shared.b32 %0, [%1];" : "=r"(braw[j]) : "r"(sb + OFF_RPB + braw[j] * 4) : "memory");
    }
    asm volatile("barrier.cluster.wait.aligned;" ::: "memory");

    const int mrow = 16 * warp + (g >> 1) + 4 * (g & 1);
#undef SF
#define SF sched_fence(mk_addr, never)
    uint32_t mk_addr = sb + OFF_MASK + a * STAGE + mrow * 128 + ((q ^ (mrow & 7)) << 4);
    const uint32_t ostage = sb + OFF_OIN + a * STAGE + warp * 3072;
    const uint32_t ost = ostage + ((lane >> 3) & 1) * 1536 + (lane & 7) * 64 + (((lane >> 4) ^ ((lane & 7) >> 1)) << 4);
    const uint32_t oin_rem = mapa(ostage + g * 64 + ((q ^ (g >> 1)) << 4), rank ^ 1);
    const uint32_t bar_rem = mapa(bar, rank ^ 1);

    auto store_out = [&](int win) {
      fence_async();
      __syncwarp();
      if (elect()) {
        int yy = (((win >> 3) & ~7) + 4 + 4 * (warp >> 1)) & 511;
        int xh = (win * 4 + 2 + 2 * (warp & 1)) & 255;
        asm volatile("cp.async.bulk.tensor.5d.global.shared::cta.bulk_group [%0, {0, 0, %2, %3, %4}], [%1];" ::"l"(&maps.out), "r"(ostage),
                     "r"(yy), "r"(3 * rank), "r"(xh)
                     : "memory");
        asm volatile("cp.async.bulk.commit_group;" ::: "memory");
      }
      __syncwarp();
    };
    auto release_oin = [&]() {
      if (elect()) {
        asm volatile("cp.async.bulk.wait_group.read 0;" ::: "memory");
        if (warp == 0) mbar_expect_tx(bar + B_OFULL, O_BYTES);
        mbar_arrive_cluster(bar_rem + B_OEMPTY);
      }
      __syncwarp();
    };
    float qa[48];
    uint32_t bias0[16], bias1[16];
    uint32_t mk[16];
    auto load_mask = [&](uint32_t z) {
#pragma unroll
      for (int c = 0; c < 4; c++)
        lds128((c & 1 ? mk_addr ^ (64 + z) : mk_addr) + (c >> 1) * 1024, mk[4 * c], mk[4 * c + 1], mk[4 * c + 2], mk[4 * c + 3]);
    };
    auto clamp_mask = [&]() {
      SF;
#pragma unroll
      for (int j = 0; j < 16; j++) asm("max.NaN.bf16x2 %0, %0, %1;" : "+r"(mk[j]) : "r"(0xFD80FD80u));
      pin(mk);
    };
    auto issue_q = [&](uint32_t ua, bool tok, int win) {
#pragma unroll
      for (int ks = 0; ks < 12; ks++) {
        if (ks == Q_SPLIT && tok) {
          tok_pass<T4>();
          store_out(win);
          tok_wait<T7>();
          wg_fence();
        }
        uint64_t da = mkdesc(ua + LO_X + (((ks >> 2) * 1024 + (ks & 3) * 32) >> 4), HI_X);
        uint64_t db = mkdesc(LO_WQ + ks * 64, HI_W);
        if (ks == 0) mma_q_init(qa, da, db);
        else mma_q(qa, da, db);
      }
      wg_commit();
      if (tok) tok_pass<T5>();
    };
#pragma unroll
    for (int j = 0; j < 16; j++) {
      const uint32_t b0 = braw[2 * j], b1 = braw[2 * j + 1];
      bias0[j] = pack_bias(__uint_as_float(b0 << 16), __uint_as_float(b1 << 16));
      bias1[j] = pack_bias(__uint_as_float(b0 & 0xffff0000u), __uint_as_float(b1 & 0xffff0000u));
    }
    pin(bias0);
    pin(bias1);
    SF;
    mbar_wait(bars + B_WQ, 0);
    wg_fence();
    if (a == 0) tok_wait<T3>();
    else tok_wait<T1>();
    issue_q(a * (STAGE >> 4), false, 0);
    if (a == 0) mbar_wait(bars + B_M0, 0);
    else tok_pass<T2>();
    load_mask(0);
    if (a == 1) {
      tok_wait<T3>();
      tok_pass<T4>();
      tok_pass<T5>();
      tok_wait<T7>();
    }
    clamp_mask();
    uint32_t ph = 0;
    int win = cl + a * ncl;
    for (;; win += 2 * ncl, ph ^= 1) {
      const uint32_t ua = a * (STAGE >> 4) + (win >> 20);
      const uint32_t kd = ua + LO_KV;
      float s0[32], s1[32];
      wg_wait<0>();
      pin(qa);
      uint32_t q0[12], q1[12];
#pragma unroll
      for (int j = 0; j < 12; j++) q0[j] = pack_bf16(qa[2 * j], qa[2 * j + 1]);
#pragma unroll
      for (int j = 0; j < 12; j++) q1[j] = pack_bf16(qa[24 + 2 * j], qa[25 + 2 * j]);
      pin(q0);
      pin(q1);
      s_init(s0, mk, bias0);
      s_init(s1, mk, bias1);
      wg_fence();
      tok_wait<T6>();
#pragma unroll
      for (int ks = 0; ks < 3; ks++)
        mma_s(s0, q0[4 * ks], q0[4 * ks + 1], q0[4 * ks + 2], q0[4 * ks + 3], mkdesc(kd + ks * 128, HI_KV));
      wg_commit();
#pragma unroll
      for (int ks = 0; ks < 3; ks++)
        mma_s(s1, q1[4 * ks], q1[4 * ks + 1], q1[4 * ks + 2], q1[4 * ks + 3], mkdesc(kd + (3 + ks) * 128, HI_KV));
      wg_commit();
      tok_pass<T0>();
      release_oin();
      int x0, x1, y0, y1;
      uint32_t p0[16], p1[16];
      wg_wait<1>();
      pin(s0);
      pin(q0);
      row_pick<false>(s0, x0, x1);
      quad_pick<false>(x0, x1, 1);
      wg_wait<0>();
      pin(s1);
      pin(q1);
      row_pick<false>(s1, y0, y1);
      quad_pick<false>(x0, x1, 2);
      quad_pick<false>(y0, y1, 1);
      quad_pick<false>(y0, y1, 2);
      if (__builtin_expect(__any_sync(0xffffffffu, (x0 | x1 | y0 | y1) < 0), 0)) {
        fix_negative_rows(s0, x0, x1);
        fix_negative_rows(s1, y0, y1);
      }
      exp_rows<EXP_CH>(s0, p0, x0, x1, mk_addr, never);
      exp_rows<EXP_CH>(s1, p1, y0, y1, mk_addr, never);
      float o0[28], o1[28];
      wg_fence();
      SF;
      tok_wait<T4>();
      issue_p(o0, p0, kd + ((96 * 128) >> 4));
      issue_p(o1, p1, kd + ((144 * 128) >> 4));
      tok_pass<T7>();
      mbar_wait(bar + B_OEMPTY, ph);
      uint32_t f0[12], f1[12];
      wg_wait<1>();
      pin(o0);
      pin(p0);
      normalize<24, 0>(o0, f0);
      st_async<0>(oin_rem, bar_rem + B_OFULL, f0[0], f0[2], f0[4], f0[6]);
      st_async<1536>(oin_rem, bar_rem + B_OFULL, f0[1], f0[3], f0[5], f0[7]);
      wg_wait<0>();
      pin(o1);
      pin(p1);
      normalize<0, 4>(o1, f1);
      st_async<512>(oin_rem, bar_rem + B_OFULL, f0[8], f0[10], f1[0], f1[2]);
      st_async<2048>(oin_rem, bar_rem + B_OFULL, f0[9], f0[11], f1[1], f1[3]);
      st_async<1024>(oin_rem, bar_rem + B_OFULL, f1[4], f1[6], f1[8], f1[10]);
      st_async<2560>(oin_rem, bar_rem + B_OFULL, f1[5], f1[7], f1[9], f1[11]);
      pin(f0);
      pin(f1);
      float (&oa)[48] = qa;
      int wn1 = 0, wn2 = 0;
      if ((unsigned)(win - 2 * ncl) >= (unsigned)(base - 4 * ncl)) {
        if (win < 2 * ncl) {
          mbar_wait(bars + B_WO, 0);
        } else {
          read_ticket();
          wn1 = window(win + ncl), wn2 = window(win + 2 * ncl);
        }
      }
      const bool last = wn1 >= NWIN;
      if (!last) tok_wait<T1>();
      wg_fence();
#pragma unroll
      for (int ks = 0; ks < 3; ks++) {
        uint64_t db = mkdesc(LO_WO + ks * 64, HI_W);
        if (ks == 0) mma_o_init(oa, f0[0], f0[1], f0[2], f0[3], db);
        else mma_o(oa, f0[4 * ks], f0[4 * ks + 1], f0[4 * ks + 2], f0[4 * ks + 3], db);
      }
#pragma unroll
      for (int ks = 0; ks < 3; ks++)
        mma_o(oa, f1[4 * ks], f1[4 * ks + 1], f1[4 * ks + 2], f1[4 * ks + 3], mkdesc(LO_WO + (3 + ks) * 64, HI_W));
      mbar_wait(bar + B_OFULL, ph);
      asm volatile("fence.proxy.async::generic.acquire.sync_restrict::shared::cluster.cluster;" ::: "memory");
      wg_fence();
#pragma unroll
      for (int ks = 0; ks < 6; ks++)
        mma_q(oa, mkdesc(ua + LO_O + (((ks >> 1) * 512 + (ks & 1) * 32) >> 4), HI_O), mkdesc(LO_WO + (18432 >> 4) + ks * 64, HI_W));
      wg_commit();
      if (!last) tok_pass<T2>();
      load_mask(win >> 20);
      wg_wait<0>();
      pin(oa);
      pin(f0);
      pin(f1);
#pragma unroll
      for (int jj = 0; jj < 6; jj++)
        stsm4((jj & 1 ? ost ^ (32 + (win >> 20)) : ost) + (jj >> 1) * 512, pack_bf16(oa[8 * jj], oa[8 * jj + 1]), pack_bf16(oa[8 * jj + 2], oa[8 * jj + 3]),
              pack_bf16(oa[8 * jj + 4], oa[8 * jj + 5]), pack_bf16(oa[8 * jj + 6], oa[8 * jj + 7]));
      if (wn2 >= NWIN) {
        if (!last) {
          tok_wait<T3>();
          tok_pass<T4>();
          tok_pass<T5>();
          tok_wait<T7>();
        }
        break;
      }
      wg_fence();
      tok_wait<T3>();
      issue_q(ua, true, win);
      clamp_mask();
    }
    store_out(window(win));
    asm volatile("cp.async.bulk.wait_group.read 0;" ::: "memory");
    __syncwarp();
  }
}

typedef CUresult (*EncodeFn)(CUtensorMap*, CUtensorMapDataType, cuuint32_t, void*, const cuuint64_t*, const cuuint64_t*,
                             const cuuint32_t*, const cuuint32_t*, CUtensorMapInterleave, CUtensorMapSwizzle,
                             CUtensorMapL2promotion, CUtensorMapFloatOOBfill);

void encode_map(EncodeFn encode, CUtensorMap* m, void* p, int rank, const cuuint64_t* dim, const cuuint64_t* str,
                const cuuint32_t* box, CUtensorMapSwizzle sw,
                CUtensorMapL2promotion promo = CU_TENSOR_MAP_L2_PROMOTION_L2_128B) {
  const cuuint32_t es[5] = {1, 1, 1, 1, 1};
  CUresult r = encode(m, CU_TENSOR_MAP_DATA_TYPE_BFLOAT16, rank, p, dim, str, box, es, CU_TENSOR_MAP_INTERLEAVE_NONE, sw,
                      promo, CU_TENSOR_MAP_FLOAT_OOB_FILL_NONE);
  if (r != CUDA_SUCCESS) fprintf(stderr, "tensor map encode failed: %d\n", (int)r);
}

}

extern "C" void kernel_launch(void* const* d_in, const int* in_sizes, int n_in, void* d_out, int out_size) {
  static EncodeFn encode = nullptr;
  static int grid = 0;
  if (!encode) {
    cudaDriverEntryPointQueryResult qr;
    void* fn = nullptr;
    cudaGetDriverEntryPoint("cuTensorMapEncodeTiled", &fn, cudaEnableDefault, &qr);
    encode = (EncodeFn)fn;
    cudaFuncSetAttribute(swin_attn_kernel, cudaFuncAttributeMaxDynamicSharedMemorySize, SMEM_BYTES);
    cudaLaunchConfig_t cfg = {};
    cfg.gridDim = dim3(132);
    cfg.blockDim = dim3(384);
    cfg.dynamicSmemBytes = SMEM_BYTES;
    cudaLaunchAttribute at;
    at.id = cudaLaunchAttributeClusterDimension;
    at.val.clusterDim.x = 2;
    at.val.clusterDim.y = 1;
    at.val.clusterDim.z = 1;
    cfg.attrs = &at;
    cfg.numAttrs = 1;
    int ncl = 0;
    if (cudaOccupancyMaxActiveClusters(&ncl, swin_attn_kernel, &cfg) != cudaSuccess || ncl < 1) {
      (void)cudaGetLastError();
      ncl = 66;
    }
    if (ncl > 256) ncl = 256;
    grid = 2 * ncl;
  }
  Maps maps;
  {
    const cuuint64_t dim[5] = {64, 2, 512, 3, 256}, str[4] = {384, 512 * 384, 128, 768};
    const cuuint32_t box[5] = {64, 2, 4, 3, 2};
    encode_map(encode, &maps.x, d_in[0], 5, dim, str, box, CU_TENSOR_MAP_SWIZZLE_128B);
  }
  {
    const cuuint64_t dim[5] = {64, 4, 2, 4, 8192}, str[4] = {1024, 128, 256, 4096};
    const cuuint32_t box[5] = {64, 4, 2, 4, 1};
    encode_map(encode, &maps.mask, d_in[5], 5, dim, str, box, CU_TENSOR_MAP_SWIZZLE_128B);
  }
  {
    const cuuint64_t dim[3] = {64, 768, 512}, str[2] = {256, 512 * 384};
    const cuuint32_t box[3] = {64, 6, 4};
    encode_map(encode, &maps.xpf, d_in[0], 3, dim, str, box, CU_TENSOR_MAP_SWIZZLE_NONE, CU_TENSOR_MAP_L2_PROMOTION_L2_256B);
    const cuuint64_t dim2[3] = {64, 16, 8192}, str2[2] = {256, 4096};
    const cuuint32_t box2[3] = {64, 16, 1};
    encode_map(encode, &maps.mpf, d_in[5], 3, dim2, str2, box2, CU_TENSOR_MAP_SWIZZLE_NONE, CU_TENSOR_MAP_L2_PROMOTION_L2_256B);
  }
  {
    const cuuint64_t dim[5] = {32, 2, 512, 6, 256}, str[4] = {384, 512 * 384, 64, 768};
    const cuuint32_t box[5] = {32, 2, 4, 3, 2};
    encode_map(encode, &maps.out, d_out, 5, dim, str, box, CU_TENSOR_MAP_SWIZZLE_64B);
  }
  {
    const cuuint64_t dim[3] = {32, 192, 18}, str[2] = {576 * 2, 64};
    const cuuint32_t box[3] = {32, 192, 1};
    encode_map(encode, &maps.wqkv, d_in[1], 3, dim, str, box, CU_TENSOR_MAP_SWIZZLE_64B);
    const cuuint64_t dim2[3] = {32, 192, 6}, str2[2] = {192 * 2, 64};
    const cuuint32_t box2[3] = {32, 96, 3};
    encode_map(encode, &maps.wo, d_in[2], 3, dim2, str2, box2, CU_TENSOR_MAP_SWIZZLE_64B);
    const cuuint64_t dim3_[5] = {192, 2, 4, 4, 6}, str3[4] = {384, 8 * 384, 2 * 384, 32 * 384};
    const cuuint32_t box3[5] = {32, 2, 4, 4, 3};
    encode_map(encode, &maps.wop, d_in[2], 5, dim3_, str3, box3, CU_TENSOR_MAP_SWIZZLE_64B);
  }
  swin_attn_kernel<<<grid, 384, SMEM_BYTES>>>(maps, (const __nv_bfloat16*)d_in[3], (const int*)d_in[4], NWIN / (grid / 2) * (grid / 2), 0);
}
```

```cpp
#include <cuda_runtime.h>
#include <cuda_bf16.h>
#include <cuda.h>
#include <stdint.h>
#include <stdio.h>

namespace {

constexpr int NWIN = 4096;
constexpr int KV_WG = 0;
constexpr int Q_SPLIT = 4;
constexpr int EXP_CH = 4;

constexpr uint32_t SM_BASE  = 1024;
constexpr uint32_t OFF_WQ   = 0;
constexpr uint32_t OFF_WO   = 36864;
constexpr uint32_t STAGE    = 70656;
constexpr uint32_t OFF_X    = 73728;
constexpr uint32_t X_BYTES  = 24576;
constexpr uint32_t OFF_MASK = OFF_X + X_BYTES;
constexpr uint32_t M_BYTES  = 8192;
constexpr uint32_t OFF_KV   = OFF_MASK + M_BYTES;
constexpr uint32_t OFF_OIN  = OFF_KV + 25600;
constexpr uint32_t O_BYTES  = 12288;
constexpr uint32_t OFF_BAR  = 215040;
constexpr uint32_t OFF_RPB  = OFF_BAR + 1024;
constexpr uint32_t SMEM_BYTES = OFF_RPB + 1024;
constexpr uint32_t B_XFULL = 0, B_XEMPTY = 16, B_OFULL = 32, B_OEMPTY = 48, B_WKV = 64  , B_WQ = 88, B_WO = 96,
                   B_TICK = 104, B_M0 = 112, W_TICK = 120;
enum { T0 = 1, T1, T2, T3, T4, T5, T6, T7, BAR_BIAS, BAR_STAGE };

__device__ unsigned int g_ticket;

template <int V> struct IC { static constexpr int value = V; };
struct Maps { CUtensorMap x, mask, out, wqkv, wo, wop, xpf, mpf; };

__device__ __forceinline__ void mma_q_init(float (&d)[48], uint64_t descA, uint64_t descB) {
  asm volatile("wgmma.mma_async.sync.aligned.m64n96k16.f32.bf16.bf16 {%0, %1, %2, %3, %4, %5, %6, %7, %8, %9, %10, %11, %12, %13, %14, %15, %16, %17, %18, %19, %20, %21, %22, %23, %24, %25, %26, %27, %28, %29, %30, %31, %32, %33, %34, %35, %36, %37, %38, %39, %40, %41, %42, %43, %44, %45, %46, %47}, "
    "%48, %49, 0, 1, 1, 0, 1;"
    : "+f"(d[0]), "+f"(d[1]), "+f"(d[2]), "+f"(d[3]), "+f"(d[4]), "+f"(d[5]), "+f"(d[6]), "+f"(d[7]), "+f"(d[8]), "+f"(d[9]), "+f"(d[10]), "+f"(d[11]), "+f"(d[12]), "+f"(d[13]), "+f"(d[14]), "+f"(d[15]), "+f"(d[16]), "+f"(d[17]), "+f"(d[18]), "+f"(d[19]), "+f"(d[20]), "+f"(d[21]), "+f"(d[22]), "+f"(d[23]), "+f"(d[24]), "+f"(d[25]), "+f"(d[26]), "+f"(d[27]), "+f"(d[28]), "+f"(d[29]), "+f"(d[30]), "+f"(d[31]), "+f"(d[32]), "+f"(d[33]), "+f"(d[34]), "+f"(d[35]), "+f"(d[36]), "+f"(d[37]), "+f"(d[38]), "+f"(d[39]), "+f"(d[40]), "+f"(d[41]), "+f"(d[42]), "+f"(d[43]), "+f"(d[44]), "+f"(d[45]), "+f"(d[46]), "+f"(d[47])
    : "l"(descA), "l"(descB));
}
__device__ __forceinline__ void mma_q(float (&d)[48], uint64_t descA, uint64_t descB) {
  asm volatile("wgmma.mma_async.sync.aligned.m64n96k16.f32.bf16.bf16 {%0, %1, %2, %3, %4, %5, %6, %7, %8, %9, %10, %11, %12, %13, %14, %15, %16, %17, %18, %19, %20, %21, %22, %23, %24, %25, %26, %27, %28, %29, %30, %31, %32, %33, %34, %35, %36, %37, %38, %39, %40, %41, %42, %43, %44, %45, %46, %47}, "
    "%48, %49, 1, 1, 1, 0, 1;"
    : "+f"(d[0]), "+f"(d[1]), "+f"(d[2]), "+f"(d[3]), "+f"(d[4]), "+f"(d[5]), "+f"(d[6]), "+f"(d[7]), "+f"(d[8]), "+f"(d[9]), "+f"(d[10]), "+f"(d[11]), "+f"(d[12]), "+f"(d[13]), "+f"(d[14]), "+f"(d[15]), "+f"(d[16]), "+f"(d[17]), "+f"(d[18]), "+f"(d[19]), "+f"(d[20]), "+f"(d[21]), "+f"(d[22]), "+f"(d[23]), "+f"(d[24]), "+f"(d[25]), "+f"(d[26]), "+f"(d[27]), "+f"(d[28]), "+f"(d[29]), "+f"(d[30]), "+f"(d[31]), "+f"(d[32]), "+f"(d[33]), "+f"(d[34]), "+f"(d[35]), "+f"(d[36]), "+f"(d[37]), "+f"(d[38]), "+f"(d[39]), "+f"(d[40]), "+f"(d[41]), "+f"(d[42]), "+f"(d[43]), "+f"(d[44]), "+f"(d[45]), "+f"(d[46]), "+f"(d[47])
    : "l"(descA), "l"(descB));
}
__device__ __forceinline__ void mma_kv_init(float (&d)[32], uint32_t a0, uint32_t a1, uint32_t a2, uint32_t a3, uint64_t descB) {
  asm volatile("wgmma.mma_async.sync.aligned.m64n64k16.f32.bf16.bf16 {%0, %1, %2, %3, %4, %5, %6, %7, %8, %9, %10, %11, %12, %13, %14, %15, %16, %17, %18, %19, %20, %21, %22, %23, %24, %25, %26, %27, %28, %29, %30, %31}, "
    "{%32, %33, %34, %35}, %36, 0, 1, 1, 0;"
    : "+f"(d[0]), "+f"(d[1]), "+f"(d[2]), "+f"(d[3]), "+f"(d[4]), "+f"(d[5]), "+f"(d[6]), "+f"(d[7]), "+f"(d[8]), "+f"(d[9]), "+f"(d[10]), "+f"(d[11]), "+f"(d[12]), "+f"(d[13]), "+f"(d[14]), "+f"(d[15]), "+f"(d[16]), "+f"(d[17]), "+f"(d[18]), "+f"(d[19]), "+f"(d[20]), "+f"(d[21]), "+f"(d[22]), "+f"(d[23]), "+f"(d[24]), "+f"(d[25]), "+f"(d[26]), "+f"(d[27]), "+f"(d[28]), "+f"(d[29]), "+f"(d[30]), "+f"(d[31])
    : "r"(a0), "r"(a1), "r"(a2), "r"(a3), "l"(descB));
}
__device__ __forceinline__ void mma_kv(float (&d)[32], uint32_t a0, uint32_t a1, uint32_t a2, uint32_t a3, uint64_t descB) {
  asm volatile("wgmma.mma_async.sync.aligned.m64n64k16.f32.bf16.bf16 {%0, %1, %2, %3, %4, %5, %6, %7, %8, %9, %10, %11, %12, %13, %14, %15, %16, %17, %18, %19, %20, %21, %22, %23, %24, %25, %26, %27, %28, %29, %30, %31}, "
    "{%32, %33, %34, %35}, %36, 1, 1, 1, 0;"
    : "+f"(d[0]), "+f"(d[1]), "+f"(d[2]), "+f"(d[3]), "+f"(d[4]), "+f"(d[5]), "+f"(d[6]), "+f"(d[7]), "+f"(d[8]), "+f"(d[9]), "+f"(d[10]), "+f"(d[11]), "+f"(d[12]), "+f"(d[13]), "+f"(d[14]), "+f"(d[15]), "+f"(d[16]), "+f"(d[17]), "+f"(d[18]), "+f"(d[19]), "+f"(d[20]), "+f"(d[21]), "+f"(d[22]), "+f"(d[23]), "+f"(d[24]), "+f"(d[25]), "+f"(d[26]), "+f"(d[27]), "+f"(d[28]), "+f"(d[29]), "+f"(d[30]), "+f"(d[31])
    : "r"(a0), "r"(a1), "r"(a2), "r"(a3), "l"(descB));
}
__device__ __forceinline__ void mma_s(float (&d)[32], uint32_t a0, uint32_t a1, uint32_t a2, uint32_t a3, uint64_t descB) {
  asm volatile("wgmma.mma_async.sync.aligned.m64n64k16.f32.bf16.bf16 {%0, %1, %2, %3, %4, %5, %6, %7, %8, %9, %10, %11, %12, %13, %14, %15, %16, %17, %18, %19, %20, %21, %22, %23, %24, %25, %26, %27, %28, %29, %30, %31}, "
    "{%32, %33, %34, %35}, %36, 1, 1, 1, 1;"
    : "+f"(d[0]), "+f"(d[1]), "+f"(d[2]), "+f"(d[3]), "+f"(d[4]), "+f"(d[5]), "+f"(d[6]), "+f"(d[7]), "+f"(d[8]), "+f"(d[9]), "+f"(d[10]), "+f"(d[11]), "+f"(d[12]), "+f"(d[13]), "+f"(d[14]), "+f"(d[15]), "+f"(d[16]), "+f"(d[17]), "+f"(d[18]), "+f"(d[19]), "+f"(d[20]), "+f"(d[21]), "+f"(d[22]), "+f"(d[23]), "+f"(d[24]), "+f"(d[25]), "+f"(d[26]), "+f"(d[27]), "+f"(d[28]), "+f"(d[29]), "+f"(d[30]), "+f"(d[31])
    : "r"(a0), "r"(a1), "r"(a2), "r"(a3), "l"(descB));
}
__device__ __forceinline__ void mma_p_init(float (&d)[28], uint32_t a0, uint32_t a1, uint32_t a2, uint32_t a3, uint64_t descB) {
  asm volatile("wgmma.mma_async.sync.aligned.m64n56k16.f32.bf16.bf16 {%0, %1, %2, %3, %4, %5, %6, %7, %8, %9, %10, %11, %12, %13, %14, %15, %16, %17, %18, %19, %20, %21, %22, %23, %24, %25, %26, %27}, "
    "{%28, %29, %30, %31}, %32, 0, 1, 1, 0;"
    : "=f"(d[0]), "=f"(d[1]), "=f"(d[2]), "=f"(d[3]), "=f"(d[4]), "=f"(d[5]), "=f"(d[6]), "=f"(d[7]), "=f"(d[8]), "=f"(d[9]), "=f"(d[10]), "=f"(d[11]), "=f"(d[12]), "=f"(d[13]), "=f"(d[14]), "=f"(d[15]), "=f"(d[16]), "=f"(d[17]), "=f"(d[18]), "=f"(d[19]), "=f"(d[20]), "=f"(d[21]), "=f"(d[22]), "=f"(d[23]), "=f"(d[24]), "=f"(d[25]), "=f"(d[26]), "=f"(d[27])
    : "r"(a0), "r"(a1), "r"(a2), "r"(a3), "l"(descB));
}
__device__ __forceinline__ void mma_p(float (&d)[28], uint32_t a0, uint32_t a1, uint32_t a2, uint32_t a3, uint64_t descB) {
  asm volatile("wgmma.mma_async.sync.aligned.m64n56k16.f32.bf16.bf16 {%0, %1, %2, %3, %4, %5, %6, %7, %8, %9, %10, %11, %12, %13, %14, %15, %16, %17, %18, %19, %20, %21, %22, %23, %24, %25, %26, %27}, "
    "{%28, %29, %30, %31}, %32, 1, 1, 1, 0;"
    : "+f"(d[0]), "+f"(d[1]), "+f"(d[2]), "+f"(d[3]), "+f"(d[4]), "+f"(d[5]), "+f"(d[6]), "+f"(d[7]), "+f"(d[8]), "+f"(d[9]), "+f"(d[10]), "+f"(d[11]), "+f"(d[12]), "+f"(d[13]), "+f"(d[14]), "+f"(d[15]), "+f"(d[16]), "+f"(d[17]), "+f"(d[18]), "+f"(d[19]), "+f"(d[20]), "+f"(d[21]), "+f"(d[22]), "+f"(d[23]), "+f"(d[24]), "+f"(d[25]), "+f"(d[26]), "+f"(d[27])
    : "r"(a0), "r"(a1), "r"(a2), "r"(a3), "l"(descB));
}
__device__ __forceinline__ void mma_o_init(float (&d)[48], uint32_t a0, uint32_t a1, uint32_t a2, uint32_t a3, uint64_t descB) {
  asm volatile("wgmma.mma_async.sync.aligned.m64n96k16.f32.bf16.bf16 {%0, %1, %2, %3, %4, %5, %6, %7, %8, %9, %10, %11, %12, %13, %14, %15, %16, %17, %18, %19, %20, %21, %22, %23, %24, %25, %26, %27, %28, %29, %30, %31, %32, %33, %34, %35, %36, %37, %38, %39, %40, %41, %42, %43, %44, %45, %46, %47}, "
    "{%48, %49, %50, %51}, %52, 0, 1, 1, 1;"
    : "=f"(d[0]), "=f"(d[1]), "=f"(d[2]), "=f"(d[3]), "=f"(d[4]), "=f"(d[5]), "=f"(d[6]), "=f"(d[7]), "=f"(d[8]), "=f"(d[9]), "=f"(d[10]), "=f"(d[11]), "=f"(d[12]), "=f"(d[13]), "=f"(d[14]), "=f"(d[15]), "=f"(d[16]), "=f"(d[17]), "=f"(d[18]), "=f"(d[19]), "=f"(d[20]), "=f"(d[21]), "=f"(d[22]), "=f"(d[23]), "=f"(d[24]), "=f"(d[25]), "=f"(d[26]), "=f"(d[27]), "=f"(d[28]), "=f"(d[29]), "=f"(d[30]), "=f"(d[31]), "=f"(d[32]), "=f"(d[33]), "=f"(d[34]), "=f"(d[35]), "=f"(d[36]), "=f"(d[37]), "=f"(d[38]), "=f"(d[39]), "=f"(d[40]), "=f"(d[41]), "=f"(d[42]), "=f"(d[43]), "=f"(d[44]), "=f"(d[45]), "=f"(d[46]), "=f"(d[47])
    : "r"(a0), "r"(a1), "r"(a2), "r"(a3), "l"(descB));
}
__device__ __forceinline__ void mma_o(float (&d)[48], uint32_t a0, uint32_t a1, uint32_t a2, uint32_t a3, uint64_t descB) {
  asm volatile("wgmma.mma_async.sync.aligned.m64n96k16.f32.bf16.bf16 {%0, %1, %2, %3, %4, %5, %6, %7, %8, %9, %10, %11, %12, %13, %14, %15, %16, %17, %18, %19, %20, %21, %22, %23, %24, %25, %26, %27, %28, %29, %30, %31, %32, %33, %34, %35, %36, %37, %38, %39, %40, %41, %42, %43, %44, %45, %46, %47}, "
    "{%48, %49, %50, %51}, %52, 1, 1, 1, 1;"
    : "+f"(d[0]), "+f"(d[1]), "+f"(d[2]), "+f"(d[3]), "+f"(d[4]), "+f"(d[5]), "+f"(d[6]), "+f"(d[7]), "+f"(d[8]), "+f"(d[9]), "+f"(d[10]), "+f"(d[11]), "+f"(d[12]), "+f"(d[13]), "+f"(d[14]), "+f"(d[15]), "+f"(d[16]), "+f"(d[17]), "+f"(d[18]), "+f"(d[19]), "+f"(d[20]), "+f"(d[21]), "+f"(d[22]), "+f"(d[23]), "+f"(d[24]), "+f"(d[25]), "+f"(d[26]), "+f"(d[27]), "+f"(d[28]), "+f"(d[29]), "+f"(d[30]), "+f"(d[31]), "+f"(d[32]), "+f"(d[33]), "+f"(d[34]), "+f"(d[35]), "+f"(d[36]), "+f"(d[37]), "+f"(d[38]), "+f"(d[39]), "+f"(d[40]), "+f"(d[41]), "+f"(d[42]), "+f"(d[43]), "+f"(d[44]), "+f"(d[45]), "+f"(d[46]), "+f"(d[47])
    : "r"(a0), "r"(a1), "r"(a2), "r"(a3), "l"(descB));
}

__device__ __forceinline__ void wg_fence() { asm volatile("wgmma.fence.sync.aligned;" ::: "memory"); }
__device__ __forceinline__ void wg_commit() { asm volatile("wgmma.commit_group.sync.aligned;" ::: "memory"); }
template <int N> __device__ __forceinline__ void wg_wait() { asm volatile("wgmma.wait_group.sync.aligned %0;" ::"n"(N) : "memory"); }
template <int N> __device__ __forceinline__ void pin(float (&d)[N]) {
#pragma unroll
  for (int i = 0; i < N; i++) asm volatile("" : "+f"(d[i])::"memory");
}
template <int N> __device__ __forceinline__ void pin(uint32_t (&d)[N]) {
#pragma unroll
  for (int i = 0; i < N; i++) asm volatile("" : "+r"(d[i])::"memory");
}
__device__ __forceinline__ uint64_t mkdesc(uint32_t lo, uint32_t hi) { return ((uint64_t)hi << 32) | lo; }
constexpr uint64_t EVICT_FIRST = 0x12F0000000000000ull;
constexpr uint32_t HI_X = (3072 >> 4) | (1u << 30);
constexpr uint32_t HI_KV = (1024 >> 4) | (1u << 30);
constexpr uint32_t HI_W = (512 >> 4) | (2u << 30);
constexpr uint32_t HI_O = (1536 >> 4) | (2u << 30);
constexpr uint32_t LO_O = (1u << 16) + ((SM_BASE + OFF_OIN) >> 4);
constexpr uint32_t LO_WQ = ((12288 >> 4) << 16) + ((SM_BASE + OFF_WQ) >> 4);
constexpr uint32_t LO_WO = ((6144 >> 4) << 16) + ((SM_BASE + OFF_WO) >> 4);
constexpr uint32_t LO_X = (1u << 16) + ((SM_BASE + OFF_X) >> 4);
constexpr uint32_t LO_KV = (1u << 16) + ((SM_BASE + OFF_KV) >> 4);

__device__ __forceinline__ uint32_t pack_bf16(float lo, float hi) {
  uint32_t r;
  asm("cvt.rn.bf16x2.f32 %0, %1, %2;" : "=r"(r) : "f"(hi), "f"(lo));
  return r;
}
__device__ __forceinline__ float ex2(float x) {
  float r;
  asm("ex2.approx.ftz.f32 %0, %1;" : "=f"(r) : "f"(x));
  return r;
}
__device__ __forceinline__ float rcp(float x) {
  float r;
  asm("rcp.approx.ftz.f32 %0, %1;" : "=f"(r) : "f"(x));
  return r;
}
__device__ __forceinline__ bool elect() {
  uint32_t p;
  asm volatile("{\n.reg .pred P;\nelect.sync _|P, 0xffffffff;\nselp.u32 %0, 1, 0, P;\n}" : "=r"(p));
  return p;
}
__device__ __forceinline__ void mbar_init(uint32_t bar, uint32_t cnt) {
  asm volatile("mbarrier.init.shared::cta.b64 [%0], %1;" ::"r"(bar), "r"(cnt) : "memory");
}
__device__ __forceinline__ void mbar_wait(uint32_t bar, uint32_t parity) {
  asm volatile(
      "{\n.reg .pred p;\n.reg .u32 n;\n"
      "mbarrier.try_wait.parity.shared::cta.b64 p, [%0], %1;\n"
      "@p bra DONE;\n"
      "mov.u32 n, 0;\n"
      "LOOP:\n"
      "mbarrier.try_wait.parity.shared::cta.b64 p, [%0], %1;\n"
      "@p bra DONE;\n"
      "add.u32 n, n, 1;\n"
      "setp.lt.u32 p, n, 0x400000;\n"
      "@p bra LOOP;\n"
      "trap;\n"
      "DONE:\n}\n" ::"r"(bar), "r"(parity)
      : "memory");
}
__device__ __forceinline__ void mbar_arrive_cluster(uint32_t bar) {
  asm volatile("mbarrier.arrive.shared::cluster.b64 _, [%0];" ::"r"(bar) : "memory");
}
__device__ __forceinline__ void mbar_expect_tx(uint32_t bar, uint32_t bytes) {
  asm volatile("mbarrier.arrive.expect_tx.shared::cta.b64 _, [%0], %1;" ::"r"(bar), "r"(bytes) : "memory");
}
__device__ __forceinline__ uint32_t mapa(uint32_t addr, uint32_t rank) {
  uint32_t r;
  asm("mapa.shared::cluster.u32 %0, %1, %2;" : "=r"(r) : "r"(addr), "r"(rank));
  return r;
}
__device__ __forceinline__ void sched_fence(uint32_t& keep, int never) {
  asm volatile("{\n.reg .pred p;\nsetp.ne.s32 p, %1, 0;\n@p mov.u32 %0, %clock;\n}" : "+r"(keep) : "r"(never) : "memory");
}
template <int ID> __device__ __forceinline__ void tok_wait() { asm volatile("bar.sync %0, %1;" ::"n"(ID), "n"(ID == T7 ? 384 : 256) : "memory"); }
template <int ID> __device__ __forceinline__ void tok_pass() { asm volatile("bar.arrive %0, %1;" ::"n"(ID), "n"(ID == T7 ? 384 : 256) : "memory"); }
__device__ __forceinline__ void fence_async() { asm volatile("fence.proxy.async.shared::cta;" ::: "memory"); }
__device__ __forceinline__ void stsm4(uint32_t addr, uint32_t r0, uint32_t r1, uint32_t r2, uint32_t r3) {
  asm volatile("stmatrix.sync.aligned.m8n8.x4.shared.b16 [%0], {%1,%2,%3,%4};" ::"r"(addr), "r"(r0), "r"(r1), "r"(r2), "r"(r3) : "memory");
}
__device__ __forceinline__ void lds128(uint32_t addr, uint32_t& r0, uint32_t& r1, uint32_t& r2, uint32_t& r3) {
  asm volatile("ld.shared.v4.b32 {%0,%1,%2,%3}, [%4];" : "=r"(r0), "=r"(r1), "=r"(r2), "=r"(r3) : "r"(addr) : "memory");
}
template <int OFF>
__device__ __forceinline__ void st_async(uint32_t addr, uint32_t bar, uint32_t r0, uint32_t r1, uint32_t r2, uint32_t r3) {
  asm volatile("st.async.shared::cluster.mbarrier::complete_tx::bytes.v4.b32 [%0+%6], {%1,%2,%3,%4}, [%5];" ::"r"(addr), "r"(r0),
               "r"(r1), "r"(r2), "r"(r3), "r"(bar), "n"(OFF)
               : "memory");
}
__device__ __forceinline__ void tma5_mc(uint32_t dst, const CUtensorMap* tm, uint32_t bar, int c2, int c4) {
  asm volatile(
      "cp.async.bulk.tensor.5d.shared::cluster.global.mbarrier::complete_tx::bytes.multicast::cluster.L2::cache_hint "
      "[%0], [%1, {0, 0, %3, 0, %4}], [%2], %5, %6;" ::"r"(dst), "l"(tm), "r"(bar), "r"(c2), "r"(c4), "h"((uint16_t)3), "l"(EVICT_FIRST)
      : "memory");
}
__device__ __forceinline__ void tma3_pf(const CUtensorMap* tm, int c1, int c2) {
  asm volatile("cp.async.bulk.prefetch.tensor.3d.L2.global [%0, {0, %1, %2}];" ::"l"(tm), "r"(c1), "r"(c2) : "memory");
}
__device__ __forceinline__ void tma3(uint32_t dst, const CUtensorMap* tm, uint32_t bar, int c1, int c2) {
  asm volatile("cp.async.bulk.tensor.3d.shared::cluster.global.mbarrier::complete_tx::bytes [%0], [%1, {0, %3, %4}], [%2];" ::"r"(dst),
               "l"(tm), "r"(bar), "r"(c1), "r"(c2)
               : "memory");
}

constexpr float SQRT_HD = 6.92820323027551f;
constexpr float SM_C = 1.4426950408889634f / SQRT_HD;

__device__ __forceinline__ void s_init(float (&s)[32], const uint32_t (&mk)[16], const uint32_t (&b)[16]) {
#pragma unroll
  for (int i = 0; i < 16; i++) {
    const int o = 4 * (i & 7) + 2 * (i >> 3);
    uint32_t t0, t1;
    asm("{\n.reg .b16 ml, mh, bl, bh;\n.reg .b32 m2, b2;\n"
        "mov.b32 {ml, mh}, %1;\nmov.b32 {bl, bh}, %3;\nmov.b32 m2, {ml, ml};\nmov.b32 b2, {bl, bl};\n"
        "fma.rn.bf16x2 %0, m2, %2, b2;\n}"
        : "=r"(t0)
        : "r"(mk[i]), "r"(0x40DE40DEu), "r"(b[i]));
    asm("fma.rn.bf16x2 %0, %1, %2, %3;" : "=r"(t1) : "r"(mk[i]), "r"(0x40DE40DEu), "r"(b[i]));
    s[o] = __uint_as_float(t0);
    s[o + 1] = __uint_as_float(t1);
    asm volatile("" : "+f"(s[o]), "+f"(s[o + 1])::"memory");
  }
}
__device__ __forceinline__ uint32_t pack_bias(float lo, float hi) {
  uint32_t l = __float_as_uint(fmaf(lo, SQRT_HD, 0x1p-100f)), h = __float_as_uint(fmaf(hi, SQRT_HD, 0x1p-100f));
  l = (l - (l >> 16) + 0x8000u) >> 16;
  return ((h - l + 0x8000u) & 0xffff0000u) | l;
}
template <bool NEG>
__device__ __forceinline__ int pick3(int a, int b, int c) { return NEG ? (int)__vimin3_u32(a, b, c) : __vimax3_s32(a, b, c); }
template <bool NEG>
__device__ __forceinline__ int pick2(int a, int b) { return NEG ? (int)min((unsigned)a, (unsigned)b) : max(a, b); }
template <bool NEG>
__device__ __forceinline__ void row_pick(const float (&s)[32], int& i0, int& i1) {
#define FI(x) __float_as_int(x)
  i0 = pick2<NEG>(FI(s[0]), FI(s[1])), i1 = pick2<NEG>(FI(s[2]), FI(s[3]));
  int k0 = pick3<NEG>(FI(s[4]), FI(s[5]), FI(s[8])), k1 = pick3<NEG>(FI(s[6]), FI(s[7]), FI(s[10]));
  i0 = pick3<NEG>(i0, FI(s[9]), FI(s[12]));   i1 = pick3<NEG>(i1, FI(s[11]), FI(s[14]));
  k0 = pick3<NEG>(k0, FI(s[13]), FI(s[16]));  k1 = pick3<NEG>(k1, FI(s[15]), FI(s[18]));
  i0 = pick3<NEG>(i0, FI(s[17]), FI(s[20]));  i1 = pick3<NEG>(i1, FI(s[19]), FI(s[22]));
  k0 = pick3<NEG>(k0, FI(s[21]), FI(s[24]));  k1 = pick3<NEG>(k1, FI(s[23]), FI(s[26]));
  i0 = pick3<NEG>(i0, FI(s[25]), FI(s[28]));  i1 = pick3<NEG>(i1, FI(s[27]), FI(s[30]));
  i0 = pick3<NEG>(i0, k0, FI(s[29]));         i1 = pick3<NEG>(i1, k1, FI(s[31]));
#undef FI
}
template <bool NEG>
__device__ __forceinline__ void quad_pick(int& i0, int& i1, int x) {
  i0 = pick2<NEG>(i0, __shfl_xor_sync(0xffffffffu, i0, x));
  i1 = pick2<NEG>(i1, __shfl_xor_sync(0xffffffffu, i1, x));
}
__device__ __forceinline__ void fix_negative_rows(const float (&s)[32], int& i0, int& i1) {
  int n0, n1;
  row_pick<true>(s, n0, n1);
  quad_pick<true>(n0, n1, 1);
  quad_pick<true>(n0, n1, 2);
  if (i0 < 0) i0 = n0;
  if (i1 < 0) i1 = n1;
}
template <int CH>
__device__ __forceinline__ void exp_rows(const float (&s)[32], uint32_t (&p)[16], int max0, int max1, uint32_t& keep, int never) {
  const float m0 = __int_as_float(max0) * -SM_C, m1 = __int_as_float(max1) * -SM_C;
  float t[32];
#pragma unroll
  for (int c = 0; c <= 16 / CH; c++) {
#pragma unroll
    for (int i = 2 * CH * c; i < 2 * CH * (c + 1) && i < 32; i++) {
      t[i] = fmaf(s[i], SM_C, (i & 2) ? m1 : m0);
      asm volatile("" : "+f"(t[i]));
    }
    if (c > 0) {
#pragma unroll
      for (int i = CH * (c - 1); i < CH * c; i++) {
        t[2 * i] = ex2(t[2 * i]), t[2 * i + 1] = ex2(t[2 * i + 1]);
        asm volatile("" : "+f"(t[2 * i]), "+f"(t[2 * i + 1]));
      }
    }
    if (c > 1) {
#pragma unroll
      for (int i = CH * (c - 2); i < CH * (c - 1); i++) {
        p[i] = pack_bf16(t[2 * i], t[2 * i + 1]);
        asm volatile("" : "+r"(p[i]));
      }
    }
    if (c < 16 / CH) sched_fence(keep, never);
  }
#pragma unroll
  for (int i = 16 - CH; i < 16; i++) p[i] = pack_bf16(t[2 * i], t[2 * i + 1]);
  pin(p);
}
__device__ __forceinline__ void issue_p(float (&o)[28], const uint32_t (&p)[16], uint32_t lo) {
#pragma unroll
  for (int ks = 0; ks < 4; ks++) {
    uint64_t db = mkdesc(lo + ks * 2, HI_KV);
    if (ks == 0) mma_p_init(o, p[0], p[1], p[2], p[3], db);
    else mma_p(o, p[4 * ks], p[4 * ks + 1], p[4 * ks + 2], p[4 * ks + 3], db);
  }
  wg_commit();
}
template <int SUM, int OFF>
__device__ __forceinline__ void normalize(const float (&o)[28], uint32_t (&f)[12]) {
  const float r0 = rcp(o[SUM]), r1 = rcp(o[SUM + 2]);
  uint32_t h0 = pack_bf16(r0, r0), h1 = pack_bf16(r1, r1);
#pragma unroll
  for (int j = 0; j < 12; j++)
    asm("mul.rn.bf16x2 %0, %1, %2;" : "=r"(f[j]) : "r"(pack_bf16(o[OFF + 2 * j], o[OFF + 2 * j + 1])), "r"((j & 1) ? h1 : h0));
}

__global__ void __cluster_dims__(2, 1, 1) __launch_bounds__(384, 1)
swin_attn_kernel(const __grid_constant__ Maps maps, const __nv_bfloat16* __restrict__ rpb, const int* __restrict__ rp_idx, int base, int never) {
  extern __shared__ __align__(1024) uint8_t smem_raw[];
  const uint32_t sb = (uint32_t)__cvta_generic_to_shared(smem_raw);
  const int tid = threadIdx.x;
  const int wg = __shfl_sync(0xffffffffu, tid >> 7, 0);
  const int warp = __shfl_sync(0xffffffffu, (tid >> 5) & 3, 0);
  const int lane = tid & 31;
  const int rank = blockIdx.x & 1;
  const int cl = blockIdx.x >> 1;
  const int ncl = gridDim.x >> 1;
  const uint32_t bars = sb + OFF_BAR;
  int extra = NWIN;
  auto read_ticket = [&]() {
    mbar_wait(bars + B_TICK, 0);
    uint32_t t;
    asm volatile("ld.shared.b32 %0, [%1];" : "=r"(t) : "r"(bars + W_TICK) : "memory");
    extra = base + __shfl_sync(0xffffffffu, t, 0);
  };
  auto window = [&](int v) { return v < base ? v : (v < base + ncl ? extra : NWIN); };
  auto prefetch = [&](int p, int win) {
    if (p < 2) tma3_pf(&maps.xpf, ((win * 2 + 1 + p) & 127) * 6, (((win >> 3) & ~7) + 4 + 4 * rank) & 511);
    else tma3_pf(&maps.mpf, 0, 2 * win + rank);
  };
  auto load = [&](int p, int win, int a) {
    if (p < 2)
      tma5_mc(sb + OFF_X + a * STAGE + rank * 12288 + p * 6144, &maps.x, bars + B_XFULL + 8 * a,
              (((win >> 3) & ~7) + 4 + 4 * rank) & 511, (win * 4 + 2 + 2 * p) & 255);
    else tma5_mc(sb + OFF_MASK + a * STAGE + rank * 4096, &maps.mask, bars + B_XFULL + 8 * a, 0, 2 * win + rank);
  };
  auto load_wkv = [&](int b) {
    tma3(sb + OFF_KV + (b < 3 ? b * 12288 : STAGE + (b - 3) * 12288), &maps.wqkv, bars + B_WKV + 8 * (b >> 1), 0,
         (b < 3 ? 6 : 9) + b + 3 * rank);
  };
  auto startup_loads = [&]() {
    if ((sb & 0x3FFFF) != SM_BASE) __trap();
    if (blockIdx.x == 0) asm volatile("st.relaxed.gpu.global.u32 [%0], 0;" ::"l"(&g_ticket) : "memory");
    mbar_expect_tx(bars + B_XFULL, X_BYTES);
    mbar_expect_tx(bars + B_M0, M_BYTES);
    mbar_expect_tx(bars + B_WKV + 8, 24576);
    load_wkv(2);
    load_wkv(3);
    tma5_mc(sb + OFF_MASK + rank * 4096, &maps.mask, bars + B_M0, 0, 2 * cl + rank);
    mbar_expect_tx(bars + B_WQ, 36864);
    for (int nb = 0; nb < 3; nb++) tma3(sb + OFF_WQ + nb * 12288, &maps.wqkv, bars + B_WQ, 0, 3 * rank + nb);
    mbar_expect_tx(bars + B_WKV + 16, 24576);
    load_wkv(4);
    load_wkv(5);
    mbar_expect_tx(bars + B_XFULL + 8, X_BYTES + M_BYTES);
    for (int p = 0; p < 3; p++) load(p, cl + ncl, 1);
    mbar_expect_tx(bars + B_TICK, 4);
    mbar_expect_tx(bars + B_WO, 36864);
    tma3(sb + OFF_WO, &maps.wo, bars + B_WO, 96 * rank, 3 * rank);
    for (int nb = 0; nb < 3; nb++)
      asm volatile("cp.async.bulk.tensor.5d.shared::cluster.global.mbarrier::complete_tx::bytes [%0], [%1, {%3, 0, 0, 0, %4}], [%2];" ::"r"(
                       sb + OFF_WO + 18432 + nb * 6144), "l"(&maps.wop), "r"(bars + B_WO), "r"(96 * rank + 32 * nb), "r"(3 * (rank ^ 1))
                   : "memory");
  };
  if (wg == KV_WG && warp == 3) {
    if (elect()) {
#pragma unroll
      for (int k = 0; k < 15; k++) mbar_init(bars + 8 * k, (k >> 1) == B_OEMPTY / 16 ? 4 : 1);
      asm volatile("fence.mbarrier_init.release.cluster;" ::: "memory");
    }
    __syncwarp();
  }
  asm volatile("barrier.cluster.arrive.relaxed.aligned;" ::: "memory");

  if (wg == KV_WG) {
    if (warp == 3 && elect()) {
      fence_async();
      mbar_expect_tx(bars + B_WKV, 24576);
      load_wkv(0);
      load_wkv(1);
    }
    __syncwarp();
    asm volatile("barrier.cluster.wait.aligned;" ::: "memory");
    if (elect()) {
      if (warp < 2) load(warp, cl, 0);
      else if (warp == 3) startup_loads();
    }
    __syncwarp();
    asm volatile("setmaxnreg.inc.sync.aligned.u32 216;");
    uint32_t w[3][48];
    auto load_frags = [&](int s) {
      const uint32_t la = sb + OFF_KV + (warp >> 1) * 12288 + (8 * (lane >> 4) + (lane & 7)) * 64 +
                          (((2 * (warp & 1) + ((lane >> 3) & 1)) ^ ((lane & 7) >> 1)) << 4);
      mbar_wait(bars + B_WKV + 8 * s, 0);
#pragma unroll
      for (int ks = 0; ks < 12; ks++)
        asm volatile("ldmatrix.sync.aligned.m8n8.x4.trans.shared.b16 {%0,%1,%2,%3}, [%4];"
                     : "=r"(w[s][4 * ks]), "=r"(w[s][4 * ks + 1]), "=r"(w[s][4 * ks + 2]), "=r"(w[s][4 * ks + 3])
                     : "r"(la + s * 24576 + (s == 2 || (s == 1 && warp >= 2) ? STAGE - 36864 : 0) + ks * 1024)
                     : "memory");
    };
    load_frags(0);
    uint32_t sta[4];
#pragma unroll
    for (int jj = 0; jj < 4; jj++) {
      sta[jj] = sb + OFF_KV + (16 * warp + (lane & 15)) * 128 + (((2 * jj + (lane >> 4)) ^ (lane & 7)) << 4);
      asm volatile("" : "+r"(sta[jj]));
    }
    const uint32_t xe_rem = mapa(bars + B_XEMPTY, rank ^ 1);
    const uint32_t v1off = warp > 0 ? 1024 : 0;

#define SF sched_fence(sta[0], never)
    float acc[32];
    uint32_t pk[16];
    auto store = [&](uint32_t off) {
#pragma unroll
      for (int jj = 0; jj < 4; jj++) stsm4(sta[jj] + off, pk[4 * jj], pk[4 * jj + 1], pk[4 * jj + 2], pk[4 * jj + 3]);
    };
    auto issue = [&](int s, uint32_t xd, bool st, uint32_t off) {
#pragma unroll
      for (int ks = 0; ks < 12; ks++) {
        uint64_t db = mkdesc(xd + (((ks >> 2) * 1024 + (ks & 3) * 32) >> 4), HI_X);
        if (ks == 0) mma_kv_init(acc, w[s][0], w[s][1], w[s][2], w[s][3], db);
        else mma_kv(acc, w[s][4 * ks], w[s][4 * ks + 1], w[s][4 * ks + 2], w[s][4 * ks + 3], db);
        if (ks == 1 && st) {
          __syncwarp();
          store(off);
          __syncwarp();
        }
      }
      wg_commit();
    };
    auto convert = [&]() {
      wg_wait<0>();
      pin(acc);
#pragma unroll
      for (int j = 0; j < 16; j++) pk[j] = pack_bf16(acc[2 * j], acc[2 * j + 1]);
      pin(pk);
    };

    mbar_wait(bars + B_XFULL, 0);
    wg_fence();
    issue(0, LO_X, false, 0);
    load_frags(1);
    int nxt = cl + ncl;
    uint32_t ph = 0;
    uint32_t ticket = 0;
    auto step = [&](auto A) -> bool {
      constexpr int a = decltype(A)::value;
      constexpr uint32_t xd = LO_X + a * (STAGE >> 4);
      if (nxt + ncl >= base && nxt < base) read_ticket();
      const bool more = window(nxt) < NWIN;
      const int wn2 = window(nxt + ncl);
      convert();
      wg_fence();
      SF;
      tok_wait<T2>();
      issue(1, xd, true, a * STAGE);
      tok_pass<T3>();
      if (warp < 3 && wn2 < NWIN && elect()) prefetch(warp, wn2);
      __syncwarp();
      const bool first = a == 0 && nxt == cl + ncl;
      convert();
      SF;
      if (!first) tok_wait<T7>();
      store(a * STAGE + 8192);
      fence_async();
      if (first) {
        load_frags(2);
        asm volatile("bar.sync %0, 128;" ::"n"((int)BAR_STAGE) : "memory");
        asm volatile("st.shared.v4.b32 [%0], {%1,%1,%1,%1};" ::"r"(sb + OFF_KV + (warp >> 1) * STAGE + 144 * 128 + (tid & 63) * 16), "r"(0x3F803F80u) : "memory");
      }
      wg_fence();
      tok_wait<T5>();
      issue(2, xd, false, 0);
      tok_pass<T6>();
      if (!more) {
        convert();
        store(a * STAGE + 16384 + v1off);
        fence_async();
        return false;
      }
      mbar_wait(bars + B_XFULL + 8 * (a ^ 1), a ? ph ^ 1 : ph);
      convert();
      wg_fence();
      SF;
      tok_wait<T0>();
      if (tid == KV_WG * 128 && wn2 < NWIN) mbar_arrive_cluster(xe_rem + 8 * a);
      issue(0, LO_X + (a ^ 1) * (STAGE >> 4), true, a * STAGE + 16384 + v1off);
      tok_pass<T1>();
      fence_async();
      nxt += ncl;
      if (wn2 < NWIN) {
        mbar_wait(bars + B_XEMPTY + 8 * a, ph);
        if (elect()) {
          if (warp < 3) {
            load(warp, wn2, a);
          } else {
            mbar_expect_tx(bars + B_XFULL + 8 * a, X_BYTES + M_BYTES);
            if (rank == 0 && nxt + 3 * ncl >= base) {
              if (nxt + 2 * ncl < base) {
                asm volatile("atom.global.inc.u32 %0, [%1], %2;" : "=r"(ticket) : "l"(&g_ticket), "r"(ncl - 1) : "memory");
              } else if (nxt + ncl < base) {
#pragma unroll
                for (int r = 0; r < 2; r++)
                  asm volatile("st.async.shared::cluster.mbarrier::complete_tx::bytes.b32 [%0], %1, [%2];" ::"r"(mapa(bars + W_TICK, r)),
                               "r"(ticket), "r"(mapa(bars + B_TICK, r))
                               : "memory");
              }
            }
          }
        }
        __syncwarp();
      }
      return true;
    };
    while (step(IC<0>{}) && step(IC<1>{})) ph ^= 1;
    tok_wait<T0>();
    tok_pass<T1>();
    tok_wait<T2>();
    tok_pass<T3>();
    tok_wait<T7>();
    tok_wait<T5>();
  } else {
    const int a = wg - (KV_WG == 0 ? 1 : 0);
    const int g = lane >> 2, q = lane & 3;
    const uint32_t bar = bars + 8 * a;
    if (a == 0) {
      tok_pass<T2>();
      tok_pass<T5>();
    }
    asm volatile("setmaxnreg.dec.sync.aligned.u32 144;");
    uint32_t braw[32];
    {
      const int ty = 4 * (warp >> 1) + (g >> 1), tx = 4 * (warp & 1) + (g & 1);
      const int* ip = rp_idx + (ty * 8 + tx) * 64 + 8 * q;
#pragma unroll
      for (int c = 0; c < 8; c++)
        asm volatile("ld.global.nc.v4.b32 {%0,%1,%2,%3}, [%4];"
                     : "=r"(braw[4 * c]), "=r"(braw[4 * c + 1]), "=r"(braw[4 * c + 2]), "=r"(braw[4 * c + 3])
                     : "l"(ip + (c >> 2) * 128 + ((c >> 1) & 1) * 32 + (c & 1) * 4));
      const int e = a * 128 + (tid & 127);
      uint32_t v = 0;
      if (e < 225) asm volatile("ld.global.nc.b32 %0, [%1];" : "=r"(v) : "l"(reinterpret_cast<const uint32_t*>(rpb) + e * 2 + rank));
      asm volatile("st.shared.b32 [%0], %1;" ::"r"(sb + OFF_RPB + e * 4), "r"(v) : "memory");
      tok_wait<BAR_BIAS>();
#pragma unroll
      for (int j = 0; j < 32; j++)
        asm volatile("ld.shared.b32 %0, [%1];" : "=r"(braw[j]) : "r"(sb + OFF_RPB + braw[j] * 4) : "memory");
    }
    asm volatile("barrier.cluster.wait.aligned;" ::: "memory");

    const int mrow = 16 * warp + (g >> 1) + 4 * (g & 1);
#undef SF
#define SF sched_fence(mk_addr, never)
    uint32_t mk_addr = sb + OFF_MASK + a * STAGE + mrow * 128 + ((q ^ (mrow & 7)) << 4);
    const uint32_t ostage = sb + OFF_OIN + a * STAGE + warp * 3072;
    const uint32_t ost = ostage + ((lane >> 3) & 1) * 1536 + (lane & 7) * 64 + (((lane >> 4) ^ ((lane & 7) >> 1)) << 4);
    const uint32_t oin_rem = mapa(ostage + g * 64 + ((q ^ (g >> 1)) << 4), rank ^ 1);
    const uint32_t bar_rem = mapa(bar, rank ^ 1);

    auto store_out = [&](int win) {
      fence_async();
      __syncwarp();
      if (elect()) {
        int yy = (((win >> 3) & ~7) + 4 + 4 * (warp >> 1)) & 511;
        int xh = (win * 4 + 2 + 2 * (warp & 1)) & 255;
        asm volatile("cp.async.bulk.tensor.5d.global.shared::cta.bulk_group [%0, {0, 0, %2, %3, %4}], [%1];" ::"l"(&maps.out), "r"(ostage),
                     "r"(yy), "r"(3 * rank), "r"(xh)
                     : "memory");
        asm volatile("cp.async.bulk.commit_group;" ::: "memory");
      }
      __syncwarp();
    };
    auto release_oin = [&]() {
      if (elect()) {
        asm volatile("cp.async.bulk.wait_group.read 0;" ::: "memory");
        if (warp == 0) mbar_expect_tx(bar + B_OFULL, O_BYTES);
        mbar_arrive_cluster(bar_rem + B_OEMPTY);
      }
      __syncwarp();
    };
    float qa[48];
    uint32_t bias0[16], bias1[16];
    uint32_t mk[16];
    auto load_mask = [&](uint32_t z) {
#pragma unroll
      for (int c = 0; c < 4; c++)
        lds128((c & 1 ? mk_addr ^ (64 + z) : mk_addr) + (c >> 1) * 1024, mk[4 * c], mk[4 * c + 1], mk[4 * c + 2], mk[4 * c + 3]);
    };
    auto clamp_mask = [&]() {
      SF;
#pragma unroll
      for (int j = 0; j < 16; j++) asm("max.NaN.bf16x2 %0, %0, %1;" : "+r"(mk[j]) : "r"(0xFD80FD80u));
      pin(mk);
    };
    auto issue_q = [&](uint32_t ua, bool tok, int win) {
      uint64_t xd = mkdesc(ua + LO_X, HI_X), wd = mkdesc(LO_WQ + (win >> 20), HI_W);
      asm volatile("" : "+l"(xd));
      asm volatile("" : "+l"(wd));
#pragma unroll
      for (int ks = 0; ks < 12; ks++) {
        if (ks == Q_SPLIT && tok) {
          tok_pass<T4>();
          store_out(win);
          tok_wait<T7>();
          wg_fence();
        }
        const uint64_t da = xd + (((ks >> 2) * 1024 + (ks & 3) * 32) >> 4), db = wd + ks * 64;
        if (ks == 0) mma_q_init(qa, da, db);
        else mma_q(qa, da, db);
      }
      wg_commit();
      if (tok) tok_pass<T5>();
    };
#pragma unroll
    for (int j = 0; j < 16; j++) {
      const uint32_t b0 = braw[2 * j], b1 = braw[2 * j + 1];
      bias0[j] = pack_bias(__uint_as_float(b0 << 16), __uint_as_float(b1 << 16));
      bias1[j] = pack_bias(__uint_as_float(b0 & 0xffff0000u), __uint_as_float(b1 & 0xffff0000u));
    }
    pin(bias0);
    pin(bias1);
    SF;
    mbar_wait(bars + B_WQ, 0);
    wg_fence();
    if (a == 0) tok_wait<T3>();
    else tok_wait<T1>();
    issue_q(a * (STAGE >> 4), false, 0);
    if (a == 0) mbar_wait(bars + B_M0, 0);
    else tok_pass<T2>();
    load_mask(0);
    if (a == 1) {
      tok_wait<T3>();
      tok_pass<T4>();
      tok_pass<T5>();
      tok_wait<T7>();
    }
    clamp_mask();
    uint32_t ph = 0;
    int win = cl + a * ncl;
    for (;; win += 2 * ncl, ph ^= 1) {
      const uint32_t ua = a * (STAGE >> 4) + (win >> 20);
      const uint32_t kd = ua + LO_KV;
      float s0[32], s1[32];
      wg_wait<0>();
      pin(qa);
      uint32_t q0[12], q1[12];
#pragma unroll
      for (int j = 0; j < 12; j++) q0[j] = pack_bf16(qa[2 * j], qa[2 * j + 1]);
#pragma unroll
      for (int j = 0; j < 12; j++) q1[j] = pack_bf16(qa[24 + 2 * j], qa[25 + 2 * j]);
      pin(q0);
      pin(q1);
      s_init(s0, mk, bias0);
      s_init(s1, mk, bias1);
      wg_fence();
      tok_wait<T6>();
#pragma unroll
      for (int ks = 0; ks < 3; ks++)
        mma_s(s0, q0[4 * ks], q0[4 * ks + 1], q0[4 * ks + 2], q0[4 * ks + 3], mkdesc(kd + ks * 128, HI_KV));
      wg_commit();
#pragma unroll
      for (int ks = 0; ks < 3; ks++)
        mma_s(s1, q1[4 * ks], q1[4 * ks + 1], q1[4 * ks + 2], q1[4 * ks + 3], mkdesc(kd + (3 + ks) * 128, HI_KV));
      wg_commit();
      tok_pass<T0>();
      release_oin();
      int x0, x1, y0, y1;
      uint32_t p0[16], p1[16];
      wg_wait<1>();
      pin(s0);
      pin(q0);
      row_pick<false>(s0, x0, x1);
      quad_pick<false>(x0, x1, 1);
      wg_wait<0>();
      pin(s1);
      pin(q1);
      row_pick<false>(s1, y0, y1);
      quad_pick<false>(x0, x1, 2);
      quad_pick<false>(y0, y1, 1);
      quad_pick<false>(y0, y1, 2);
      if (__builtin_expect(__any_sync(0xffffffffu, (x0 | x1 | y0 | y1) < 0), 0)) {
        fix_negative_rows(s0, x0, x1);
        fix_negative_rows(s1, y0, y1);
      }
      exp_rows<EXP_CH>(s0, p0, x0, x1, mk_addr, never);
      exp_rows<EXP_CH>(s1, p1, y0, y1, mk_addr, never);
      float o0[28], o1[28];
      wg_fence();
      SF;
      tok_wait<T4>();
      issue_p(o0, p0, kd + ((96 * 128) >> 4));
      issue_p(o1, p1, kd + ((144 * 128) >> 4));
      tok_pass<T7>();
      mbar_wait(bar + B_OEMPTY, ph);
      uint32_t f0[12], f1[12];
      wg_wait<1>();
      pin(o0);
      pin(p0);
      normalize<24, 0>(o0, f0);
      st_async<0>(oin_rem, bar_rem + B_OFULL, f0[0], f0[2], f0[4], f0[6]);
      st_async<1536>(oin_rem, bar_rem + B_OFULL, f0[1], f0[3], f0[5], f0[7]);
      wg_wait<0>();
      pin(o1);
      pin(p1);
      normalize<0, 4>(o1, f1);
      st_async<512>(oin_rem, bar_rem + B_OFULL, f0[8], f0[10], f1[0], f1[2]);
      st_async<2048>(oin_rem, bar_rem + B_OFULL, f0[9], f0[11], f1[1], f1[3]);
      st_async<1024>(oin_rem, bar_rem + B_OFULL, f1[4], f1[6], f1[8], f1[10]);
      st_async<2560>(oin_rem, bar_rem + B_OFULL, f1[5], f1[7], f1[9], f1[11]);
      pin(f0);
      pin(f1);
      float (&oa)[48] = qa;
      int wn1 = 0, wn2 = 0;
      if ((unsigned)(win - 2 * ncl) >= (unsigned)(base - 4 * ncl)) {
        if (win < 2 * ncl) {
          mbar_wait(bars + B_WO, 0);
        } else {
          read_ticket();
          wn1 = window(win + ncl), wn2 = window(win + 2 * ncl);
        }
      }
      const bool last = wn1 >= NWIN;
      if (!last) tok_wait<T1>();
      wg_fence();
#pragma unroll
      for (int ks = 0; ks < 3; ks++) {
        uint64_t db = mkdesc(LO_WO + ks * 64, HI_W);
        if (ks == 0) mma_o_init(oa, f0[0], f0[1], f0[2], f0[3], db);
        else mma_o(oa, f0[4 * ks], f0[4 * ks + 1], f0[4 * ks + 2], f0[4 * ks + 3], db);
      }
#pragma unroll
      for (int ks = 0; ks < 3; ks++)
        mma_o(oa, f1[4 * ks], f1[4 * ks + 1], f1[4 * ks + 2], f1[4 * ks + 3], mkdesc(LO_WO + (3 + ks) * 64, HI_W));
      mbar_wait(bar + B_OFULL, ph);
      asm volatile("fence.proxy.async::generic.acquire.sync_restrict::shared::cluster.cluster;" ::: "memory");
      wg_fence();
#pragma unroll
      for (int ks = 0; ks < 6; ks++)
        mma_q(oa, mkdesc(ua + LO_O + (((ks >> 1) * 512 + (ks & 1) * 32) >> 4), HI_O), mkdesc(LO_WO + (18432 >> 4) + ks * 64, HI_W));
      wg_commit();
      if (!last) tok_pass<T2>();
      load_mask(win >> 20);
      wg_wait<0>();
      pin(oa);
      pin(f0);
      pin(f1);
#pragma unroll
      for (int jj = 0; jj < 6; jj++)
        stsm4((jj & 1 ? ost ^ (32 + (win >> 20)) : ost) + (jj >> 1) * 512, pack_bf16(oa[8 * jj], oa[8 * jj + 1]), pack_bf16(oa[8 * jj + 2], oa[8 * jj + 3]),
              pack_bf16(oa[8 * jj + 4], oa[8 * jj + 5]), pack_bf16(oa[8 * jj + 6], oa[8 * jj + 7]));
      if (wn2 >= NWIN) {
        if (!last) {
          tok_wait<T3>();
          tok_pass<T4>();
          tok_pass<T5>();
          tok_wait<T7>();
        }
        break;
      }
      wg_fence();
      tok_wait<T3>();
      issue_q(ua, true, win);
      clamp_mask();
    }
    store_out(window(win));
    asm volatile("cp.async.bulk.wait_group.read 0;" ::: "memory");
    __syncwarp();
  }
}

typedef CUresult (*EncodeFn)(CUtensorMap*, CUtensorMapDataType, cuuint32_t, void*, const cuuint64_t*, const cuuint64_t*,
                             const cuuint32_t*, const cuuint32_t*, CUtensorMapInterleave, CUtensorMapSwizzle,
                             CUtensorMapL2promotion, CUtensorMapFloatOOBfill);

void encode_map(EncodeFn encode, CUtensorMap* m, void* p, int rank, const cuuint64_t* dim, const cuuint64_t* str,
                const cuuint32_t* box, CUtensorMapSwizzle sw,
                CUtensorMapL2promotion promo = CU_TENSOR_MAP_L2_PROMOTION_L2_128B) {
  const cuuint32_t es[5] = {1, 1, 1, 1, 1};
  CUresult r = encode(m, CU_TENSOR_MAP_DATA_TYPE_BFLOAT16, rank, p, dim, str, box, es, CU_TENSOR_MAP_INTERLEAVE_NONE, sw,
                      promo, CU_TENSOR_MAP_FLOAT_OOB_FILL_NONE);
  if (r != CUDA_SUCCESS) fprintf(stderr, "tensor map encode failed: %d\n", (int)r);
}

}

extern "C" void kernel_launch(void* const* d_in, const int* in_sizes, int n_in, void* d_out, int out_size) {
  static EncodeFn encode = nullptr;
  static int grid = 0;
  if (!encode) {
    cudaDriverEntryPointQueryResult qr;
    void* fn = nullptr;
    cudaGetDriverEntryPoint("cuTensorMapEncodeTiled", &fn, cudaEnableDefault, &qr);
    encode = (EncodeFn)fn;
    cudaFuncSetAttribute(swin_attn_kernel, cudaFuncAttributeMaxDynamicSharedMemorySize, SMEM_BYTES);
    cudaLaunchConfig_t cfg = {};
    cfg.gridDim = dim3(132);
    cfg.blockDim = dim3(384);
    cfg.dynamicSmemBytes = SMEM_BYTES;
    cudaLaunchAttribute at;
    at.id = cudaLaunchAttributeClusterDimension;
    at.val.clusterDim.x = 2;
    at.val.clusterDim.y = 1;
    at.val.clusterDim.z = 1;
    cfg.attrs = &at;
    cfg.numAttrs = 1;
    int ncl = 0;
    if (cudaOccupancyMaxActiveClusters(&ncl, swin_attn_kernel, &cfg) != cudaSuccess || ncl < 1) {
      (void)cudaGetLastError();
      ncl = 66;
    }
    if (ncl > 256) ncl = 256;
    grid = 2 * ncl;
  }
  Maps maps;
  {
    const cuuint64_t dim[5] = {64, 2, 512, 3, 256}, str[4] = {384, 512 * 384, 128, 768};
    const cuuint32_t box[5] = {64, 2, 4, 3, 2};
    encode_map(encode, &maps.x, d_in[0], 5, dim, str, box, CU_TENSOR_MAP_SWIZZLE_128B);
  }
  {
    const cuuint64_t dim[5] = {64, 4, 2, 4, 8192}, str[4] = {1024, 128, 256, 4096};
    const cuuint32_t box[5] = {64, 4, 2, 4, 1};
    encode_map(encode, &maps.mask, d_in[5], 5, dim, str, box, CU_TENSOR_MAP_SWIZZLE_128B);
  }
  {
    const cuuint64_t dim[3] = {64, 768, 512}, str[2] = {256, 512 * 384};
    const cuuint32_t box[3] = {64, 6, 4};
    encode_map(encode, &maps.xpf, d_in[0], 3, dim, str, box, CU_TENSOR_MAP_SWIZZLE_NONE, CU_TENSOR_MAP_L2_PROMOTION_L2_256B);
    const cuuint64_t dim2[3] = {64, 16, 8192}, str2[2] = {256, 4096};
    const cuuint32_t box2[3] = {64, 16, 1};
    encode_map(encode, &maps.mpf, d_in[5], 3, dim2, str2, box2, CU_TENSOR_MAP_SWIZZLE_NONE, CU_TENSOR_MAP_L2_PROMOTION_L2_256B);
  }
  {
    const cuuint64_t dim[5] = {32, 2, 512, 6, 256}, str[4] = {384, 512 * 384, 64, 768};
    const cuuint32_t box[5] = {32, 2, 4, 3, 2};
    encode_map(encode, &maps.out, d_out, 5, dim, str, box, CU_TENSOR_MAP_SWIZZLE_64B);
  }
  {
    const cuuint64_t dim[3] = {32, 192, 18}, str[2] = {576 * 2, 64};
    const cuuint32_t box[3] = {32, 192, 1};
    encode_map(encode, &maps.wqkv, d_in[1], 3, dim, str, box, CU_TENSOR_MAP_SWIZZLE_64B);
    const cuuint64_t dim2[3] = {32, 192, 6}, str2[2] = {192 * 2, 64};
    const cuuint32_t box2[3] = {32, 96, 3};
    encode_map(encode, &maps.wo, d_in[2], 3, dim2, str2, box2, CU_TENSOR_MAP_SWIZZLE_64B);
    const cuuint64_t dim3_[5] = {192, 2, 4, 4, 6}, str3[4] = {384, 8 * 384, 2 * 384, 32 * 384};
    const cuuint32_t box3[5] = {32, 2, 4, 4, 3};
    encode_map(encode, &maps.wop, d_in[2], 5, dim3_, str3, box3, CU_TENSOR_MAP_SWIZZLE_64B);
  }
  swin_attn_kernel<<<grid, 384, SMEM_BYTES>>>(maps, (const __nv_bfloat16*)d_in[3], (const int*)d_in[4], NWIN / (grid / 2) * (grid / 2), 0);
}
```
